```python
import torch

def _softmax(x, axis=-1):
    return torch.softmax(x, dim=axis)
def _gelu(x):
    return torch.nn.functional.gelu(x, approximate="tanh")
def _silu(x):
    return torch.nn.functional.silu(x)
def _sigmoid(x):
    return torch.sigmoid(x)
def _layernorm(x, axis=-1, eps=1e-5):
    m = x.mean(dim=axis, keepdim=True)
    v = x.var(dim=axis, keepdim=True, unbiased=False)
    return (x - m) / torch.sqrt(v + eps)
def _scatter_add(tgt, idx, src, axis=0):
    return tgt.clone().index_add_(axis, idx, src)
def _segment_sum(src, seg, n):
    out = torch.zeros((n,) + src.shape[1:], dtype=src.dtype)
    return out.index_add_(0, seg, src)
def _pad(x, pw):
    flat = tuple(v for pair in reversed(pw) for v in pair)
    return torch.nn.functional.pad(x, flat)

kernel_name = 'sequential_preLN__linear_kernel_hedgehog__moe_arch_mod__prompt'

def setup_inputs():

    _w = (lambda a: (lambda t: t.to(torch.bfloat16) if t.is_floating_point() else t)(torch.as_tensor(a)))
    def _A_setup():
        B, S, D, H = 1, 2048, 1024, 32
        Dh = D // H
        return {
            "x": _w((lambda *s: torch.randn(*s, dtype=torch.bfloat16) * 0.05)(B, S, D)),
            "wqkv": _w((lambda *s: torch.randn(*s, dtype=torch.bfloat16) * 0.2)(D, 3 * D)),
            "w_phi": _w((lambda *s: torch.randn(*s, dtype=torch.bfloat16) * 0.2)(H, Dh, Dh) * (Dh ** -0.5)),
            "wo": _w((lambda *s: torch.randn(*s, dtype=torch.bfloat16) * 0.05)(D, D)),
        }
    _A_in = _A_setup()

    def _B_setup():
        B, S, D, F, C = 1, 2048, 1024, 3584, 1
        return {
            "x": _w((lambda *s: torch.randn(*s, dtype=torch.bfloat16) * 0.05)(B, S, D)),
            "w_r": _w((lambda *s: torch.randn(*s, dtype=torch.bfloat16) * 0.1)(D)),
            "w_gate": _w((lambda *s: torch.randn(*s, dtype=torch.bfloat16) * 0.05)(D, F)),
            "w_up": _w((lambda *s: torch.randn(*s, dtype=torch.bfloat16) * 0.05)(D, F)),
            "w_down": _w((lambda *s: torch.randn(*s, dtype=torch.bfloat16) * 0.05)(F, D)),
        }
    _B_in = _B_setup()

    return {
        "A_x": _A_in["x"],
        "A_wqkv": _A_in["wqkv"],
        "A_w_phi": _A_in["w_phi"],
        "A_wo": _A_in["wo"],
        "B_x": _B_in["x"],
        "B_w_r": _B_in["w_r"],
        "B_w_gate": _B_in["w_gate"],
        "B_w_up": _B_in["w_up"],
        "B_w_down": _B_in["w_down"],
    }

def reference(A_x, A_wqkv, A_w_phi, A_wo, B_x, B_w_r, B_w_gate, B_w_up, B_w_down):
    def _A_ref(x, wqkv, w_phi, wo):
        B, S, D = x.shape
        H = 32; Dh = D // H
        qkv = (lambda x, *d: x.permute(*d))((x @ wqkv).reshape(B, S, 3, H, Dh), 2, 0, 3, 1, 4)
        q, k, v = qkv[0], qkv[1], qkv[2]
        pq = torch.einsum("bhsd,hdf->bhsf", q, w_phi)
        pk = torch.einsum("bhsd,hdf->bhsf", k, w_phi)
        phi_q = torch.concatenate([_softmax(pq, axis=-1), _softmax(-pq, axis=-1)], axis=-1)
        phi_k = torch.concatenate([_softmax(pk, axis=-1), _softmax(-pk, axis=-1)], axis=-1)
        kv = torch.einsum("bhsf,bhsd->bhfd", phi_k, v)
        z  = torch.einsum("bhsf->bhf", phi_k)
        num = torch.einsum("bhqf,bhfd->bhqd", phi_q, kv)
        den = torch.einsum("bhqf,bhf->bhq", phi_q, z)[..., None] + 1e-6
        o = num / den
        return (lambda x, *d: x.permute(*d))(o, 0, 2, 1, 3).reshape(B, S, D) @ wo

    def _B_ref(x, w_r, w_gate, w_up, w_down):
        B, S, D = x.shape
        C = 1
        r = x @ w_r
        idx = torch.argsort(-r, axis=-1)[:, :C]
        idx_e = (lambda x, n, axis: torch.repeat_interleave(x, n, dim=axis))(idx.reshape(B, C, 1), D, axis=2)
        x_sel = (lambda x, i, axis: torch.take_along_dim(x, i, dim=axis))(x, idx_e, axis=1)
        g = _silu(x_sel @ w_gate)
        u = x_sel @ w_up
        y = (g * u) @ w_down
        r_sel = _sigmoid((lambda x, i, axis: torch.take_along_dim(x, i, dim=axis))(r, idx, axis=1))
        y = y * r_sel.reshape(B, C, 1)
        b_off = (torch.arange(B) * S).reshape(B, 1)
        flat_idx = (idx + b_off).reshape(B * C)
        zero = (x * 0.0).reshape(B * S, D)
        upd = _scatter_add(zero, flat_idx, y.reshape(B * C, D), axis=0)
        return x + upd.reshape(B, S, D)

    x = A_x
    h = x + _A_ref(_layernorm(x, axis=-1), A_wqkv, A_w_phi, A_wo)
    h2 = h + _B_ref(_layernorm(h, axis=-1), B_w_r, B_w_gate, B_w_up, B_w_down)
    return h2
```

```cpp
#include <cuda_runtime.h>
#include <cuda_bf16.h>
#include <cuda.h>
#include <stdint.h>

namespace {

constexpr int SEQ = 2048, DM = 1024, FF = 3584;
constexpr int NCTA = 128, NTHREADS = 512, NFFN = 112;
constexpr int SPIN = 1 << 17;
constexpr int QG = 0;
constexpr int QG2 = 0;
constexpr int RSTQ = 3;
constexpr int ORST = 1;
constexpr int PSPL = 1;
constexpr int EXPV = 0;
constexpr int PIN = 0;

constexpr uint32_t SLOT = 16384;
constexpr uint32_t OFF_MISC = 13 * SLOT;
constexpr uint32_t OFF_PHIK = OFF_MISC;
constexpr uint32_t OFF_PHIQ = OFF_MISC + 4096;
constexpr uint32_t OFF_ONES = OFF_MISC + 12288;
constexpr uint32_t OFF_RSTAT = OFF_MISC + 13312;
constexpr uint32_t OFF_CS = OFF_MISC + 15360;
constexpr uint32_t OFF_WR = OFF_MISC + 16384;
constexpr uint32_t OFF_BAR = OFF_MISC + 16896;
constexpr uint32_t OFF_RED = OFF_MISC + 18304;
constexpr uint32_t SMEM_BYTES = OFF_MISC + 19456;

enum {
  B_FKV = 0, B_DKV = 16, B_FQ = 32, B_DQ = 48,
  B_PHI = 64, B_RESET = 65, B_RESET2 = 66, B_ROW = 67, B_FX = 68, B_REL = 72,
  B_FB = 80, B_DC = 96, B_QD = 112, B_STAT = 114,
  B_KVFREE = 120, B_QGO = 121, B_QGO2 = 122, B_CSD = 123, B_XDONE = 124, B_F1 = 126, B_KVRDY = 127,
  B_FS = 128, B_RELD = 142, B_FW = 144
};
constexpr unsigned long long MISC_COUNTS = 0x0802020203020202ull;

struct Params {
  CUtensorMap mX, mW, mWo, mPhi, mWg, mWu, mWs, mWd, mOut, mWgP, mWuP;
  const __nv_bfloat16 *x, *wqkv, *wo, *wr, *wg, *wu, *wd;
  __nv_bfloat16* out;
};

__device__ unsigned g_epoch;
__device__ __align__(128) uint4 g_rowstat[SEQ];
__device__ __align__(128) uint2 g_colsum[4][3 * DM];
__device__ __align__(128) uint4 g_kvp[32][8][3][128];
__device__ __align__(128) uint4 g_kvr[32][3][128];
__device__ __align__(128) uint4 g_o[128][16][4][32];
__device__ __align__(128) uint4 g_hstat[16][8][128];
__device__ __align__(128) uint4 g_cand[16][512];
__device__ __align__(128) uint2 g_candx[16][512];
__device__ __align__(128) uint2 g_key[8][16][4];
__device__ __align__(128) uint2 g_ypart[128][NFFN][8];

__device__ __forceinline__ uint32_t smem_u32(const void* p) { return (uint32_t)__cvta_generic_to_shared(p); }
__device__ __forceinline__ bool elect() {
  uint32_t p;
  asm volatile("{\n.reg .pred P;\nelect.sync _|P, 0xffffffff;\nselp.u32 %0, 1, 0, P;\n}\n" : "=r"(p));
  return p != 0;
}
__device__ __forceinline__ void mbar_init(uint32_t bar, uint32_t cnt) { asm volatile("mbarrier.init.shared::cta.b64 [%0], %1;" :: "r"(bar), "r"(cnt)); }
__device__ __forceinline__ void mbar_expect_tx(uint32_t bar, uint32_t bytes) { asm volatile("mbarrier.arrive.expect_tx.shared::cta.b64 _, [%0], %1;" :: "r"(bar), "r"(bytes) : "memory"); }
__device__ __forceinline__ void mbar_arrive(uint32_t bar) { asm volatile("mbarrier.arrive.shared::cta.b64 _, [%0];" :: "r"(bar) : "memory"); }
__device__ __forceinline__ void prefetch_map(const CUtensorMap* m) { asm volatile("prefetch.tensormap [%0];" :: "l"(m) : "memory"); }
__device__ __forceinline__ void mbar_wait(uint32_t bar) {
#pragma unroll 1
  for (int it = 0; it < SPIN; it++) {
    uint32_t ok;
    asm volatile("{\n.reg .pred p;\nmbarrier.try_wait.parity.shared::cta.b64 p, [%1], 0;\nselp.u32 %0, 1, 0, p;\n}\n" : "=r"(ok) : "r"(bar) : "memory");
    if (ok) break;
  }
}
__device__ __forceinline__ bool mbar_test(uint32_t bar) {
  uint32_t ok;
  asm volatile("{\n.reg .pred p;\nmbarrier.test_wait.parity.shared::cta.b64 p, [%1], 0;\nselp.u32 %0, 1, 0, p;\n}\n" : "=r"(ok) : "r"(bar) : "memory");
  return ok != 0;
}
__device__ __forceinline__ void tma_load_2d(uint32_t dst, const CUtensorMap* m, uint32_t bar, int c0, int c1) {
  asm volatile("cp.async.bulk.tensor.2d.shared::cluster.global.mbarrier::complete_tx::bytes [%0], [%1, {%3, %4}], [%2];"
    :: "r"(dst), "l"(m), "r"(bar), "r"(c0), "r"(c1) : "memory");
}
__device__ __forceinline__ void tma_load_2d_ef(uint32_t dst, const CUtensorMap* m, uint32_t bar, int c0, int c1) {
  uint64_t pol;
  asm("createpolicy.fractional.L2::evict_first.b64 %0, 1.0;" : "=l"(pol));
  asm volatile("cp.async.bulk.tensor.2d.shared::cluster.global.mbarrier::complete_tx::bytes.L2::cache_hint [%0], [%1, {%3, %4}], [%2], %5;"
    :: "r"(dst), "l"(m), "r"(bar), "r"(c0), "r"(c1), "l"(pol) : "memory");
}
__device__ __forceinline__ void tma_store_2d(const CUtensorMap* m, uint32_t src, int c0, int c1) {
  asm volatile("cp.async.bulk.tensor.2d.global.shared::cta.bulk_group [%0, {%2, %3}], [%1];"
    :: "l"(m), "r"(src), "r"(c0), "r"(c1) : "memory");
}
__device__ __forceinline__ void cp_async16(uint32_t dst, const void* src) { asm volatile("cp.async.cg.shared.global [%0], [%1], 16;" :: "r"(dst), "l"(src) : "memory"); }
__device__ __forceinline__ void cp_commit() { asm volatile("cp.async.commit_group;" ::: "memory"); }
template <int N> __device__ __forceinline__ void cp_wait() { asm volatile("cp.async.wait_group %0;" :: "n"(N) : "memory"); }
__device__ __forceinline__ void l2_prefetch(const void* src, uint32_t bytes) {
  asm volatile("cp.async.bulk.prefetch.L2.global [%0], %1;" :: "l"(src), "r"(bytes) : "memory");
}
__device__ __forceinline__ void wg_fence() { asm volatile("wgmma.fence.sync.aligned;" ::: "memory"); }
__device__ __forceinline__ void wg_commit() { asm volatile("wgmma.commit_group.sync.aligned;" ::: "memory"); }
template <int N> __device__ __forceinline__ void wg_wait() { asm volatile("wgmma.wait_group.sync.aligned %0;" :: "n"(N) : "memory"); }
__device__ __forceinline__ void fence_async_smem() { asm volatile("fence.proxy.async.shared::cta;" ::: "memory"); }
__device__ __forceinline__ void bar_sync(int id, int n) { asm volatile("bar.sync %0, %1;" :: "r"(id), "r"(n) : "memory"); }
__device__ __forceinline__ void bar_arrive(int id, int n) { asm volatile("bar.arrive %0, %1;" :: "r"(id), "r"(n) : "memory"); }
__device__ __forceinline__ uint64_t mk_desc(uint32_t addr, uint32_t lbo, uint32_t sbo, uint32_t swz) {
  return (uint64_t)((addr & 0x3FFFF) >> 4) | ((uint64_t)((lbo & 0x3FFFF) >> 4) << 16) | ((uint64_t)(sbo >> 4) << 32) | ((uint64_t)swz << 62);
}
__device__ __forceinline__ void stsm_x4(uint32_t addr, uint32_t r0, uint32_t r1, uint32_t r2, uint32_t r3) {
  asm volatile("stmatrix.sync.aligned.m8n8.x4.shared.b16 [%0], {%1, %2, %3, %4};" :: "r"(addr), "r"(r0), "r"(r1), "r"(r2), "r"(r3) : "memory");
}
__device__ __forceinline__ void stsm_x4_if(int c, uint32_t addr, uint32_t r0, uint32_t r1, uint32_t r2, uint32_t r3) {
  asm volatile("{\n.reg .pred p;\nsetp.ne.b32 p, %5, 0;\n@p stmatrix.sync.aligned.m8n8.x4.shared.b16 [%0], {%1, %2, %3, %4};\n}\n"
    :: "r"(addr), "r"(r0), "r"(r1), "r"(r2), "r"(r3), "r"(c) : "memory");
}
__device__ __forceinline__ void ldsm_x4(uint32_t& r0, uint32_t& r1, uint32_t& r2, uint32_t& r3, uint32_t addr) {
  asm volatile("ldmatrix.sync.aligned.m8n8.x4.shared.b16 {%0, %1, %2, %3}, [%4];" : "=r"(r0), "=r"(r1), "=r"(r2), "=r"(r3) : "r"(addr) : "memory");
}
__device__ __forceinline__ void ldsm_x4_t(uint32_t (&r)[4], uint32_t addr) {
  asm volatile("ldmatrix.sync.aligned.m8n8.x4.trans.shared.b16 {%0, %1, %2, %3}, [%4];" : "=r"(r[0]), "=r"(r[1]), "=r"(r[2]), "=r"(r[3]) : "r"(addr) : "memory");
}
__device__ __forceinline__ void mma_bf16(float* d, const uint32_t (&a)[4], uint32_t b0, uint32_t b1) {
  asm volatile("mma.sync.aligned.m16n8k16.row.col.f32.bf16.bf16.f32 {%0, %1, %2, %3}, {%4, %5, %6, %7}, {%8, %9}, {%0, %1, %2, %3};"
    : "+f"(d[0]), "+f"(d[1]), "+f"(d[2]), "+f"(d[3]) : "r"(a[0]), "r"(a[1]), "r"(a[2]), "r"(a[3]), "r"(b0), "r"(b1));
}
__device__ __forceinline__ uint32_t zero_after(uint32_t v) { uint32_t r; asm volatile("prmt.b32 %0, %1, 0, 0x4444;" : "=r"(r) : "r"(v)); return r; }
__device__ __forceinline__ int fresh_tid() { int v; asm volatile("mov.u32 %0, %%tid.x;" : "=r"(v)); return v; }
__device__ __forceinline__ void pin_order() { if (blockIdx.y) asm volatile("exit;"); }
__device__ __forceinline__ uint32_t pack_bf16(float lo, float hi) {
  uint32_t r; asm("cvt.rn.bf16x2.f32 %0, %1, %2;" : "=r"(r) : "f"(hi), "f"(lo)); return r;
}
__device__ __forceinline__ uint32_t pack_pin(float lo, float hi) {
  uint32_t r; asm volatile("cvt.rn.bf16x2.f32 %0, %1, %2;" : "=r"(r) : "f"(hi), "f"(lo)); return r;
}
__device__ __forceinline__ float bf_lo(uint32_t v) { return __uint_as_float(v << 16); }
__device__ __forceinline__ float bf_hi(uint32_t v) { return __uint_as_float(v & 0xFFFF0000u); }
__device__ __forceinline__ float bf_round(float v) { return bf_lo(pack_bf16(v, 0.f)); }
__device__ __forceinline__ float ex2(float v) { float r; asm("ex2.approx.ftz.f32 %0, %1;" : "=f"(r) : "f"(v)); return r; }
__device__ __forceinline__ float rsq(float v) { float r; asm("rsqrt.approx.ftz.f32 %0, %1;" : "=f"(r) : "f"(v)); return r; }
__device__ __forceinline__ float rcp(float v) { float r; asm("rcp.approx.ftz.f32 %0, %1;" : "=f"(r) : "f"(v)); return r; }
__device__ __forceinline__ void st_rec16(uint4* p, uint32_t a, uint32_t b, uint32_t c, uint32_t d) {
  asm volatile("{\n.reg .b128 r;\n.reg .b64 lo, hi;\nmov.b64 lo, {%1, %2};\nmov.b64 hi, {%3, %4};\nmov.b128 r, {lo, hi};\nst.relaxed.gpu.global.b128 [%0], r;\n}\n"
    :: "l"(p), "r"(a), "r"(b), "r"(c), "r"(d) : "memory");
}
__device__ __forceinline__ uint4 ld_rec16(const uint4* p) {
  uint4 v;
  asm volatile("{\n.reg .b128 r;\n.reg .b64 lo, hi;\nld.relaxed.gpu.global.b128 r, [%4];\nmov.b128 {lo, hi}, r;\nmov.b64 {%0, %1}, lo;\nmov.b64 {%2, %3}, hi;\n}\n"
    : "=r"(v.x), "=r"(v.y), "=r"(v.z), "=r"(v.w) : "l"(p) : "memory");
  return v;
}
__device__ __forceinline__ void st_rec8(uint2* p, uint32_t a, uint32_t b) {
  asm volatile("{\n.reg .b64 r;\nmov.b64 r, {%1, %2};\nst.relaxed.gpu.global.b64 [%0], r;\n}\n" :: "l"(p), "r"(a), "r"(b) : "memory");
}
__device__ __forceinline__ uint2 ld_rec8(const uint2* p) {
  uint2 v;
  asm volatile("{\n.reg .b64 r;\nld.relaxed.gpu.global.b64 r, [%2];\nmov.b64 {%0, %1}, r;\n}\n" : "=r"(v.x), "=r"(v.y) : "l"(p) : "memory");
  return v;
}
__device__ __forceinline__ unsigned ld_acquire(const unsigned* p) { unsigned v; asm volatile("ld.acquire.gpu.global.u32 %0, [%1];" : "=r"(v) : "l"(p) : "memory"); return v; }
__device__ __forceinline__ unsigned ld_relaxed(const unsigned* p) { unsigned v; asm volatile("ld.relaxed.gpu.global.u32 %0, [%1];" : "=r"(v) : "l"(p) : "memory"); return v; }
__device__ __forceinline__ void st_release(unsigned* p, unsigned v) { asm volatile("st.release.gpu.global.u32 [%0], %1;" :: "l"(p), "r"(v) : "memory"); }
__device__ __forceinline__ uint4 ldg_nc16(const void* p) {
  uint4 v; asm volatile("ld.global.nc.L1::no_allocate.v4.u32 {%0, %1, %2, %3}, [%4];" : "=r"(v.x), "=r"(v.y), "=r"(v.z), "=r"(v.w) : "l"(p)); return v;
}
__device__ __forceinline__ void stg16(void* p, uint4 v) { asm volatile("st.global.v4.u32 [%0], {%1, %2, %3, %4};" :: "l"(p), "r"(v.x), "r"(v.y), "r"(v.z), "r"(v.w) : "memory"); }
__device__ __forceinline__ float2 lds_f2(uint32_t a) { float2 v; asm volatile("ld.shared.v2.f32 {%0, %1}, [%2];" : "=f"(v.x), "=f"(v.y) : "r"(a)); return v; }
__device__ __forceinline__ float lds_f(uint32_t a) { float v; asm volatile("ld.shared.f32 %0, [%1];" : "=f"(v) : "r"(a)); return v; }
__device__ __forceinline__ uint32_t lds_u(uint32_t a) { uint32_t v; asm volatile("ld.shared.u32 %0, [%1];" : "=r"(v) : "r"(a)); return v; }
__device__ __forceinline__ uint4 lds_u4(uint32_t a) { uint4 v; asm volatile("ld.shared.v4.u32 {%0, %1, %2, %3}, [%4];" : "=r"(v.x), "=r"(v.y), "=r"(v.z), "=r"(v.w) : "r"(a)); return v; }
__device__ __forceinline__ void sts_f(uint32_t a, float v) { asm volatile("st.shared.f32 [%0], %1;" :: "r"(a), "f"(v) : "memory"); }
__device__ __forceinline__ void sts_f2(uint32_t a, float x, float y) { asm volatile("st.shared.v2.f32 [%0], {%1, %2};" :: "r"(a), "f"(x), "f"(y) : "memory"); }
__device__ __forceinline__ void sts_u2(uint32_t a, uint32_t x, uint32_t y) { asm volatile("st.shared.v2.u32 [%0], {%1, %2};" :: "r"(a), "r"(x), "r"(y) : "memory"); }
__device__ __forceinline__ void sts_u4(uint32_t a, uint32_t x, uint32_t y, uint32_t z, uint32_t w) { asm volatile("st.shared.v4.u32 [%0], {%1, %2, %3, %4};" :: "r"(a), "r"(x), "r"(y), "r"(z), "r"(w) : "memory"); }
__device__ __forceinline__ void sts_h(uint32_t a, uint32_t v) { asm volatile("st.shared.u16 [%0], %1;" :: "r"(a), "h"((uint16_t)v) : "memory"); }
__device__ __forceinline__ void sts_u(uint32_t a, uint32_t v) { asm volatile("st.shared.u32 [%0], %1;" :: "r"(a), "r"(v) : "memory"); }

template <int TA, int TB>
__device__ __forceinline__ void wg_n128(float (&d)[64], uint64_t da, uint64_t db, int sd) {
  asm volatile("{\n.reg .pred p;\nsetp.ne.b32 p, %66, 0;\n"
    "wgmma.mma_async.sync.aligned.m64n128k16.f32.bf16.bf16 {%0, %1, %2, %3, %4, %5, %6, %7, %8, %9, %10, %11, %12, %13, %14, %15, %16, %17, %18, %19, %20, %21, %22, %23, %24, %25, %26, %27, %28, %29, %30, %31, %32, %33, %34, %35, %36, %37, %38, %39, %40, %41, %42, %43, %44, %45, %46, %47, %48, %49, %50, %51, %52, %53, %54, %55, %56, %57, %58, %59, %60, %61, %62, %63}, %64, %65, p, 1, 1, %67, %68;\n}\n"
    : "+f"(d[0]), "+f"(d[1]), "+f"(d[2]), "+f"(d[3]), "+f"(d[4]), "+f"(d[5]), "+f"(d[6]), "+f"(d[7]), "+f"(d[8]), "+f"(d[9]), "+f"(d[10]), "+f"(d[11]), "+f"(d[12]), "+f"(d[13]), "+f"(d[14]), "+f"(d[15]), "+f"(d[16]), "+f"(d[17]), "+f"(d[18]), "+f"(d[19]), "+f"(d[20]), "+f"(d[21]), "+f"(d[22]), "+f"(d[23]), "+f"(d[24]), "+f"(d[25]), "+f"(d[26]), "+f"(d[27]), "+f"(d[28]), "+f"(d[29]), "+f"(d[30]), "+f"(d[31]), "+f"(d[32]), "+f"(d[33]), "+f"(d[34]), "+f"(d[35]), "+f"(d[36]), "+f"(d[37]), "+f"(d[38]), "+f"(d[39]), "+f"(d[40]), "+f"(d[41]), "+f"(d[42]), "+f"(d[43]), "+f"(d[44]), "+f"(d[45]), "+f"(d[46]), "+f"(d[47]), "+f"(d[48]), "+f"(d[49]), "+f"(d[50]), "+f"(d[51]), "+f"(d[52]), "+f"(d[53]), "+f"(d[54]), "+f"(d[55]), "+f"(d[56]), "+f"(d[57]), "+f"(d[58]), "+f"(d[59]), "+f"(d[60]), "+f"(d[61]), "+f"(d[62]), "+f"(d[63])
    : "l"(da), "l"(db), "r"(sd), "n"(TA), "n"(TB));
}

template <int TA, int TB, int O>
__device__ __forceinline__ void wg_n64(float (&d)[64], uint64_t da, uint64_t db, int sd) {
  asm volatile("{\n.reg .pred p;\nsetp.ne.b32 p, %34, 0;\n"
    "wgmma.mma_async.sync.aligned.m64n64k16.f32.bf16.bf16 {%0, %1, %2, %3, %4, %5, %6, %7, %8, %9, %10, %11, %12, %13, %14, %15, %16, %17, %18, %19, %20, %21, %22, %23, %24, %25, %26, %27, %28, %29, %30, %31}, %32, %33, p, 1, 1, %35, %36;\n}\n"
    : "+f"(d[O + 0]), "+f"(d[O + 1]), "+f"(d[O + 2]), "+f"(d[O + 3]), "+f"(d[O + 4]), "+f"(d[O + 5]), "+f"(d[O + 6]), "+f"(d[O + 7]), "+f"(d[O + 8]), "+f"(d[O + 9]), "+f"(d[O + 10]), "+f"(d[O + 11]), "+f"(d[O + 12]), "+f"(d[O + 13]), "+f"(d[O + 14]), "+f"(d[O + 15]), "+f"(d[O + 16]), "+f"(d[O + 17]), "+f"(d[O + 18]), "+f"(d[O + 19]), "+f"(d[O + 20]), "+f"(d[O + 21]), "+f"(d[O + 22]), "+f"(d[O + 23]), "+f"(d[O + 24]), "+f"(d[O + 25]), "+f"(d[O + 26]), "+f"(d[O + 27]), "+f"(d[O + 28]), "+f"(d[O + 29]), "+f"(d[O + 30]), "+f"(d[O + 31])
    : "l"(da), "l"(db), "r"(sd), "n"(TA), "n"(TB));
}

template <int TA, int TB>
__device__ __forceinline__ void wg_n40(float (&d)[20], uint64_t da, uint64_t db, int sd) {
  asm volatile("{\n.reg .pred p;\nsetp.ne.b32 p, %22, 0;\n"
    "wgmma.mma_async.sync.aligned.m64n40k16.f32.bf16.bf16 {%0, %1, %2, %3, %4, %5, %6, %7, %8, %9, %10, %11, %12, %13, %14, %15, %16, %17, %18, %19}, %20, %21, p, 1, 1, %23, %24;\n}\n"
    : "+f"(d[0]), "+f"(d[1]), "+f"(d[2]), "+f"(d[3]), "+f"(d[4]), "+f"(d[5]), "+f"(d[6]), "+f"(d[7]), "+f"(d[8]), "+f"(d[9]), "+f"(d[10]), "+f"(d[11]), "+f"(d[12]), "+f"(d[13]), "+f"(d[14]), "+f"(d[15]), "+f"(d[16]), "+f"(d[17]), "+f"(d[18]), "+f"(d[19])
    : "l"(da), "l"(db), "r"(sd), "n"(TA), "n"(TB));
}

template <int TA, int TB>
__device__ __forceinline__ void wg_n32(float (&d)[16], uint64_t da, uint64_t db, int sd) {
  asm volatile("{\n.reg .pred p;\nsetp.ne.b32 p, %18, 0;\n"
    "wgmma.mma_async.sync.aligned.m64n32k16.f32.bf16.bf16 {%0, %1, %2, %3, %4, %5, %6, %7, %8, %9, %10, %11, %12, %13, %14, %15}, %16, %17, p, 1, 1, %19, %20;\n}\n"
    : "+f"(d[0]), "+f"(d[1]), "+f"(d[2]), "+f"(d[3]), "+f"(d[4]), "+f"(d[5]), "+f"(d[6]), "+f"(d[7]), "+f"(d[8]), "+f"(d[9]), "+f"(d[10]), "+f"(d[11]), "+f"(d[12]), "+f"(d[13]), "+f"(d[14]), "+f"(d[15])
    : "l"(da), "l"(db), "r"(sd), "n"(TA), "n"(TB));
}

template <int TB>
__device__ __forceinline__ void wg_n40_rs(float (&d)[20], uint32_t a0, uint32_t a1, uint32_t a2, uint32_t a3, uint64_t db, int sd) {
  asm volatile("{\n.reg .pred p;\nsetp.ne.b32 p, %25, 0;\n"
    "wgmma.mma_async.sync.aligned.m64n40k16.f32.bf16.bf16 {%0, %1, %2, %3, %4, %5, %6, %7, %8, %9, %10, %11, %12, %13, %14, %15, %16, %17, %18, %19}, {%20, %21, %22, %23}, %24, p, 1, 1, %26;\n}\n"
    : "+f"(d[0]), "+f"(d[1]), "+f"(d[2]), "+f"(d[3]), "+f"(d[4]), "+f"(d[5]), "+f"(d[6]), "+f"(d[7]), "+f"(d[8]), "+f"(d[9]), "+f"(d[10]), "+f"(d[11]), "+f"(d[12]), "+f"(d[13]), "+f"(d[14]), "+f"(d[15]), "+f"(d[16]), "+f"(d[17]), "+f"(d[18]), "+f"(d[19])
    : "r"(a0), "r"(a1), "r"(a2), "r"(a3), "l"(db), "r"(sd), "n"(TB));
}

template <int TB>
__device__ __forceinline__ void wg_n32_rs(float (&d)[16], uint32_t a0, uint32_t a1, uint32_t a2, uint32_t a3, uint64_t db, int sd) {
  asm volatile("{\n.reg .pred p;\nsetp.ne.b32 p, %21, 0;\n"
    "wgmma.mma_async.sync.aligned.m64n32k16.f32.bf16.bf16 {%0, %1, %2, %3, %4, %5, %6, %7, %8, %9, %10, %11, %12, %13, %14, %15}, {%16, %17, %18, %19}, %20, p, 1, 1, %22;\n}\n"
    : "+f"(d[0]), "+f"(d[1]), "+f"(d[2]), "+f"(d[3]), "+f"(d[4]), "+f"(d[5]), "+f"(d[6]), "+f"(d[7]), "+f"(d[8]), "+f"(d[9]), "+f"(d[10]), "+f"(d[11]), "+f"(d[12]), "+f"(d[13]), "+f"(d[14]), "+f"(d[15])
    : "r"(a0), "r"(a1), "r"(a2), "r"(a3), "l"(db), "r"(sd), "n"(TB));
}

template <int TB>
__device__ __forceinline__ void wg_n128_rs(float (&d)[64], uint32_t a0, uint32_t a1, uint32_t a2, uint32_t a3, uint64_t db, int sd) {
  asm volatile("{\n.reg .pred p;\nsetp.ne.b32 p, %69, 0;\n"
    "wgmma.mma_async.sync.aligned.m64n128k16.f32.bf16.bf16 {%0, %1, %2, %3, %4, %5, %6, %7, %8, %9, %10, %11, %12, %13, %14, %15, %16, %17, %18, %19, %20, %21, %22, %23, %24, %25, %26, %27, %28, %29, %30, %31, %32, %33, %34, %35, %36, %37, %38, %39, %40, %41, %42, %43, %44, %45, %46, %47, %48, %49, %50, %51, %52, %53, %54, %55, %56, %57, %58, %59, %60, %61, %62, %63}, {%64, %65, %66, %67}, %68, p, 1, 1, %70;\n}\n"
    : "+f"(d[0]), "+f"(d[1]), "+f"(d[2]), "+f"(d[3]), "+f"(d[4]), "+f"(d[5]), "+f"(d[6]), "+f"(d[7]), "+f"(d[8]), "+f"(d[9]), "+f"(d[10]), "+f"(d[11]), "+f"(d[12]), "+f"(d[13]), "+f"(d[14]), "+f"(d[15]), "+f"(d[16]), "+f"(d[17]), "+f"(d[18]), "+f"(d[19]), "+f"(d[20]), "+f"(d[21]), "+f"(d[22]), "+f"(d[23]), "+f"(d[24]), "+f"(d[25]), "+f"(d[26]), "+f"(d[27]), "+f"(d[28]), "+f"(d[29]), "+f"(d[30]), "+f"(d[31]), "+f"(d[32]), "+f"(d[33]), "+f"(d[34]), "+f"(d[35]), "+f"(d[36]), "+f"(d[37]), "+f"(d[38]), "+f"(d[39]), "+f"(d[40]), "+f"(d[41]), "+f"(d[42]), "+f"(d[43]), "+f"(d[44]), "+f"(d[45]), "+f"(d[46]), "+f"(d[47]), "+f"(d[48]), "+f"(d[49]), "+f"(d[50]), "+f"(d[51]), "+f"(d[52]), "+f"(d[53]), "+f"(d[54]), "+f"(d[55]), "+f"(d[56]), "+f"(d[57]), "+f"(d[58]), "+f"(d[59]), "+f"(d[60]), "+f"(d[61]), "+f"(d[62]), "+f"(d[63])
    : "r"(a0), "r"(a1), "r"(a2), "r"(a3), "l"(db), "r"(sd), "n"(TB));
}


template <int N>
__device__ __forceinline__ void feature_shifted(float (&p)[16], const float (&p2)[16], float sc0, float sc1, uint32_t (&o)[N]) {
#pragma unroll 1
  for (int it = 0; it < N / 8; it++) {
    float e[16], s[2];
#pragma unroll
    for (int r = 0; r < 2; r++) {
      const float* x = p + 2 * r;
      const float sc = r ? sc1 : sc0;
      float mx = fmaxf(fmaxf(fmaxf(x[0], x[1]), fmaxf(x[4], x[5])), fmaxf(fmaxf(x[8], x[9]), fmaxf(x[12], x[13])));
      mx = fmaxf(mx, __shfl_xor_sync(0xffffffffu, mx, 1));
      mx = fmaxf(mx, __shfl_xor_sync(0xffffffffu, mx, 2));
      s[r] = 0.f;
#pragma unroll
      for (int i = 0; i < 8; i++) {
        const int n = (i >> 1) * 4 + 2 * r + (i & 1);
        e[n] = ex2((p[n] - mx) * sc);
        s[r] += e[n];
      }
      s[r] += __shfl_xor_sync(0xffffffffu, s[r], 1);
      s[r] += __shfl_xor_sync(0xffffffffu, s[r], 2);
      s[r] = rcp(s[r]);
    }
#pragma unroll
    for (int j = 0; j < N - 8; j++) o[j] = o[j + 8];
#pragma unroll
    for (int j = 0; j < 8; j++) o[N - 8 + j] = pack_bf16(e[2 * j] * s[j & 1], e[2 * j + 1] * s[j & 1]);
#pragma unroll
    for (int i = 0; i < 16; i++) p[i] = (N > 16 && (it & 1)) ? p2[i] : -p[i];
  }
}
template <bool FULL, class H>
__device__ __forceinline__ float feature_fast(const float* p, float sc0, float sc1, uint32_t* o, float (&sp)[2], H hook) {
  float e[16], r[8], sm[2] = {0.f, 0.f};
  sp[0] = 0.f; sp[1] = 0.f;
#pragma unroll
  for (int i = 0; i < 16; i++) e[i] = ex2(p[i] * ((i & 2) ? sc1 : sc0));
#pragma unroll
  for (int i = 0; i < 8; i++) {
    r[i] = rcp(e[2 * i] * e[2 * i + 1]);
    const float t = e[2 * i] + e[2 * i + 1];
    sp[i & 1] += t; sm[i & 1] = fmaf(t, r[i], sm[i & 1]);
  }
  const float tot = (sp[0] + sp[1]) + (sm[0] + sm[1]);
#pragma unroll
  for (int m = 1; m <= 2; m <<= 1)
#pragma unroll
    for (int i = 0; i < 2; i++) { sp[i] += __shfl_xor_sync(0xffffffffu, sp[i], m); sm[i] += __shfl_xor_sync(0xffffffffu, sm[i], m); }
  hook();
#pragma unroll
  for (int i = 0; i < 2; i++) {
    sm[i] = FULL ? rcp(sm[i]) : sp[i] * rcp(sm[i]);
    if (FULL) sp[i] = rcp(sp[i]);
  }
#pragma unroll
  for (int i = 0; i < 8; i++) {
    const float c = r[i] * sm[i & 1];
    o[i] = FULL ? pack_bf16(e[2 * i] * sp[i & 1], e[2 * i + 1] * sp[i & 1]) : pack_bf16(e[2 * i], e[2 * i + 1]);
    o[8 + i] = pack_bf16(e[2 * i + 1] * c, e[2 * i] * c);
  }
  return tot;
}
__device__ __forceinline__ bool warp_fails(bool ok) { return __builtin_expect(!__all_sync(0xffffffffu, ok), 0); }
constexpr uint32_t OTAG = 0x00010001u;
__device__ __forceinline__ void attn_out(const float (&u)[20], const float (&sp)[2], uint32_t tg, uint32_t sdst, uint4* dst) {
  const float d0 = rcp(fmaf(sp[0], 1e-6f, u[16])), d1 = rcp(fmaf(sp[1], 1e-6f, u[18]));
  uint32_t r[8];
#pragma unroll
  for (int j = 0; j < 8; j++) r[j] = pack_bf16(u[2 * j] * ((j & 1) ? d1 : d0), u[2 * j + 1] * ((j & 1) ? d1 : d0));
  r[0] = (r[0] & ~OTAG) | tg; r[4] = (r[4] & ~OTAG) | tg;
  st_rec16(dst, r[0], r[1], r[2], r[3]);
  st_rec16(dst + 32, r[4], r[5], r[6], r[7]);
  sts_u4(sdst, r[0], r[1], r[2], r[3]);
  sts_u4(sdst + 512, r[4], r[5], r[6], r[7]);
}

constexpr float L2E = 1.4426950408889634f;

__device__ __forceinline__ int pc_chunk(int j, int cb) {
  const int c = j > 8, e = j - 2 - 7 * c;
  return j < 2 ? 2 * cb + j : 2 * (e == cb ? 7 : e) + c;
}
constexpr unsigned long long Q_ASLOTS = 0x9763097630976309ull, Q_BSLOTS = 0x1854218542185421ull;
constexpr unsigned long long Q_CHUNKS = 0xBA9876543210EDCFull;
constexpr unsigned long long PC_ASLOTS = 0x20BA20BA20BA20BAull, PC_BSLOTS = 0x3756437564375643ull;
constexpr unsigned long long FFN_SLOTS = 0xBA9898C11987ull;
constexpr unsigned long long FFN_ORDER = 0xBA7654983210ull;
constexpr unsigned long long FFN_WAIT0 = 0x7C4B4A493F3F3E3Eull, FFN_WAIT1 = 0x6C6B8F8Eull;
constexpr unsigned long long FFN_PACE0 = 0x9499989392919044ull, FFN_PACE1 = 0x9A979695ull;
constexpr unsigned long long WO_WAIT0 = 0x626160483D3D3C3Cull, WO_WAIT1 = 0x6A69686766656463ull;
constexpr unsigned long long WO_PACE0 = 0x527F502Full, WO_PACE1 = 0x0ull;
constexpr int X_PACE = 81;
__device__ __forceinline__ uint32_t tab4(unsigned long long t, int i) { return (uint32_t)(t >> (4 * i)) & 15u; }
__device__ __forceinline__ uint32_t tab8(unsigned long long lo, unsigned long long hi, int i) { return (uint32_t)((i < 8 ? lo : hi) >> (8 * (i & 7))) & 255u; }

__device__ __forceinline__ float sum8(uint4 v) {
  return ((bf_lo(v.x) + bf_hi(v.x)) + (bf_lo(v.y) + bf_hi(v.y))) + ((bf_lo(v.z) + bf_hi(v.z)) + (bf_lo(v.w) + bf_hi(v.w)));
}
__device__ __forceinline__ void acc2(uint32_t v, float sh, float& s, float& q) {
  const float a = bf_lo(v) - sh, c = bf_hi(v) - sh;
  s += a + c; q = fmaf(a, a, fmaf(c, c, q));
}
__device__ __forceinline__ float warp_sum(float s) {
#pragma unroll
  for (int m = 16; m >= 1; m >>= 1) s += __shfl_xor_sync(0xffffffffu, s, m);
  return s;
}
__device__ __forceinline__ uint32_t ln_res(uint32_t h, float a, float c, uint32_t& n) {
  const float l = bf_lo(h), u = bf_hi(h);
  n = pack_bf16(fmaf(l, a, c), fmaf(u, a, c));
  return pack_bf16(l + bf_lo(n), u + bf_hi(n));
}

__device__ __forceinline__ uint64_t ext_a(uint32_t sb, uint32_t row) { return mk_desc(sb + 12 * SLOT + 4096 + row * 16, 4096 - row * 16, 128, 0); }
__device__ __forceinline__ uint64_t ext_b(uint32_t sb, uint32_t part) { return mk_desc(sb + 12 * SLOT + part * 2048, 1024, 0, 1); }
__device__ __forceinline__ uint32_t split_bf16(float v) { return pack_bf16(v, v - bf_round(v)); }

__global__ void __launch_bounds__(NTHREADS, 1) fused_kernel(const __grid_constant__ Params P) {
  extern __shared__ __align__(1024) uint8_t smem_raw[];
  const uint32_t sb = smem_u32(smem_raw);
  const uint32_t bars = sb + OFF_BAR;
  const int tid = threadIdx.x;
  const int wg = __shfl_sync(0xffffffffu, tid >> 7, 0);
  const int warp = __shfl_sync(0xffffffffu, (tid >> 5) & 3, 0);
  const int lane = tid & 31;
  const int b = (blockIdx.x & 1) * 64 + (blockIdx.x >> 1);
  const bool ffn = (blockIdx.x & 7) != 7;
  const int fi = blockIdx.x - (blockIdx.x >> 3);
  const int rbk = b >> 4, hp = b & 15;
  const int rb = b >> 3, cb = b & 7;
#define BAR(i) (bars + 8u * (uint32_t)(i))
#define MMA_IDS \
    const int tid = fresh_tid(), lane = tid & 31; \
    const bool leader = (tid & 127) == 0; \
    const uint32_t srow = (uint32_t)(warp * 16 + (lane & 7) + ((lane >> 3) & 1) * 8); \
    const uint32_t sx = (uint32_t)(lane >> 4) ^ (srow & 7); \
    const int c2 = (lane & 3) * 2, lr = warp * 16 + (lane >> 2); \
    (void)leader; (void)sx; (void)c2; (void)lr;

  auto load_kv = [&](int it) {
    const uint32_t s = sb + (uint32_t)(it & 3) * 3 * SLOT, fb = BAR(B_FKV + it);
    mbar_expect_tx(fb, 3 * SLOT);
    tma_load_2d(s, &P.mX, fb, it * 64, rb * 128);
    tma_load_2d(s + SLOT, &P.mX, fb, it * 64, (rb ^ 1) * 128);
    tma_load_2d(s + 2 * SLOT, &P.mW, fb, 1024 + hp * 64, it * 64);
    tma_load_2d(s + 2 * SLOT + 8192, &P.mW, fb, 2048 + hp * 64, it * 64);
  };
  auto prefetch = [&](int c) {
    if (c < 2) { l2_prefetch(P.wo + b * 8192 + c * 4096, 8192); return; }
    if (!ffn) return;
    const int e = c - 2;
    if (e < 16) {
      asm volatile("cp.async.bulk.prefetch.tensor.2d.L2.global.tile [%0, {%1, %2}];"
                   :: "l"((e & 1) ? &P.mWuP : &P.mWgP), "r"((fi >> 1) * 64), "r"((e >> 1) * 128 + (fi & 1) * 64) : "memory");
    } else {
      l2_prefetch(P.wd + (size_t)fi * 32768 + (e - 16) * 4096, 8192);
    }
  };

  {
    const int w16 = wg * 4 + warp;
    const uint32_t cnt = w16 == 14 ? 128u : ((0x300Cu >> w16) & 1u) + 1u;
    if (elect()) {
      if (w16 == 11) {
#pragma unroll
        for (int i = 0; i < 4; i++) mbar_init(BAR(B_FKV + i), 1u);
        asm volatile("fence.mbarrier_init.release.cluster;" ::: "memory");
        load_kv(0);
      }
#pragma unroll
      for (int i = 0; i < 8; i++)
        if (w16 || i >= 4) mbar_init(BAR(w16 * 8 + i), w16 == 15 ? (uint32_t)(MISC_COUNTS >> (8 * i)) & 255u : cnt);
      mbar_init(BAR(B_FS + w16), w16 >= 14 ? 2u : 1u);
      mbar_init(BAR(B_FW + w16), 1u);
      asm volatile("fence.mbarrier_init.release.cluster;" ::: "memory");
    }
    __syncwarp();
    if (w16 == 11 && elect()) {
#pragma unroll 1
      for (int i = 1; i < 4; i++) load_kv(i);
    }
    __syncwarp();
  }

  if (wg >= 2) {
    if (wg == 3) {
      asm volatile("setmaxnreg.dec.sync.aligned.u32 64;");
      asm volatile("barrier.sync 0;" ::: "memory");
        if (warp) {
          const int q = 3 * b + warp - 1, cg = q % 96, kq = q / 96;
          const uint32_t buf = sb + (warp == 3 ? OFF_PHIQ : 12 * SLOT + (warp - 1) * 8192);
          const uint32_t fb = BAR(B_FS + (warp - 1) * 4);
          mbar_wait(BAR(B_FKV + 5));
          if (elect()) {
#pragma unroll
            for (int p = 0; p < 2; p++) { mbar_expect_tx(fb + p * 8, 4096); tma_load_2d(buf + p * 4096, &P.mWs, fb + p * 8, cg * 32, kq * 256 + p * 64); }
          }
          float cs[8];
#pragma unroll
          for (int i = 0; i < 8; i++) cs[i] = 0.f;
          const unsigned ep = ld_relaxed(&g_epoch);
#pragma unroll 1
          for (int p = 0; p < 4; p++) {
            mbar_wait(fb + p * 8);
            uint4 v[8];
#pragma unroll
            for (int i = 0; i < 8; i++) v[i] = lds_u4(buf + (p & 1) * 4096 + i * 512 + lane * 16);
            if (p < 2) {
              uint32_t dep = 0;
#pragma unroll
              for (int i = 0; i < 8; i++) dep ^= v[i].x;
              const int n = p + 2 + (int)__shfl_sync(0xffffffffu, zero_after(dep), 0);
              if (elect()) {
                mbar_expect_tx(fb + n * 8, 4096);
                tma_load_2d(buf + (n & 1) * 4096, &P.mWs, fb + n * 8, cg * 32, kq * 256 + n * 64);
              }
            }
#pragma unroll
            for (int i = 0; i < 8; i += 2) {
              cs[0] += bf_lo(v[i].x) + bf_lo(v[i + 1].x); cs[1] += bf_hi(v[i].x) + bf_hi(v[i + 1].x);
              cs[2] += bf_lo(v[i].y) + bf_lo(v[i + 1].y); cs[3] += bf_hi(v[i].y) + bf_hi(v[i + 1].y);
              cs[4] += bf_lo(v[i].z) + bf_lo(v[i + 1].z); cs[5] += bf_hi(v[i].z) + bf_hi(v[i + 1].z);
              cs[6] += bf_lo(v[i].w) + bf_lo(v[i + 1].w); cs[7] += bf_hi(v[i].w) + bf_hi(v[i + 1].w);
            }
          }
          {
            const bool u4 = lane & 16, u2 = lane & 8, u1 = lane & 4;
#pragma unroll
            for (int i = 0; i < 4; i++) cs[i] = (u4 ? cs[4 + i] : cs[i]) + __shfl_xor_sync(0xffffffffu, u4 ? cs[i] : cs[4 + i], 16);
#pragma unroll
            for (int i = 0; i < 2; i++) cs[i] = (u2 ? cs[2 + i] : cs[i]) + __shfl_xor_sync(0xffffffffu, u2 ? cs[i] : cs[2 + i], 8);
            cs[0] = (u1 ? cs[1] : cs[0]) + __shfl_xor_sync(0xffffffffu, u1 ? cs[0] : cs[1], 4);
          }
          if (warp == 3 && elect()) {
            mbar_expect_tx(BAR(B_PHI), 12288);
            tma_load_2d(sb + OFF_PHIK, &P.mPhi, BAR(B_PHI), 0, hp * 64);
            tma_load_2d(sb + OFF_PHIQ, &P.mPhi, BAR(B_PHI), (int)zero_after(__float_as_uint(cs[0])), cb * 128);
            tma_load_2d(sb + OFF_PHIQ + 4096, &P.mPhi, BAR(B_PHI), (int)zero_after(__float_as_uint(cs[0])), cb * 128 + 64);
          }
          st_rec8(&g_colsum[kq][cg * 32 + (lane & 3) * 8 + (lane >> 2)], __float_as_uint(cs[0]), ep + 1);
          if (lane == 0) mbar_arrive(BAR(B_CSD));
        }
      asm volatile("setmaxnreg.dec.sync.aligned.u32 32;");
      if (warp == 0) {
#pragma unroll 1
        for (int it = 4; it < 16; it++) {
          mbar_wait(BAR(B_DKV + it - 4));
          if (elect()) load_kv(it);
        }
#pragma unroll 1
        for (int it = 0; it < 16; it++) {
          const uint32_t fb = BAR(B_FQ + it), s = sb + tab4(Q_BSLOTS, it) * SLOT;
          const int kc = (int)tab4(Q_CHUNKS, it) * 64;
          if (it == 5) mbar_wait(BAR(B_DKV + 15));
          mbar_wait(it >= 5 ? BAR(B_DQ + it - 5) : BAR(B_DKV + 12 + (it >> 1)));
          if (elect()) {
            mbar_expect_tx(fb, it < 4 ? SLOT : 2 * SLOT);
            if (it >= 4) tma_load_2d(sb + tab4(Q_ASLOTS, it) * SLOT, &P.mX, fb, kc, rb * 128);
            tma_load_2d(s, &P.mW, fb, cb * 128, kc);
            tma_load_2d(s + 8192, &P.mW, fb, cb * 128 + 64, kc);
          }
        }
        mbar_wait(BAR(B_DQ + 11));
        mbar_wait(BAR(X_PACE));
        if (elect()) {
          mbar_expect_tx(BAR(B_FX), 2 * SLOT);
          tma_load_2d(sb, &P.mX, BAR(B_FX), cb * 128, rb * 128);
          tma_load_2d(sb + 2 * SLOT, &P.mX, BAR(B_FX), cb * 128 + 64, rb * 128);
        }
      } else {
        if (warp == 1) {
#pragma unroll 1
          for (int j = 0; j < 16; j++) {
            const uint32_t s = sb + tab4(PC_BSLOTS, j) * SLOT, fb = BAR(B_FB + j);
            const int kc = pc_chunk(j, cb);
            mbar_wait(BAR(tab8(WO_WAIT0, WO_WAIT1, j)));
            mbar_wait(BAR(tab8(WO_PACE0, WO_PACE1, j)));
            if (elect()) {
              mbar_expect_tx(fb, SLOT);
              tma_load_2d(s, &P.mWo, fb, cb * 128, kc * 64);
              tma_load_2d(s + 8192, &P.mWo, fb, cb * 128 + 64, kc * 64);
            }
          }
        } else if (warp == 3) {
#pragma unroll 1
          for (int c = 0; c < 26; c++) {
            mbar_wait(BAR(c < 8 ? B_DKV + 8 + c : B_DQ + ((c - 8) >> 1)));
            if (elect()) prefetch(c);
          }
          mbar_wait(BAR(B_DC + 10));
#pragma unroll 1
          for (int i = 0; i < 4; i++) st_rec16(&g_hstat[rb][cb][i * 32 + lane], 0u, 0u, 0u, 0u);
          st_rec16(reinterpret_cast<uint4*>(&g_candx[rb][cb * 64]) + lane, 0u, 0u, 0u, 0u);
          if (lane < 2) st_rec16(reinterpret_cast<uint4*>(&g_key[cb][rb][0]) + lane, 0u, 0u, 0u, 0u);
          __syncwarp();
          if (lane == 0) mbar_arrive(BAR(B_RESET2));
        } else {
          mbar_wait(BAR(B_DQ + RSTQ));
#pragma unroll 1
          for (int i = 0; i < 12; i++) {
            st_rec16(&g_kvp[2 * hp][rbk][0][i * 32 + lane], 0u, 0u, 0u, 0u);
            st_rec16(&g_kvp[2 * hp + 1][rbk][0][i * 32 + lane], 0u, 0u, 0u, 0u);
          }
#pragma unroll 1
          for (int i = 0; i < 3; i++) st_rec16(&g_kvr[2 * hp + (lane >> 4)][i][rbk * 16 + (lane & 15)], 0u, 0u, 0u, 0u);
          __syncwarp();
          if (lane == 0) mbar_arrive(BAR(B_RESET));
          if (ffn) {
#pragma unroll 1
            for (int n = 0; n < 12; n++) {
              const int i = (int)tab4(FFN_ORDER, n);
              const uint32_t s = sb + tab4(FFN_SLOTS, i) * SLOT, fb = BAR(B_FW + i);
              mbar_wait(BAR(tab8(FFN_WAIT0, FFN_WAIT1, n)));
              mbar_wait(BAR(tab8(FFN_PACE0, FFN_PACE1, n)));
              if (elect()) {
                mbar_expect_tx(fb, SLOT);
                if (i < 8) tma_load_2d_ef(s, (i & 1) ? &P.mWu : &P.mWg, fb, fi * 32, (i >> 1) * 256);
                else {
#pragma unroll
                  for (int e = 0; e < 4; e++) tma_load_2d_ef(s + e * 4096, &P.mWd, fb, (i - 8) * 256 + e * 64, fi * 32);
                }
              }
            }
          }
        }
      }
    } else {
      asm volatile("barrier.sync 0;" ::: "memory");
      const int t = tid - 256;
      const unsigned tag = ld_relaxed(&g_epoch) + 1;
      if (warp == 0) {
        float s = 0.f;
#pragma unroll
        for (int i = 0; i < 4; i++) s += sum8(ldg_nc16(P.wr + i * 256 + lane * 8));
        const uint2 w = *reinterpret_cast<const uint2*>(P.wr + cb * 128 + lane * 4);
        s = warp_sum(s);
        if (lane == 0) { sts_f(sb + OFF_RED, s); sts_u(sb + OFF_RED + 4, tag); }
        sts_f2(sb + OFF_WR + lane * 16, bf_lo(w.x), bf_hi(w.x));
        sts_f2(sb + OFF_WR + lane * 16 + 8, bf_lo(w.y), bf_hi(w.y));
      }
      __syncwarp();
      uint4 xv[16];
#pragma unroll
      for (int i = 0; i < 16; i++) {
        if (i == 0) mbar_wait(BAR(B_FKV + 5));
        xv[i] = ldg_nc16(P.x + (size_t)(b * 16 + warp * 4 + (lane >> 3)) * DM + i * 64 + (lane & 7) * 8);
      }
      {
        const float sh = __shfl_sync(0xffffffffu, bf_lo(xv[0].x), lane & 24);
        float s0 = 0.f, q0 = 0.f, s1 = 0.f, q1 = 0.f;
#pragma unroll
        for (int i = 0; i < 16; i++) { acc2(xv[i].x, sh, s0, q0); acc2(xv[i].y, sh, s1, q1); acc2(xv[i].z, sh, s0, q0); acc2(xv[i].w, sh, s1, q1); }
        s0 += s1; q0 += q1;
#pragma unroll
        for (int m = 4; m >= 1; m >>= 1) { s0 += __shfl_xor_sync(0xffffffffu, s0, m); q0 += __shfl_xor_sync(0xffffffffu, q0, m); }
        s0 *= (1.f / DM);
        const float var = fmaxf(q0 * (1.f / DM) - s0 * s0, 0.f);
        if ((lane & 7) == 0) st_rec16(&g_rowstat[b * 16 + warp * 4 + (lane >> 3)], __float_as_uint(rsq(var + 1e-5f)), __float_as_uint(-(s0 + sh)), 0u, tag);
      }
      {
        const uint4* rp = &g_rowstat[rb * 128 + t];
        const uint4* rq = &g_rowstat[(rb ^ 1) * 128 + t];
        const uint2* c0 = &g_colsum[0][1024 + (t >> 6) * 1024 + hp * 64 + (t & 63)];
        const uint2* c1 = &g_colsum[0][cb * 128 + t];
        uint4 v0, v1; uint2 u[8];
#pragma unroll 1
        for (int it = 0; it < SPIN; it++) {
          v0 = ld_rec16(rp); v1 = ld_rec16(rq);
          bool ok = true;
#pragma unroll
          for (int i = 0; i < 4; i++) { u[i] = ld_rec8(c0 + i * 3072); u[4 + i] = ld_rec8(c1 + i * 3072); }
#pragma unroll
          for (int i = 0; i < 8; i++) ok = ok && u[i].y == tag;
          if (__all_sync(0xffffffffu, ok && v0.w == tag && v1.w == tag)) break;
          __nanosleep(100);
        }
        sts_u(sb + OFF_RSTAT + t * 8, v0.x); sts_u(sb + OFF_RSTAT + (t + 128) * 8, v1.x);
        mbar_wait(BAR(B_CSD));
        {
          const uint32_t m0 = split_bf16(__uint_as_float(v0.y)), m1 = split_bf16(__uint_as_float(v1.y));
          sts_u4(sb + 12 * SLOT + 4096 + t * 16, m0, m0 & 0xFFFFu, 0u, 0u);
          sts_u4(sb + 12 * SLOT + 6144 + t * 16, m1, m1 & 0xFFFFu, 0u, 0u);
          sts_u2(sb + 12 * SLOT + 8192 + t * 8, 0u, 0u);
        }
#pragma unroll
        for (int e = 0; e < 2; e++) {
          const uint32_t hl = split_bf16((__uint_as_float(u[4 * e].x) + __uint_as_float(u[4 * e + 1].x)) + (__uint_as_float(u[4 * e + 2].x) + __uint_as_float(u[4 * e + 3].x)));
          const uint32_t a = sb + 12 * SLOT + e * 2048 + (t >> 6) * 1024 + (t & 7) * 2, ch = (uint32_t)(t >> 3) & 7u;
#pragma unroll
          for (uint32_t r = 0; r < 8; r++) sts_h(a + r * 128 + ((ch ^ r) << 4), r < 2 ? hl : r == 2 ? hl >> 16 : 0u);
        }
        sts_u(sb + OFF_ONES + t * 4, 0x3F803F80u);
        sts_u(sb + OFF_ONES + 512 + t * 4, 0x3F803F80u);
        fence_async_smem();
        bar_sync(3, 128);
      }
      asm volatile("setmaxnreg.inc.sync.aligned.u32 160;");
      {
        float a0[64], a1[64];
        {
          wg_fence();
          wg_n128<0, 1>(a0, ext_a(sb, 0), ext_b(sb, 1), 0);
          wg_n128<0, 1>(a1, ext_a(sb, 64), ext_b(sb, 1), 0);
          wg_commit();
          wg_wait<0>();
          mbar_arrive(BAR(B_STAT));
        }
        {
          const bool leader = (tid & 127) == 0;
#pragma unroll 1
          for (int it = 12; it < 16; it++) mbar_wait(BAR(B_FKV + it));
          mbar_wait(BAR(B_QGO));
#pragma unroll 1
          for (int it = 0; it < 16; it++) {
            mbar_wait(BAR(B_FQ + it));
            const uint64_t da = mk_desc(sb + tab4(Q_ASLOTS, it) * SLOT, 16, 1024, 1), db = mk_desc(sb + tab4(Q_BSLOTS, it) * SLOT, 8192, 1024, 1);
#pragma unroll
            for (int hf = 0; hf < 2; hf++) {
              if (QG2 && 2 * it + hf == QG2) mbar_wait(BAR(B_QGO2));
              wg_fence();
#pragma unroll
              for (int kk = 2 * hf; kk < 2 * hf + 2; kk++) {
                wg_n128<0, 1>(a0, da + kk * 2, db + kk * 128, 1);
                wg_n128<0, 1>(a1, da + kk * 2 + 512, db + kk * 128, 1);
              }
              wg_commit();
              wg_wait<1>();
              if (hf == 0 && it > 0 && leader) mbar_arrive(BAR(B_DQ + it - 1));
            }
          }
          mbar_wait(BAR(B_KVFREE));
          wg_wait<0>();
          if (leader) mbar_arrive(BAR(B_DQ + 15));
        }
        MMA_IDS
#pragma unroll
        for (int c = 0; c < 2; c++) {
#pragma unroll
          for (int jj = 0; jj < 4; jj++)
#pragma unroll
            for (int mb = 0; mb < 2; mb++) {
              const float* a = mb ? &a1[32 * c + 8 * jj] : &a0[32 * c + 8 * jj];
              stsm_x4(sb + (10 + c) * SLOT + mb * 8192 + srow * 128 + ((sx ^ (2 * jj)) << 4),
                      pack_bf16(a[0], a[1]), pack_bf16(a[2], a[3]), pack_bf16(a[4], a[5]), pack_bf16(a[6], a[7]));
            }
          fence_async_smem();
          mbar_arrive(BAR(B_QD + c));
        }
      }
    }
    if (wg == 3) mbar_wait(BAR(B_DC + 15));
    asm volatile("setmaxnreg.inc.sync.aligned.u32 160;");
    const int w8 = (wg - 2) * 4 + warp;
    uint32_t wf[32][4], wd[16][4];
    if (ffn) {
      const int lane = fresh_tid() & 31;
      const uint32_t mrow = (uint32_t)((lane & 7) + (lane >> 4) * 8), mch = (uint32_t)(lane >> 3) & 1u;
      mbar_wait(BAR(B_FW + w8));
      const uint32_t wsm = sb + tab4(FFN_SLOTS, w8) * SLOT + mrow * 64;
      const uint32_t sw = (mrow >> 1) & 3;
#pragma unroll
      for (int i = 0; i < 16; i++) {
        ldsm_x4_t(wf[2 * i], wsm + i * 1024 + ((mch ^ sw) << 4));
        ldsm_x4_t(wf[2 * i + 1], wsm + i * 1024 + (((2 + mch) ^ sw) << 4));
      }
      uint32_t dep = 0;
#pragma unroll
      for (int i = 0; i < 32; i++) dep ^= wf[i][0];
      if (w8 < 4 && lane == 0) mbar_arrive(BAR(B_REL + w8) + zero_after(dep));
    } else if (w8 == 0 && elect()) {
      mbar_arrive(BAR(B_REL));
    }
    mbar_wait(BAR(B_XDONE));
    asm volatile("setmaxnreg.inc.sync.aligned.u32 224;");
    if (ffn) {
      const int lane = fresh_tid() & 31;
      const uint32_t mrow = (uint32_t)((lane & 7) + (lane >> 4) * 8), mch = (uint32_t)(lane >> 3) & 1u;
      mbar_wait(BAR(B_FW + 8 + (w8 >> 1)));
      const uint32_t dsm = sb + tab4(FFN_SLOTS, 8 + (w8 >> 1)) * SLOT + (w8 & 1) * 8192 + mrow * 128;
#pragma unroll
      for (int i = 0; i < 8; i++) {
        const uint32_t a = dsm + (i >> 2) * 4096 + ((((uint32_t)(i & 3) * 2 + mch) ^ (mrow & 7)) << 4);
        ldsm_x4_t(wd[2 * i], a);
        ldsm_x4_t(wd[2 * i + 1], a + 2048);
      }
      uint32_t dep = 0;
#pragma unroll
      for (int i = 0; i < 16; i++) dep ^= wd[i][0];
      if (w8 < 4 && lane == 0) mbar_arrive(BAR(B_RELD + (w8 >> 1)) + zero_after(dep));
      if (wg == 2) mbar_wait(BAR(B_DC + 12));
#pragma unroll
      for (int i = 0; i < 2; i++) st_rec16(reinterpret_cast<uint4*>(&g_ypart[w8 * 16 + i * 8 + (lane >> 2)][fi][0]) + (lane & 3), 0u, 0u, 0u, 0u);
      __syncwarp();
    }
    mbar_wait(BAR(B_DC + 15));
    {
      const int t = fresh_tid() - 256, lane = t & 31;
      const uint32_t xs = sb + OFF_PHIQ + w8 * 512;
      const unsigned tag = lds_u(sb + OFF_RED + 4);
      uint32_t wkey;
      {
        uint2 v;
#pragma unroll 1
        for (int it = 0; it < SPIN; it++) {
          v = ld_rec8(&g_key[cb][lane & 15][0]);
          if (__all_sync(0xffffffffu, v.y == tag)) break;
        }
        wkey = __reduce_max_sync(0xffffffffu, v.x);
      }
      const int wrow = (0xFFFF - (int)(wkey & 0xFFFFu)) & (SEQ - 1);
      {
        const uint4* src = reinterpret_cast<const uint4*>(&g_candx[wrow >> 7][(w8 >> 1) * 128]) + lane;
        uint4 v0, v1;
#pragma unroll 1
        for (int it = 0; it < SPIN; it++) {
          v0 = ld_rec16(src); v1 = ld_rec16(src + 32);
          if (__all_sync(0xffffffffu, v0.y == tag && v0.w == tag && v1.y == tag && v1.w == tag)) break;
        }
        const uint32_t a = xs + (lane >> 3) * 64 + (lane & 1) * 32 + ((lane >> 1) & 3) * 4;
        sts_u(a, v0.x); sts_u(a + 16, v0.z); sts_u(a + 256, v1.x); sts_u(a + 272, v1.z);
        __syncwarp();
      }
      if (t == 0) mbar_arrive(BAR(B_ROW));
      if (b == 0 && t == 0) g_epoch = tag;
      if (ffn) {
        {
          uint4 xb[8];
#pragma unroll
          for (int i = 0; i < 8; i++) xb[i] = lds_u4(xs + i * 64 + (lane & 3) * 16);
          float d[16];
#pragma unroll
          for (int i = 0; i < 16; i++) d[i] = 0.f;
#pragma unroll
          for (int i = 0; i < 8; i++) {
            mma_bf16(&d[0], wf[4 * i], xb[i].x, xb[i].y); mma_bf16(&d[4], wf[4 * i + 1], xb[i].x, xb[i].y);
            mma_bf16(&d[8], wf[4 * i + 2], xb[i].z, xb[i].w); mma_bf16(&d[12], wf[4 * i + 3], xb[i].z, xb[i].w);
          }
          const int c = lane & 3;
          const float v = c == 0 ? d[0] + d[8] : c == 1 ? d[2] + d[10] : c == 2 ? d[4] + d[12] : d[6] + d[14];
          sts_f(sb + OFF_CS + (uint32_t)(w8 * 32 + c * 8 + (lane >> 2)) * 4, v);
        }
        bar_sync(2, 256);
        uint32_t ab[4];
        {
          const uint32_t pr = sb + OFF_CS + lane * 4;
          const float g = (lds_f(pr) + lds_f(pr + 256)) + (lds_f(pr + 512) + lds_f(pr + 768));
          const float u = (lds_f(pr + 128) + lds_f(pr + 384)) + (lds_f(pr + 640) + lds_f(pr + 896));
          const float act = g * rcp(1.f + ex2(-g * L2E)) * u;
          const uint32_t pair = pack_bf16(act, __shfl_down_sync(0xffffffffu, act, 1));
#pragma unroll
          for (int i = 0; i < 4; i++) ab[i] = __shfl_sync(0xffffffffu, pair, i * 8 + (lane & 3) * 2);
        }
        float d[32];
#pragma unroll
        for (int i = 0; i < 32; i++) d[i] = 0.f;
        {
#pragma unroll
          for (int i = 0; i < 8; i++) mma_bf16(&d[4 * i], wd[2 * i], ab[0], ab[1]);
#pragma unroll
          for (int i = 0; i < 8; i++) mma_bf16(&d[4 * i], wd[2 * i + 1], ab[2], ab[3]);
        }
        const int c = lane & 3;
#pragma unroll
        for (int i = 0; i < 4; i++) {
          const float v = c == 0 ? d[8 * i] : c == 1 ? d[8 * i + 2] : c == 2 ? d[8 * i + 4] : d[8 * i + 6];
          st_rec8(&g_ypart[w8 * 16 + i * 4 + c][fi][lane >> 2], __float_as_uint(v), tag);
        }
      }
      float y0 = 0.f, y1 = 0.f;
      uint4 fin;
      if (w8 == 7) {
#pragma unroll 1
        for (int it = 0; it < SPIN; it++) {
          fin = ld_rec16(&g_cand[wrow >> 7][b * 4 + (lane & 3)]);
          if (__all_sync(0xffffffffu, fin.w == tag)) break;
        }
      } else {
        const uint4* yp = reinterpret_cast<const uint4*>(&g_ypart[b][0][0]) + t;
        uint4 v0, v1;
#pragma unroll 1
        for (int it = 0; it < SPIN; it++) {
          v0 = ld_rec16(yp); v1 = ld_rec16(yp + 2 * NFFN);
          if (__all_sync(0xffffffffu, v0.y == tag && v0.w == tag && v1.y == tag && v1.w == tag)) break;
        }
        y0 = __uint_as_float(v0.x) + __uint_as_float(v1.x); y1 = __uint_as_float(v0.z) + __uint_as_float(v1.z);
      }
#pragma unroll
      for (int m = 4; m <= 16; m <<= 1) { y0 += __shfl_xor_sync(0xffffffffu, y0, m); y1 += __shfl_xor_sync(0xffffffffu, y1, m); }
      if (lane < 4) sts_f2(sb + OFF_RED + 64 + (uint32_t)(w8 * 8 + lane * 2) * 4, y0, y1);
      uint32_t u = wkey >> 16;
      u = (u & 0x8000u) ? (u & 0x7FFFu) : (~u & 0xFFFFu);
      const float sig = rcp(1.f + ex2(-__uint_as_float(u << 16) * L2E));
      bar_sync(2, 256);
      if (w8 == 7) {
        float2 v = lds_f2(sb + OFF_RED + 64 + lane * 8);
#pragma unroll
        for (int m = 4; m <= 16; m <<= 1) { v.x += __shfl_xor_sync(0xffffffffu, v.x, m); v.y += __shfl_xor_sync(0xffffffffu, v.y, m); }
        if (lane < 4)
          *reinterpret_cast<uint32_t*>(P.out + (size_t)wrow * DM + b * 8 + lane * 2) =
              pack_bf16(bf_lo(fin.y) + fmaf(v.x, sig, bf_lo(fin.x)), bf_hi(fin.y) + fmaf(v.y, sig, bf_hi(fin.x)));
      }
    }
  } else {
    asm volatile("setmaxnreg.inc.sync.aligned.u32 160;");
    asm volatile("barrier.sync 0;" ::: "memory");
    {
      const bool leader = (tid & 127) == 0;
      {
        float a0[64], a1[64];
#pragma unroll 1
        for (int it = 0; it < 16; it++) {
          mbar_wait(BAR(B_FKV + it));
          const uint32_t s = sb + (uint32_t)(it & 3) * 3 * SLOT;
          const uint64_t da = mk_desc(s + wg * SLOT, 16, 1024, 1), db = mk_desc(s + 2 * SLOT, 8192, 1024, 1);
          wg_fence();
#pragma unroll
          for (int kk = 0; kk < 4; kk++) {
            wg_n128<0, 1>(a0, da + kk * 2, db + kk * 128, (it | kk) != 0);
            wg_n128<0, 1>(a1, da + kk * 2 + 512, db + kk * 128, (it | kk) != 0);
          }
          wg_commit();
          wg_wait<1>();
          if (it > 0 && leader) mbar_arrive(BAR(B_DKV + it - 1));
        }
        mbar_wait(BAR(B_STAT));
        wg_fence();
        wg_n128<0, 1>(a0, ext_a(sb, wg * 128), ext_b(sb, 0), 1);
        wg_n128<0, 1>(a1, ext_a(sb, wg * 128 + 64), ext_b(sb, 0), 1);
        wg_commit();
        if (QG == 0 && leader) mbar_arrive(BAR(B_QGO));
        mbar_wait(BAR(B_PHI));
        wg_wait<0>();
        if (leader) mbar_arrive(BAR(B_DKV + 15));
        if (QG == 1 && leader) mbar_arrive(BAR(B_QGO));
        if (PIN & 2) pin_order();
        if (EXPV == 1) asm volatile("setmaxnreg.inc.sync.aligned.u32 200;");
        MMA_IDS
        const uint32_t rs = sb + OFF_RSTAT + (uint32_t)(wg * 128 + lr) * 8;
        const uint32_t vt = sb + 12 * SLOT + wg * 4096 + srow * 64 + (((uint32_t)(lane >> 4) ^ ((srow >> 1) & 3)) << 4);
        float pa[16], pb[16];
        uint32_t vp[16];
        const uint64_t dw = mk_desc(sb + OFF_PHIK, 16, 512, 2);
        auto pack_v = [&](const float* a, int mb) {
          const float r0 = lds_f(rs + mb * 512), r1 = lds_f(rs + mb * 512 + 64);
#pragma unroll
          for (int i = 0; i < 16; i++) vp[i] = pack_bf16(a[32 + 2 * i] * ((i & 1) ? r1 : r0), a[33 + 2 * i] * ((i & 1) ? r1 : r0));
        };
        auto put_v = [&]() {
#pragma unroll
          for (int jj = 0; jj < 4; jj++) stsm_x4((vt + (jj >> 1) * 8192) ^ (32 * (jj & 1)), vp[4 * jj], vp[4 * jj + 1], vp[4 * jj + 2], vp[4 * jj + 3]);
        };
        bar_sync(1, 256);
        pack_v(a0, 0);
        put_v();
        auto logits = [&](const uint32_t (&k)[16]) {
          wg_fence();
          wg_n32_rs<1>(pa, k[0], k[1], k[2], k[3], dw, 0);
          wg_n32_rs<1>(pb, k[8], k[9], k[10], k[11], dw + 128, 0);
          wg_n32_rs<1>(pa, k[4], k[5], k[6], k[7], dw + 64, 1);
          wg_n32_rs<1>(pb, k[12], k[13], k[14], k[15], dw + 192, 1);
          wg_commit();
        };
        uint32_t k0[16], k1[16];
        pin_order();
#pragma unroll
        for (int i = 0; i < 16; i++) k0[i] = pack_pin(a0[2 * i], a0[2 * i + 1]);
        logits(k0);
        if (leader) mbar_arrive(BAR(B_QGO2));
#pragma unroll
        for (int i = 0; i < 16; i++) k1[i] = pack_pin(a1[2 * i], a1[2 * i + 1]);
        pack_v(a1, 1);
        wg_wait<0>();
        if (PIN & 1) pin_order();
        float kv[20];
        auto half = [&](float (&p0)[16], float (&p1)[16], int mb) {
          const float sc0 = lds_f(rs + mb * 512) * L2E, sc1 = lds_f(rs + mb * 512 + 64) * L2E;
          const uint32_t ft = sb + 10 * SLOT + wg * 8192 + srow * 128 + (sx << 4);
          uint32_t fo[32];
          auto put = [&](int h) {
#pragma unroll
            for (int g = 4 * h; g < 4 * h + 4; g++) stsm_x4((ft + h * SLOT) ^ (32 * (g & 3)), fo[4 * g], fo[4 * g + 1], fo[4 * g + 2], fo[4 * g + 3]);
          };
          float sp[2];
          float tot = feature_fast<true>(p0, sc0, sc1, &fo[0], sp, [&]() {
            if (mb) {
              wg_wait<0>();
              bar_arrive(6 + wg, 256);
            }
          });
          if (mb) {
            bar_sync(7 - wg, 256);
            put_v();
          }
          put(0);
          tot += feature_fast<true>(p1, sc0, sc1, &fo[16], sp, []() {});
          put(1);
          if (warp_fails(tot < 0x1p60f)) {
            feature_shifted(p0, p1, sc0, sc1, fo);
            put(0);
            put(1);
          }
          if (mb == 0) logits(k1);
          fence_async_smem();
          bar_sync(1, 256);
          if (PIN & 4) pin_order();
          const uint64_t d = mk_desc(sb + (10 + wg) * SLOT, 16, 1024, 1);
          const uint64_t e = mk_desc(sb + 12 * SLOT + wg * 8192, OFF_ONES - 12 * SLOT - wg * 8192, 512, 2);
          wg_fence();
#pragma unroll
          for (int kk = 0; kk < 8; kk++) wg_n40<1, 1>(kv, d + kk * 128, e + kk * (64 - (64 << 16)), (mb | kk) != 0);
          wg_commit();
        };
        half(pa, pb, 0);
        wg_wait<1>();
        half(pa, pb, 1);
        mbar_wait(BAR(B_RESET));
        const unsigned tag = lds_u(sb + OFF_RED + 4);
        uint4* dst = &g_kvp[2 * hp + wg][rbk][0][tid & 127];
        wg_wait<0>();
        if (PIN & 8) pin_order();
        kv[17] = kv[18];
#pragma unroll
        for (int i = 0; i < 3; i++)
          st_rec16(dst + i * 128, pack_bf16(kv[6 * i], kv[6 * i + 1]), pack_bf16(kv[6 * i + 2], kv[6 * i + 3]), pack_bf16(kv[6 * i + 4], kv[6 * i + 5]), tag);
        if (leader) mbar_arrive(BAR(B_KVFREE));
        if (wg == 0 && warp < 3) {
          const uint4* src = &g_kvp[2 * hp + (lane >> 4)][0][warp][rbk * 16 + (lane & 15)];
          uint4 a[8];
#pragma unroll 1
          for (int it = 0; it < SPIN; it++) {
            bool ok = true;
#pragma unroll
            for (int p = 0; p < 8; p++) a[p] = ld_rec16(src + p * 384);
#pragma unroll
            for (int p = 0; p < 8; p++) ok = ok && a[p].w == tag;
            if (__all_sync(0xffffffffu, ok)) break;
          }
          float v[6] = {0.f, 0.f, 0.f, 0.f, 0.f, 0.f};
#pragma unroll
          for (int p = 0; p < 8; p++) {
            v[0] += bf_lo(a[p].x); v[1] += bf_hi(a[p].x); v[2] += bf_lo(a[p].y); v[3] += bf_hi(a[p].y); v[4] += bf_lo(a[p].z); v[5] += bf_hi(a[p].z);
          }
          st_rec16(&g_kvr[2 * hp + (lane >> 4)][warp][rbk * 16 + (lane & 15)], pack_bf16(v[0], v[1]), pack_bf16(v[2], v[3]), pack_bf16(v[4], v[5]), tag);
        }
        if (ORST) {
#pragma unroll
          for (int i = 0; i < 8; i++) st_rec16(&g_o[rb * 8 + wg * 4 + warp][2 * cb][i][lane], 0u, 0u, 0u, 0u);
        }
      }
    }
    if (EXPV == 1) asm volatile("setmaxnreg.dec.sync.aligned.u32 160;");
    const uint32_t stg = sb + wg * 8192;
    float s0 = 0.f, q0 = 0.f, d0 = 0.f, s1 = 0.f, q1 = 0.f, d1 = 0.f;
    {
      MMA_IDS
      const unsigned tag = lds_u(sb + OFF_RED + 4);
      const uint32_t t3 = tag % 3u + 1u, tg = (t3 & 1u) | ((t3 & 2u) << 15);
      const int ln = __shfl_sync(0xffffffffu, lane, lane);
      uint4* const og = &g_o[rb * 8 + wg * 4 + warp][0][0][ln];
      const uint32_t af = sb + (uint32_t)(wg * 4 + warp) * 2048 + ln * 16;
      auto request = [&](int j) {
        if (j < 16) {
          const uint4* p = og + pc_chunk(j, cb) * 128;
          const uint32_t s = af + tab4(PC_ASLOTS, j) * SLOT;
#pragma unroll
          for (int i = 0; i < 4; i++) cp_async16(s + i * 512, p + i * 32);
        }
        cp_commit();
      };
      {
        const float sc0 = lds_f(sb + OFF_RSTAT + (uint32_t)(wg * 64 + lr) * 8) * L2E, sc1 = lds_f(sb + OFF_RSTAT + (uint32_t)(wg * 64 + lr + 8) * 8) * L2E;
        uint4 a[6];
        auto fetch = [&]() {
#pragma unroll
          for (int i = 0; i < 6; i++) a[i] = ld_rec16(&g_kvr[4 * cb + 2 * wg][i][tid & 127]);
        };
        auto valid = [&]() {
          bool ok = true;
#pragma unroll
          for (int i = 0; i < 6; i++) ok = ok && a[i].w == tag;
          return __all_sync(0xffffffffu, ok);
        };
        auto place = [&]() {
          const uint32_t kx = (uint32_t)(lane >> 4) ^ ((srow >> 1) & 3);
#pragma unroll
          for (int hh = 0; hh < 2; hh++) {
            const uint32_t base = sb + 12 * SLOT + wg * 8192 + hh * 4096 + srow * 64;
            stsm_x4(base + (kx << 4), a[3 * hh].x, a[3 * hh].y, a[3 * hh].z, a[3 * hh + 1].x);
            stsm_x4(base + ((kx ^ 2) << 4), a[3 * hh + 1].y, a[3 * hh + 1].z, a[3 * hh + 2].x, a[3 * hh + 2].y);
          }
          stsm_x4(sb + 13 * SLOT + srow * 64 + ((kx ^ (2 * wg)) << 4), (a[2].z & 0xFFFFu) | 0x3F800000u, (a[2].z >> 16) | 0x3F800000u,
                  (a[5].z & 0xFFFFu) | 0x3F800000u, (a[5].z >> 16) | 0x3F800000u);
          fence_async_smem();
          __syncwarp();
          if (lane == 0) mbar_arrive(BAR(B_KVRDY));
        };
        auto logits = [&](float (&p0)[16], float (&p1)[16], int c) {
          const uint64_t dq = mk_desc(sb + (10 + c) * SLOT + wg * 8192, 16, 1024, 1), dw = mk_desc(sb + OFF_PHIQ + c * 4096, 16, 512, 2);
          mbar_wait(BAR(B_QD + c));
          wg_fence();
          wg_n32<0, 1>(p0, dq, dw, 0);
          wg_n32<0, 1>(p1, dq + 4, dw + 128, 0);
          wg_n32<0, 1>(p0, dq + 2, dw + 64, 1);
          wg_n32<0, 1>(p1, dq + 6, dw + 192, 1);
          wg_commit();
        };
        auto feature = [&](float (&p)[16], uint32_t (&f)[16], float (&sp)[2]) {
          if (warp_fails(feature_fast<false>(p, sc0, sc1, f, sp, []() {}) < 0x1p60f)) {
            feature_shifted(p, p, sc0, sc1, f);
            sp[0] = 1.f; sp[1] = 1.f;
          }
        };
        auto apply = [&](float (&u)[20], const uint32_t (&f)[16], int h) {
          const uint64_t d = mk_desc(sb + 12 * SLOT + h * 4096, SLOT - h * 4096 + h * 16, 512, 2);
          wg_fence();
#pragma unroll
          for (int s = 0; s < 4; s++) wg_n40_rs<1>(u, f[4 * s], f[4 * s + 1], f[4 * s + 2], f[4 * s + 3], d + s * 64, s != 0);
          wg_commit();
        };
        float pa[16], pb[16], pc[16], pd[16], u0[20], u1[20], u2[20], n0[2], n1[2], n2[2], n3[2];
        uint32_t f0[16], f1[16], f2[16];
        uint4* const od = og + cb * 256;
        const uint32_t os = af + 10 * SLOT;
        logits(pa, pb, 0);
        fetch();
        wg_wait<0>();
        feature(pa, f0, n0);
        logits(pc, pd, 1);
        const bool early = valid();
        if (early) place(); else fetch();
        feature(pb, f1, n1);
        if (!early) {
#pragma unroll 1
          for (int it = 0; it < SPIN && !valid(); it++) fetch();
          place();
        }
        wg_wait<0>();
        mbar_wait(BAR(B_KVRDY));
        apply(u0, f0, 0);
        apply(u1, f1, 1);
        feature(pc, f2, n2);
        wg_wait<0>();
        apply(u2, f2, 2);
        attn_out(u0, n0, tg, os, od);
        attn_out(u1, n1, tg, os + 1024, od + 64);
        feature(pd, f1, n3);
        apply(u1, f1, 3);
        wg_wait<1>();
        attn_out(u2, n2, tg, os + SLOT, od + 128);
        wg_wait<0>();
        attn_out(u1, n3, tg, os + SLOT + 1024, od + 192);
      }
      asm volatile("setmaxnreg.dec.sync.aligned.u32 128;");
      uint32_t A[2][16];
      auto take = [&](uint32_t (&a)[16], int j) {
        const uint32_t s = af + tab4(PC_ASLOTS, j) * SLOT;
        cp_wait<3>();
#pragma unroll
        for (int i = 0; i < 4; i++) {
          const uint4 v = lds_u4(s + i * 512);
          a[4 * i] = v.x; a[4 * i + 1] = v.y; a[4 * i + 2] = v.z; a[4 * i + 3] = v.w;
        }
      };
      auto check = [&](uint32_t (&a)[16], int j) {
#pragma unroll
        for (int i = 0; i < 4; i++) a[4 * i] ^= tg;
#pragma unroll 1
        for (int it = 0; it < SPIN && warp_fails((((a[0] | a[4]) | (a[8] | a[12])) & OTAG) == 0); it++) {
          const uint4* p = og + pc_chunk(j, cb) * 128;
#pragma unroll
          for (int i = 0; i < 4; i++) {
            const uint4 v = ld_rec16(p + i * 32);
            a[4 * i] = v.x ^ tg; a[4 * i + 1] = v.y; a[4 * i + 2] = v.z; a[4 * i + 3] = v.w;
          }
        }
      };
      float acc[64];
      mbar_wait(BAR(B_FX));
#pragma unroll
      for (int jj = 0; jj < 8; jj++) {
        uint32_t x0, x1, x2, x3;
        ldsm_x4(x0, x1, x2, x3, sb + (jj >> 2) * 2 * SLOT + wg * 8192 + srow * 128 + ((sx ^ (2 * (jj & 3))) << 4));
        acc[8 * jj] = bf_lo(x0); acc[8 * jj + 1] = bf_hi(x0); acc[8 * jj + 2] = bf_lo(x1); acc[8 * jj + 3] = bf_hi(x1);
        acc[8 * jj + 4] = bf_lo(x2); acc[8 * jj + 5] = bf_hi(x2); acc[8 * jj + 6] = bf_lo(x3); acc[8 * jj + 7] = bf_hi(x3);
      }
#pragma unroll
      for (int i = 0; i < 64; i++) asm volatile("" : "+f"(acc[i]));
      __syncwarp();
      request(2);
      request(3);
      take(A[0], 0);
      check(A[0], 0);
      const bool lead = warp == 0 && ln == 0;
      if (lead) mbar_arrive(BAR(B_XDONE));
#pragma unroll
      for (int j = 0; j < 16; j++) {
        const uint32_t (&a)[16] = A[j & 1];
        mbar_wait(BAR(B_FB + j));
        const uint64_t db = mk_desc(sb + tab4(PC_BSLOTS, j) * SLOT, 8192, 1024, 1);
        wg_fence();
#pragma unroll
        for (int kk = 0; kk < 4; kk++) {
          wg_n128_rs<1>(acc, a[4 * kk], a[4 * kk + 1], a[4 * kk + 2], a[4 * kk + 3], db + kk * 128, 1);
          if (kk == PSPL) {
            wg_commit();
            request(j + 4);
            wg_wait<1>();
            if (j < 15) take(A[(j & 1) ^ 1], j + 1);
            if (j > 0 && lead) mbar_arrive(BAR(B_DC + j - 1));
            wg_fence();
          }
        }
        wg_commit();
        if (j < 15) check(A[(j & 1) ^ 1], j + 1);
      }
      mbar_wait(BAR(B_RESET2));
      wg_wait<0>();
      if (leader) mbar_arrive(BAR(B_DC + 15));
#pragma unroll
      for (int j = 0; j < 16; j++) {
        const float2 w = lds_f2(sb + OFF_WR + (uint32_t)(j * 8 + c2) * 4);
        float a = acc[4 * j], c = acc[4 * j + 1];
        s0 += a + c; q0 = fmaf(a, a, fmaf(c, c, q0)); d0 = fmaf(a, w.x, fmaf(c, w.y, d0));
        a = acc[4 * j + 2]; c = acc[4 * j + 3];
        s1 += a + c; q1 = fmaf(a, a, fmaf(c, c, q1)); d1 = fmaf(a, w.x, fmaf(c, w.y, d1));
      }
#pragma unroll
      for (int m = 1; m <= 2; m <<= 1) {
        s0 += __shfl_xor_sync(0xffffffffu, s0, m); q0 += __shfl_xor_sync(0xffffffffu, q0, m); d0 += __shfl_xor_sync(0xffffffffu, d0, m);
        s1 += __shfl_xor_sync(0xffffffffu, s1, m); q1 += __shfl_xor_sync(0xffffffffu, q1, m); d1 += __shfl_xor_sync(0xffffffffu, d1, m);
      }
      if ((lane & 2) == 0) {
        const bool hi = lane & 1;
        st_rec16(&g_hstat[rb][cb][wg * 64 + lr + (hi ? 8 : 0)], __float_as_uint(hi ? s1 : s0), __float_as_uint(hi ? q1 : q0), __float_as_uint(hi ? d1 : d0), lds_u(sb + OFF_RED + 4));
      }
#pragma unroll
      for (int jj = 0; jj < 8; jj++)
        stsm_x4(stg + (jj >> 2) * 2 * SLOT + srow * 128 + ((sx ^ (2 * (jj & 3))) << 4),
                pack_bf16(acc[8 * jj], acc[8 * jj + 1]), pack_bf16(acc[8 * jj + 2], acc[8 * jj + 3]),
                pack_bf16(acc[8 * jj + 4], acc[8 * jj + 5]), pack_bf16(acc[8 * jj + 6], acc[8 * jj + 7]));
    }
    asm volatile("setmaxnreg.dec.sync.aligned.u32 32;");
    {
    MMA_IDS
    const int grow0 = rb * 128 + wg * 64 + lr;
    const unsigned tag = lds_u(sb + OFF_RED + 4);
    uint32_t key;
    {
      const int trow = wg * 64 + lr;
      uint4 r00, r01, r10, r11;
#pragma unroll 1
      for (int it = 0; it < SPIN; it++) {
        r00 = ld_rec16(&g_hstat[rb][c2][trow]); r01 = ld_rec16(&g_hstat[rb][c2 + 1][trow]);
        r10 = ld_rec16(&g_hstat[rb][c2][trow + 8]); r11 = ld_rec16(&g_hstat[rb][c2 + 1][trow + 8]);
        if (__all_sync(0xffffffffu, r00.w == tag && r01.w == tag && r10.w == tag && r11.w == tag)) break;
      }
      s0 = __uint_as_float(r00.x) + __uint_as_float(r01.x); q0 = __uint_as_float(r00.y) + __uint_as_float(r01.y); d0 = __uint_as_float(r00.z) + __uint_as_float(r01.z);
      s1 = __uint_as_float(r10.x) + __uint_as_float(r11.x); q1 = __uint_as_float(r10.y) + __uint_as_float(r11.y); d1 = __uint_as_float(r10.z) + __uint_as_float(r11.z);
#pragma unroll
      for (int m = 1; m <= 2; m <<= 1) {
        s0 += __shfl_xor_sync(0xffffffffu, s0, m); q0 += __shfl_xor_sync(0xffffffffu, q0, m); d0 += __shfl_xor_sync(0xffffffffu, d0, m);
        s1 += __shfl_xor_sync(0xffffffffu, s1, m); q1 += __shfl_xor_sync(0xffffffffu, q1, m); d1 += __shfl_xor_sync(0xffffffffu, d1, m);
      }
      const float sumw = lds_f(sb + OFF_RED);
      const float mean0 = s0 * (1.f / DM), mean1 = s1 * (1.f / DM);
      const float rstd0 = rsq(fmaxf(q0 * (1.f / DM) - mean0 * mean0, 0.f) + 1e-5f);
      const float rstd1 = rsq(fmaxf(q1 * (1.f / DM) - mean1 * mean1, 0.f) + 1e-5f);
      const uint32_t rr = pack_bf16(rstd0 * (d0 - mean0 * sumw), rstd1 * (d1 - mean1 * sumw));
      uint32_t u0 = rr & 0xFFFFu, u1 = rr >> 16;
      u0 = (u0 & 0x8000u) ? (~u0 & 0xFFFFu) : (u0 | 0x8000u);
      u1 = (u1 & 0x8000u) ? (~u1 & 0xFFFFu) : (u1 | 0x8000u);
      const uint32_t k0 = (u0 << 16) | (uint32_t)(0xFFFF - grow0), k1 = (u1 << 16) | (uint32_t)(0xFFFF - (grow0 + 8));
      key = __reduce_max_sync(0xffffffffu, max(k0, k1));
      if (lane == 0) sts_u(sb + OFF_RED + 16 + (uint32_t)(wg * 4 + warp) * 4, key);
      if ((lane & 3) == 0) {
        sts_f2(sb + OFF_RSTAT + trow * 8, rstd0, -mean0 * rstd0);
        sts_f2(sb + OFF_RSTAT + (trow + 8) * 8, rstd1, -mean1 * rstd1);
      }
      bar_sync(1, 256);
      const uint4 ka = lds_u4(sb + OFF_RED + 16), kb = lds_u4(sb + OFF_RED + 32);
      key = max(max(max(ka.x, ka.y), max(ka.z, ka.w)), max(max(kb.x, kb.y), max(kb.z, kb.w)));
    }
    if (tid == 0) st_rec8(&g_key[cb][rb][0], key, tag);
    const int crow = (0xFFFF - (int)(key & 0xFFFFu)) & 127;
    const bool own = (crow >> 4) == wg * 4 + warp;
    uint32_t co0 = 0, co1 = 0;
    if (own) {
      const uint32_t r = (uint32_t)(crow & 63);
      const float2 st = lds_f2(sb + OFF_RSTAT + crow * 8);
      const uint32_t a = stg + r * 128 + ((((uint32_t)lane >> 2) ^ (r & 7)) << 4) + (lane & 3) * 4;
      const uint32_t h0 = lds_u(a), h1 = lds_u(a + 2 * SLOT);
      uint32_t n0, n1;
      co0 = ln_res(h0, st.x, st.y, n0); co1 = ln_res(h1, st.x, st.y, n1);
      st_rec8(&g_candx[rb][cb * 64 + lane], n0, tag);
      st_rec8(&g_candx[rb][cb * 64 + 32 + lane], n1, tag);
      st_rec16(&g_cand[rb][cb * 64 + lane], n0, h0, key, tag);
      st_rec16(&g_cand[rb][cb * 64 + 32 + lane], n1, h1, key, tag);
    }
    __nv_bfloat16* ob = P.out + (size_t)(rb * 128 + wg * 64) * DM + cb * 128;
#pragma unroll 4
    for (int i = 0; i < 8; i++) {
      const uint32_t r = (uint32_t)(warp * 16 + (i & 3) * 4 + (lane >> 3));
      const uint32_t a = stg + (i >> 2) * 2 * SLOT + r * 128 + ((((uint32_t)lane & 7) ^ (r & 7)) << 4);
      const uint4 h = lds_u4(a);
      const float2 st = lds_f2(sb + OFF_RSTAT + (wg * 64 + r) * 8);
      uint32_t n;
      uint4 o;
      o.x = ln_res(h.x, st.x, st.y, n); o.y = ln_res(h.y, st.x, st.y, n); o.z = ln_res(h.z, st.x, st.y, n); o.w = ln_res(h.w, st.x, st.y, n);
      if (!own) sts_u4(a, o.x, o.y, o.z, o.w);
      else if ((int)(wg * 64 + r) != crow) stg16(ob + (size_t)r * DM + (i >> 2) * 64 + (lane & 7) * 8, o);
      if ((i & 3) == 3) {
        fence_async_smem();
        __syncwarp();
        if (i == 7) mbar_wait(BAR(B_ROW));
        if (elect()) {
          if (!own) tma_store_2d(&P.mOut, stg + (i >> 2) * 2 * SLOT + warp * 2048, cb * 128 + (i >> 2) * 64, rb * 128 + wg * 64 + warp * 16);
          asm volatile("cp.async.bulk.commit_group;" ::: "memory");
        }
        __syncwarp();
      }
    }
    if (elect()) {
      asm volatile("cp.async.bulk.wait_group.read 0;" ::: "memory");
    }
    __syncwarp();
    if (own) {
      uint2 v;
#pragma unroll 1
      for (int it = 0; it < SPIN; it++) {
        v = ld_rec8(&g_key[cb][lane & 15][0]);
        if (__all_sync(0xffffffffu, v.y == tag)) break;
      }
      if (__reduce_max_sync(0xffffffffu, v.x) != key) {
        uint32_t* op = reinterpret_cast<uint32_t*>(ob + (size_t)(crow & 63) * DM);
        op[lane] = co0; op[32 + lane] = co1;
      }
    }
    }
  }
#undef BAR
}

typedef CUresult (*EncodeFn)(CUtensorMap*, CUtensorMapDataType, cuuint32_t, void*, const cuuint64_t*, const cuuint64_t*,
                             const cuuint32_t*, const cuuint32_t*, CUtensorMapInterleave, CUtensorMapSwizzle,
                             CUtensorMapL2promotion, CUtensorMapFloatOOBfill);

void make_map(EncodeFn fn, CUtensorMap* m, const void* ptr, uint64_t cols, uint64_t rows, uint32_t bc, uint32_t br, CUtensorMapSwizzle swz) {
  cuuint64_t dims[2] = {cols, rows};
  cuuint64_t strides[1] = {cols * 2};
  cuuint32_t box[2] = {bc, br};
  cuuint32_t es[2] = {1, 1};
  fn(m, CU_TENSOR_MAP_DATA_TYPE_BFLOAT16, 2, const_cast<void*>(ptr), dims, strides, box, es, CU_TENSOR_MAP_INTERLEAVE_NONE, swz,
     CU_TENSOR_MAP_L2_PROMOTION_L2_128B, CU_TENSOR_MAP_FLOAT_OOB_FILL_NONE);
}

}

extern "C" void kernel_launch(void* const* d_in, const int* in_sizes, int n_in, void* d_out, int out_size) {
  static EncodeFn fn = nullptr;
  if (!fn) {
    cudaDriverEntryPointQueryResult q;
    cudaGetDriverEntryPoint("cuTensorMapEncodeTiled", (void**)&fn, cudaEnableDefault, &q);
    cudaFuncSetAttribute(fused_kernel, cudaFuncAttributeMaxDynamicSharedMemorySize, SMEM_BYTES);
  }
  Params P;
  P.x = (const __nv_bfloat16*)d_in[0];
  P.wqkv = (const __nv_bfloat16*)d_in[1];
  const __nv_bfloat16* wphi = (const __nv_bfloat16*)d_in[2];
  P.wo = (const __nv_bfloat16*)d_in[3];
  P.wr = (const __nv_bfloat16*)d_in[5];
  P.wg = (const __nv_bfloat16*)d_in[6];
  P.wu = (const __nv_bfloat16*)d_in[7];
  P.wd = (const __nv_bfloat16*)d_in[8];
  P.out = (__nv_bfloat16*)d_out;
  make_map(fn, &P.mX, P.x, DM, SEQ, 64, 128, CU_TENSOR_MAP_SWIZZLE_128B);
  make_map(fn, &P.mW, P.wqkv, 3 * DM, DM, 64, 64, CU_TENSOR_MAP_SWIZZLE_128B);
  make_map(fn, &P.mWo, P.wo, DM, DM, 64, 64, CU_TENSOR_MAP_SWIZZLE_128B);
  make_map(fn, &P.mPhi, wphi, 32, 1024, 32, 64, CU_TENSOR_MAP_SWIZZLE_64B);
  make_map(fn, &P.mWg, P.wg, FF, DM, 32, 256, CU_TENSOR_MAP_SWIZZLE_64B);
  make_map(fn, &P.mWu, P.wu, FF, DM, 32, 256, CU_TENSOR_MAP_SWIZZLE_64B);
  make_map(fn, &P.mWs, P.wqkv, 3 * DM, DM, 32, 64, CU_TENSOR_MAP_SWIZZLE_NONE);
  make_map(fn, &P.mWd, P.wd, DM, FF, 64, 32, CU_TENSOR_MAP_SWIZZLE_128B);
  make_map(fn, &P.mOut, P.out, DM, SEQ, 64, 16, CU_TENSOR_MAP_SWIZZLE_128B);
  make_map(fn, &P.mWgP, P.wg, FF, DM, 64, 64, CU_TENSOR_MAP_SWIZZLE_128B);
  make_map(fn, &P.mWuP, P.wu, FF, DM, 64, 64, CU_TENSOR_MAP_SWIZZLE_128B);
  fused_kernel<<<NCTA, NTHREADS, SMEM_BYTES, cudaStreamPerThread>>>(P);
}
```

```cpp
#include <cuda_runtime.h>
#include <cuda_bf16.h>
#include <cuda.h>
#include <stdint.h>

namespace {

constexpr int SEQ = 2048, DM = 1024, FF = 3584;
constexpr int NCTA = 128, NTHREADS = 512, NFFN = 112;
constexpr int SPIN = 1 << 17;
constexpr int QG = 0;
constexpr int RSTQ = 3;
constexpr int ORST = 0;
constexpr int PSPL = 1;
constexpr int EXPV = 0;
constexpr int PIN = 145;
constexpr int RCPG = 4;
constexpr int KIL = 0;
constexpr int KW = 0;
constexpr int PCU = 1;
constexpr int QORD = 0;
constexpr int XH = 0;
constexpr int ORS0 = 0;
constexpr int THR = 1;
constexpr int QPRE = 0;

constexpr uint32_t SLOT = 16384;
constexpr uint32_t OFF_MISC = 13 * SLOT;
constexpr uint32_t OFF_PHIK = OFF_MISC;
constexpr uint32_t OFF_PHIQ = OFF_MISC + 4096;
constexpr uint32_t OFF_ONES = OFF_MISC + 12288;
constexpr uint32_t OFF_RSTAT = OFF_MISC + 13312;
constexpr uint32_t OFF_CS = OFF_MISC + 15360;
constexpr uint32_t OFF_WR = OFF_MISC + 16384;
constexpr uint32_t OFF_BAR = OFF_MISC + 16896;
constexpr uint32_t OFF_RED = OFF_MISC + 18304;
constexpr uint32_t SMEM_BYTES = OFF_MISC + 19456;

enum {
  B_FKV = 0, B_DKV = 16, B_FQ = 32, B_DQ = 48,
  B_PHI = 64, B_RESET = 65, B_RESET2 = 66, B_ROW = 67, B_FX = 68, B_REL = 72,
  B_FB = 80, B_DC = 96, B_QD = 112, B_STAT = 114,
  B_KVFREE = 120, B_QGO = 121, B_QGO2 = 122, B_CSD = 123, B_XDONE = 124, B_F1 = 126, B_KVRDY = 127,
  B_FS = 128, B_RELD = 142, B_FW = 144
};
constexpr unsigned long long MISC_COUNTS = 0x0502020203020202ull;

struct Params {
  CUtensorMap mX, mW, mWo, mPhi, mWg, mWu, mWs, mWd, mOut, mWgP, mWuP;
  const __nv_bfloat16 *x, *wqkv, *wo, *wr, *wg, *wu, *wd;
  __nv_bfloat16* out;
};

__device__ unsigned g_epoch;
__device__ __align__(128) uint4 g_rowstat[SEQ];
__device__ __align__(128) uint2 g_colsum[4][3 * DM];
__device__ __align__(128) uint4 g_kvp[32][8][3][128];
__device__ __align__(128) uint4 g_kvr[32][3][128];
__device__ __align__(128) uint4 g_o[128][16][4][32];
__device__ __align__(128) uint4 g_hstat[16][8][128];
__device__ __align__(128) uint4 g_cand[16][512];
__device__ __align__(128) uint2 g_candx[16][512];
__device__ __align__(128) uint2 g_key[8][16][4];
__device__ __align__(128) uint2 g_ypart[128][NFFN][8];

__device__ __forceinline__ uint32_t smem_u32(const void* p) { return (uint32_t)__cvta_generic_to_shared(p); }
__device__ __forceinline__ bool elect() {
  uint32_t p;
  asm volatile("{\n.reg .pred P;\nelect.sync _|P, 0xffffffff;\nselp.u32 %0, 1, 0, P;\n}\n" : "=r"(p));
  return p != 0;
}
__device__ __forceinline__ void mbar_init(uint32_t bar, uint32_t cnt) { asm volatile("mbarrier.init.shared::cta.b64 [%0], %1;" :: "r"(bar), "r"(cnt)); }
__device__ __forceinline__ void mbar_expect_tx(uint32_t bar, uint32_t bytes) { asm volatile("mbarrier.arrive.expect_tx.shared::cta.b64 _, [%0], %1;" :: "r"(bar), "r"(bytes) : "memory"); }
__device__ __forceinline__ void mbar_arrive(uint32_t bar) { asm volatile("mbarrier.arrive.shared::cta.b64 _, [%0];" :: "r"(bar) : "memory"); }
__device__ __forceinline__ void prefetch_map(const CUtensorMap* m) { asm volatile("prefetch.tensormap [%0];" :: "l"(m) : "memory"); }
__device__ __forceinline__ void mbar_wait(uint32_t bar) {
#pragma unroll 1
  for (int it = 0; it < SPIN; it++) {
    uint32_t ok;
    asm volatile("{\n.reg .pred p;\nmbarrier.try_wait.parity.shared::cta.b64 p, [%1], 0;\nselp.u32 %0, 1, 0, p;\n}\n" : "=r"(ok) : "r"(bar) : "memory");
    if (ok) break;
  }
}
__device__ __forceinline__ bool mbar_test(uint32_t bar) {
  uint32_t ok;
  asm volatile("{\n.reg .pred p;\nmbarrier.test_wait.parity.shared::cta.b64 p, [%1], 0;\nselp.u32 %0, 1, 0, p;\n}\n" : "=r"(ok) : "r"(bar) : "memory");
  return ok != 0;
}
__device__ __forceinline__ void tma_load_2d(uint32_t dst, const CUtensorMap* m, uint32_t bar, int c0, int c1) {
  asm volatile("cp.async.bulk.tensor.2d.shared::cluster.global.mbarrier::complete_tx::bytes [%0], [%1, {%3, %4}], [%2];"
    :: "r"(dst), "l"(m), "r"(bar), "r"(c0), "r"(c1) : "memory");
}
__device__ __forceinline__ void tma_load_2d_ef(uint32_t dst, const CUtensorMap* m, uint32_t bar, int c0, int c1) {
  uint64_t pol;
  asm("createpolicy.fractional.L2::evict_first.b64 %0, 1.0;" : "=l"(pol));
  asm volatile("cp.async.bulk.tensor.2d.shared::cluster.global.mbarrier::complete_tx::bytes.L2::cache_hint [%0], [%1, {%3, %4}], [%2], %5;"
    :: "r"(dst), "l"(m), "r"(bar), "r"(c0), "r"(c1), "l"(pol) : "memory");
}
__device__ __forceinline__ void tma_store_2d(const CUtensorMap* m, uint32_t src, int c0, int c1) {
  asm volatile("cp.async.bulk.tensor.2d.global.shared::cta.bulk_group [%0, {%2, %3}], [%1];"
    :: "l"(m), "r"(src), "r"(c0), "r"(c1) : "memory");
}
__device__ __forceinline__ void cp_async16(uint32_t dst, const void* src) { asm volatile("cp.async.cg.shared.global [%0], [%1], 16;" :: "r"(dst), "l"(src) : "memory"); }
__device__ __forceinline__ void cp_commit() { asm volatile("cp.async.commit_group;" ::: "memory"); }
template <int N> __device__ __forceinline__ void cp_wait() { asm volatile("cp.async.wait_group %0;" :: "n"(N) : "memory"); }
__device__ __forceinline__ void l2_prefetch(const void* src, uint32_t bytes) {
  asm volatile("cp.async.bulk.prefetch.L2.global [%0], %1;" :: "l"(src), "r"(bytes) : "memory");
}
__device__ __forceinline__ void wg_fence() { asm volatile("wgmma.fence.sync.aligned;" ::: "memory"); }
__device__ __forceinline__ void wg_commit() { asm volatile("wgmma.commit_group.sync.aligned;" ::: "memory"); }
template <int N> __device__ __forceinline__ void wg_wait() { asm volatile("wgmma.wait_group.sync.aligned %0;" :: "n"(N) : "memory"); }
__device__ __forceinline__ void fence_async_smem() { asm volatile("fence.proxy.async.shared::cta;" ::: "memory"); }
__device__ __forceinline__ void bar_sync(int id, int n) { asm volatile("bar.sync %0, %1;" :: "r"(id), "r"(n) : "memory"); }
__device__ __forceinline__ void bar_arrive(int id, int n) { asm volatile("bar.arrive %0, %1;" :: "r"(id), "r"(n) : "memory"); }
__device__ __forceinline__ uint64_t mk_desc(uint32_t addr, uint32_t lbo, uint32_t sbo, uint32_t swz) {
  return (uint64_t)((addr & 0x3FFFF) >> 4) | ((uint64_t)((lbo & 0x3FFFF) >> 4) << 16) | ((uint64_t)(sbo >> 4) << 32) | ((uint64_t)swz << 62);
}
__device__ __forceinline__ void stsm_x4(uint32_t addr, uint32_t r0, uint32_t r1, uint32_t r2, uint32_t r3) {
  asm volatile("stmatrix.sync.aligned.m8n8.x4.shared.b16 [%0], {%1, %2, %3, %4};" :: "r"(addr), "r"(r0), "r"(r1), "r"(r2), "r"(r3) : "memory");
}
__device__ __forceinline__ void stsm_x4_if(int c, uint32_t addr, uint32_t r0, uint32_t r1, uint32_t r2, uint32_t r3) {
  asm volatile("{\n.reg .pred p;\nsetp.ne.b32 p, %5, 0;\n@p stmatrix.sync.aligned.m8n8.x4.shared.b16 [%0], {%1, %2, %3, %4};\n}\n"
    :: "r"(addr), "r"(r0), "r"(r1), "r"(r2), "r"(r3), "r"(c) : "memory");
}
__device__ __forceinline__ void ldsm_x4(uint32_t& r0, uint32_t& r1, uint32_t& r2, uint32_t& r3, uint32_t addr) {
  asm volatile("ldmatrix.sync.aligned.m8n8.x4.shared.b16 {%0, %1, %2, %3}, [%4];" : "=r"(r0), "=r"(r1), "=r"(r2), "=r"(r3) : "r"(addr) : "memory");
}
__device__ __forceinline__ void ldsm_x4_t(uint32_t (&r)[4], uint32_t addr) {
  asm volatile("ldmatrix.sync.aligned.m8n8.x4.trans.shared.b16 {%0, %1, %2, %3}, [%4];" : "=r"(r[0]), "=r"(r[1]), "=r"(r[2]), "=r"(r[3]) : "r"(addr) : "memory");
}
__device__ __forceinline__ void mma_bf16(float* d, const uint32_t (&a)[4], uint32_t b0, uint32_t b1) {
  asm volatile("mma.sync.aligned.m16n8k16.row.col.f32.bf16.bf16.f32 {%0, %1, %2, %3}, {%4, %5, %6, %7}, {%8, %9}, {%0, %1, %2, %3};"
    : "+f"(d[0]), "+f"(d[1]), "+f"(d[2]), "+f"(d[3]) : "r"(a[0]), "r"(a[1]), "r"(a[2]), "r"(a[3]), "r"(b0), "r"(b1));
}
__device__ __forceinline__ uint32_t zero_after(uint32_t v) { uint32_t r; asm volatile("prmt.b32 %0, %1, 0, 0x4444;" : "=r"(r) : "r"(v)); return r; }
__device__ __forceinline__ int fresh_tid() { int v; asm volatile("mov.u32 %0, %%tid.x;" : "=r"(v)); return v; }
template <int ID> __device__ __forceinline__ void pin_at() {
  asm volatile("{\n.reg .pred p;\nsetp.eq.u32 p, %0, %1;\nPIN:\n@p nanosleep.u32 0;\n@p bra.uni PIN;\n}\n" :: "r"(blockIdx.x), "n"(4096 + ID) : "memory");
}
#define pin_order() pin_at<__LINE__>()
__device__ __forceinline__ uint32_t pack_bf16(float lo, float hi) {
  uint32_t r; asm("cvt.rn.bf16x2.f32 %0, %1, %2;" : "=r"(r) : "f"(hi), "f"(lo)); return r;
}
__device__ __forceinline__ uint32_t pack_pin(float lo, float hi) {
  uint32_t r; asm volatile("cvt.rn.bf16x2.f32 %0, %1, %2;" : "=r"(r) : "f"(hi), "f"(lo)); return r;
}
__device__ __forceinline__ void pack_swap(int c, uint32_t& r0, uint32_t& r1, float a, float b, float d, float e) {
  const uint32_t u = pack_pin(a, b), w = pack_pin(d, e);
  r0 = c ? u : w; r1 = c ? w : u;
}
__device__ __forceinline__ float bf_lo(uint32_t v) { return __uint_as_float(v << 16); }
__device__ __forceinline__ float bf_hi(uint32_t v) { return __uint_as_float(v & 0xFFFF0000u); }
__device__ __forceinline__ float bf_round(float v) { return bf_lo(pack_bf16(v, 0.f)); }
__device__ __forceinline__ float ex2(float v) { float r; asm("ex2.approx.ftz.f32 %0, %1;" : "=f"(r) : "f"(v)); return r; }
__device__ __forceinline__ float rsq(float v) { float r; asm("rsqrt.approx.ftz.f32 %0, %1;" : "=f"(r) : "f"(v)); return r; }
__device__ __forceinline__ float rcp(float v) { float r; asm("rcp.approx.ftz.f32 %0, %1;" : "=f"(r) : "f"(v)); return r; }
__device__ __forceinline__ void st_rec16(uint4* p, uint32_t a, uint32_t b, uint32_t c, uint32_t d) {
  asm volatile("{\n.reg .b128 r;\n.reg .b64 lo, hi;\nmov.b64 lo, {%1, %2};\nmov.b64 hi, {%3, %4};\nmov.b128 r, {lo, hi};\nst.relaxed.gpu.global.b128 [%0], r;\n}\n"
    :: "l"(p), "r"(a), "r"(b), "r"(c), "r"(d) : "memory");
}
__device__ __forceinline__ uint4 ld_rec16(const uint4* p) {
  uint4 v;
  asm volatile("{\n.reg .b128 r;\n.reg .b64 lo, hi;\nld.relaxed.gpu.global.b128 r, [%4];\nmov.b128 {lo, hi}, r;\nmov.b64 {%0, %1}, lo;\nmov.b64 {%2, %3}, hi;\n}\n"
    : "=r"(v.x), "=r"(v.y), "=r"(v.z), "=r"(v.w) : "l"(p) : "memory");
  return v;
}
__device__ __forceinline__ void ld_rec16_stale(uint4& v, const uint4* p, uint32_t tag) {
  asm volatile("{\n.reg .pred p;\n.reg .b128 r;\n.reg .b64 lo, hi;\nmov.b64 lo, {%0, %1};\nmov.b64 hi, {%2, %3};\nmov.b128 r, {lo, hi};\nsetp.ne.u32 p, %3, %5;\n"
    "@p ld.relaxed.gpu.global.b128 r, [%4];\nmov.b128 {lo, hi}, r;\nmov.b64 {%0, %1}, lo;\nmov.b64 {%2, %3}, hi;\n}\n"
    : "+r"(v.x), "+r"(v.y), "+r"(v.z), "+r"(v.w) : "l"(p), "r"(tag) : "memory");
}
__device__ __forceinline__ void st_rec8(uint2* p, uint32_t a, uint32_t b) {
  asm volatile("{\n.reg .b64 r;\nmov.b64 r, {%1, %2};\nst.relaxed.gpu.global.b64 [%0], r;\n}\n" :: "l"(p), "r"(a), "r"(b) : "memory");
}
__device__ __forceinline__ uint2 ld_rec8(const uint2* p) {
  uint2 v;
  asm volatile("{\n.reg .b64 r;\nld.relaxed.gpu.global.b64 r, [%2];\nmov.b64 {%0, %1}, r;\n}\n" : "=r"(v.x), "=r"(v.y) : "l"(p) : "memory");
  return v;
}
__device__ __forceinline__ unsigned ld_acquire(const unsigned* p) { unsigned v; asm volatile("ld.acquire.gpu.global.u32 %0, [%1];" : "=r"(v) : "l"(p) : "memory"); return v; }
__device__ __forceinline__ unsigned ld_relaxed(const unsigned* p) { unsigned v; asm volatile("ld.relaxed.gpu.global.u32 %0, [%1];" : "=r"(v) : "l"(p) : "memory"); return v; }
__device__ __forceinline__ void st_release(unsigned* p, unsigned v) { asm volatile("st.release.gpu.global.u32 [%0], %1;" :: "l"(p), "r"(v) : "memory"); }
__device__ __forceinline__ uint4 ldg_nc16(const void* p) {
  uint4 v; asm volatile("ld.global.nc.L1::no_allocate.v4.u32 {%0, %1, %2, %3}, [%4];" : "=r"(v.x), "=r"(v.y), "=r"(v.z), "=r"(v.w) : "l"(p)); return v;
}
__device__ __forceinline__ void stg16(void* p, uint4 v) { asm volatile("st.global.v4.u32 [%0], {%1, %2, %3, %4};" :: "l"(p), "r"(v.x), "r"(v.y), "r"(v.z), "r"(v.w) : "memory"); }
__device__ __forceinline__ float2 lds_f2(uint32_t a) { float2 v; asm volatile("ld.shared.v2.f32 {%0, %1}, [%2];" : "=f"(v.x), "=f"(v.y) : "r"(a)); return v; }
__device__ __forceinline__ float lds_f(uint32_t a) { float v; asm volatile("ld.shared.f32 %0, [%1];" : "=f"(v) : "r"(a)); return v; }
__device__ __forceinline__ uint32_t lds_u(uint32_t a) { uint32_t v; asm volatile("ld.shared.u32 %0, [%1];" : "=r"(v) : "r"(a)); return v; }
__device__ __forceinline__ uint4 lds_u4(uint32_t a) { uint4 v; asm volatile("ld.shared.v4.u32 {%0, %1, %2, %3}, [%4];" : "=r"(v.x), "=r"(v.y), "=r"(v.z), "=r"(v.w) : "r"(a)); return v; }
__device__ __forceinline__ void sts_f(uint32_t a, float v) { asm volatile("st.shared.f32 [%0], %1;" :: "r"(a), "f"(v) : "memory"); }
__device__ __forceinline__ void sts_f2(uint32_t a, float x, float y) { asm volatile("st.shared.v2.f32 [%0], {%1, %2};" :: "r"(a), "f"(x), "f"(y) : "memory"); }
__device__ __forceinline__ void sts_u2(uint32_t a, uint32_t x, uint32_t y) { asm volatile("st.shared.v2.u32 [%0], {%1, %2};" :: "r"(a), "r"(x), "r"(y) : "memory"); }
__device__ __forceinline__ void sts_u4(uint32_t a, uint32_t x, uint32_t y, uint32_t z, uint32_t w) { asm volatile("st.shared.v4.u32 [%0], {%1, %2, %3, %4};" :: "r"(a), "r"(x), "r"(y), "r"(z), "r"(w) : "memory"); }
__device__ __forceinline__ void sts_h(uint32_t a, uint32_t v) { asm volatile("st.shared.u16 [%0], %1;" :: "r"(a), "h"((uint16_t)v) : "memory"); }
__device__ __forceinline__ void sts_u(uint32_t a, uint32_t v) { asm volatile("st.shared.u32 [%0], %1;" :: "r"(a), "r"(v) : "memory"); }

template <int TA, int TB>
__device__ __forceinline__ void wg_n128(float (&d)[64], uint64_t da, uint64_t db, int sd) {
  asm volatile("{\n.reg .pred p;\nsetp.ne.b32 p, %66, 0;\n"
    "wgmma.mma_async.sync.aligned.m64n128k16.f32.bf16.bf16 {%0, %1, %2, %3, %4, %5, %6, %7, %8, %9, %10, %11, %12, %13, %14, %15, %16, %17, %18, %19, %20, %21, %22, %23, %24, %25, %26, %27, %28, %29, %30, %31, %32, %33, %34, %35, %36, %37, %38, %39, %40, %41, %42, %43, %44, %45, %46, %47, %48, %49, %50, %51, %52, %53, %54, %55, %56, %57, %58, %59, %60, %61, %62, %63}, %64, %65, p, 1, 1, %67, %68;\n}\n"
    : "+f"(d[0]), "+f"(d[1]), "+f"(d[2]), "+f"(d[3]), "+f"(d[4]), "+f"(d[5]), "+f"(d[6]), "+f"(d[7]), "+f"(d[8]), "+f"(d[9]), "+f"(d[10]), "+f"(d[11]), "+f"(d[12]), "+f"(d[13]), "+f"(d[14]), "+f"(d[15]), "+f"(d[16]), "+f"(d[17]), "+f"(d[18]), "+f"(d[19]), "+f"(d[20]), "+f"(d[21]), "+f"(d[22]), "+f"(d[23]), "+f"(d[24]), "+f"(d[25]), "+f"(d[26]), "+f"(d[27]), "+f"(d[28]), "+f"(d[29]), "+f"(d[30]), "+f"(d[31]), "+f"(d[32]), "+f"(d[33]), "+f"(d[34]), "+f"(d[35]), "+f"(d[36]), "+f"(d[37]), "+f"(d[38]), "+f"(d[39]), "+f"(d[40]), "+f"(d[41]), "+f"(d[42]), "+f"(d[43]), "+f"(d[44]), "+f"(d[45]), "+f"(d[46]), "+f"(d[47]), "+f"(d[48]), "+f"(d[49]), "+f"(d[50]), "+f"(d[51]), "+f"(d[52]), "+f"(d[53]), "+f"(d[54]), "+f"(d[55]), "+f"(d[56]), "+f"(d[57]), "+f"(d[58]), "+f"(d[59]), "+f"(d[60]), "+f"(d[61]), "+f"(d[62]), "+f"(d[63])
    : "l"(da), "l"(db), "r"(sd), "n"(TA), "n"(TB));
}

template <int TA, int TB, int O>
__device__ __forceinline__ void wg_n64(float (&d)[64], uint64_t da, uint64_t db, int sd) {
  asm volatile("{\n.reg .pred p;\nsetp.ne.b32 p, %34, 0;\n"
    "wgmma.mma_async.sync.aligned.m64n64k16.f32.bf16.bf16 {%0, %1, %2, %3, %4, %5, %6, %7, %8, %9, %10, %11, %12, %13, %14, %15, %16, %17, %18, %19, %20, %21, %22, %23, %24, %25, %26, %27, %28, %29, %30, %31}, %32, %33, p, 1, 1, %35, %36;\n}\n"
    : "+f"(d[O + 0]), "+f"(d[O + 1]), "+f"(d[O + 2]), "+f"(d[O + 3]), "+f"(d[O + 4]), "+f"(d[O + 5]), "+f"(d[O + 6]), "+f"(d[O + 7]), "+f"(d[O + 8]), "+f"(d[O + 9]), "+f"(d[O + 10]), "+f"(d[O + 11]), "+f"(d[O + 12]), "+f"(d[O + 13]), "+f"(d[O + 14]), "+f"(d[O + 15]), "+f"(d[O + 16]), "+f"(d[O + 17]), "+f"(d[O + 18]), "+f"(d[O + 19]), "+f"(d[O + 20]), "+f"(d[O + 21]), "+f"(d[O + 22]), "+f"(d[O + 23]), "+f"(d[O + 24]), "+f"(d[O + 25]), "+f"(d[O + 26]), "+f"(d[O + 27]), "+f"(d[O + 28]), "+f"(d[O + 29]), "+f"(d[O + 30]), "+f"(d[O + 31])
    : "l"(da), "l"(db), "r"(sd), "n"(TA), "n"(TB));
}

template <int TA, int TB>
__device__ __forceinline__ void wg_n40(float (&d)[20], uint64_t da, uint64_t db, int sd) {
  asm volatile("{\n.reg .pred p;\nsetp.ne.b32 p, %22, 0;\n"
    "wgmma.mma_async.sync.aligned.m64n40k16.f32.bf16.bf16 {%0, %1, %2, %3, %4, %5, %6, %7, %8, %9, %10, %11, %12, %13, %14, %15, %16, %17, %18, %19}, %20, %21, p, 1, 1, %23, %24;\n}\n"
    : "+f"(d[0]), "+f"(d[1]), "+f"(d[2]), "+f"(d[3]), "+f"(d[4]), "+f"(d[5]), "+f"(d[6]), "+f"(d[7]), "+f"(d[8]), "+f"(d[9]), "+f"(d[10]), "+f"(d[11]), "+f"(d[12]), "+f"(d[13]), "+f"(d[14]), "+f"(d[15]), "+f"(d[16]), "+f"(d[17]), "+f"(d[18]), "+f"(d[19])
    : "l"(da), "l"(db), "r"(sd), "n"(TA), "n"(TB));
}

template <int TA, int TB>
__device__ __forceinline__ void wg_n32(float (&d)[16], uint64_t da, uint64_t db, int sd) {
  asm volatile("{\n.reg .pred p;\nsetp.ne.b32 p, %18, 0;\n"
    "wgmma.mma_async.sync.aligned.m64n32k16.f32.bf16.bf16 {%0, %1, %2, %3, %4, %5, %6, %7, %8, %9, %10, %11, %12, %13, %14, %15}, %16, %17, p, 1, 1, %19, %20;\n}\n"
    : "+f"(d[0]), "+f"(d[1]), "+f"(d[2]), "+f"(d[3]), "+f"(d[4]), "+f"(d[5]), "+f"(d[6]), "+f"(d[7]), "+f"(d[8]), "+f"(d[9]), "+f"(d[10]), "+f"(d[11]), "+f"(d[12]), "+f"(d[13]), "+f"(d[14]), "+f"(d[15])
    : "l"(da), "l"(db), "r"(sd), "n"(TA), "n"(TB));
}

template <int TB>
__device__ __forceinline__ void wg_n40_rs(float (&d)[20], uint32_t a0, uint32_t a1, uint32_t a2, uint32_t a3, uint64_t db, int sd) {
  asm volatile("{\n.reg .pred p;\nsetp.ne.b32 p, %25, 0;\n"
    "wgmma.mma_async.sync.aligned.m64n40k16.f32.bf16.bf16 {%0, %1, %2, %3, %4, %5, %6, %7, %8, %9, %10, %11, %12, %13, %14, %15, %16, %17, %18, %19}, {%20, %21, %22, %23}, %24, p, 1, 1, %26;\n}\n"
    : "+f"(d[0]), "+f"(d[1]), "+f"(d[2]), "+f"(d[3]), "+f"(d[4]), "+f"(d[5]), "+f"(d[6]), "+f"(d[7]), "+f"(d[8]), "+f"(d[9]), "+f"(d[10]), "+f"(d[11]), "+f"(d[12]), "+f"(d[13]), "+f"(d[14]), "+f"(d[15]), "+f"(d[16]), "+f"(d[17]), "+f"(d[18]), "+f"(d[19])
    : "r"(a0), "r"(a1), "r"(a2), "r"(a3), "l"(db), "r"(sd), "n"(TB));
}

template <int TB>
__device__ __forceinline__ void wg_n32_rs(float (&d)[16], uint32_t a0, uint32_t a1, uint32_t a2, uint32_t a3, uint64_t db, int sd) {
  asm volatile("{\n.reg .pred p;\nsetp.ne.b32 p, %21, 0;\n"
    "wgmma.mma_async.sync.aligned.m64n32k16.f32.bf16.bf16 {%0, %1, %2, %3, %4, %5, %6, %7, %8, %9, %10, %11, %12, %13, %14, %15}, {%16, %17, %18, %19}, %20, p, 1, 1, %22;\n}\n"
    : "+f"(d[0]), "+f"(d[1]), "+f"(d[2]), "+f"(d[3]), "+f"(d[4]), "+f"(d[5]), "+f"(d[6]), "+f"(d[7]), "+f"(d[8]), "+f"(d[9]), "+f"(d[10]), "+f"(d[11]), "+f"(d[12]), "+f"(d[13]), "+f"(d[14]), "+f"(d[15])
    : "r"(a0), "r"(a1), "r"(a2), "r"(a3), "l"(db), "r"(sd), "n"(TB));
}

template <int TB>
__device__ __forceinline__ void wg_n128_rs(float (&d)[64], uint32_t a0, uint32_t a1, uint32_t a2, uint32_t a3, uint64_t db, int sd) {
  asm volatile("{\n.reg .pred p;\nsetp.ne.b32 p, %69, 0;\n"
    "wgmma.mma_async.sync.aligned.m64n128k16.f32.bf16.bf16 {%0, %1, %2, %3, %4, %5, %6, %7, %8, %9, %10, %11, %12, %13, %14, %15, %16, %17, %18, %19, %20, %21, %22, %23, %24, %25, %26, %27, %28, %29, %30, %31, %32, %33, %34, %35, %36, %37, %38, %39, %40, %41, %42, %43, %44, %45, %46, %47, %48, %49, %50, %51, %52, %53, %54, %55, %56, %57, %58, %59, %60, %61, %62, %63}, {%64, %65, %66, %67}, %68, p, 1, 1, %70;\n}\n"
    : "+f"(d[0]), "+f"(d[1]), "+f"(d[2]), "+f"(d[3]), "+f"(d[4]), "+f"(d[5]), "+f"(d[6]), "+f"(d[7]), "+f"(d[8]), "+f"(d[9]), "+f"(d[10]), "+f"(d[11]), "+f"(d[12]), "+f"(d[13]), "+f"(d[14]), "+f"(d[15]), "+f"(d[16]), "+f"(d[17]), "+f"(d[18]), "+f"(d[19]), "+f"(d[20]), "+f"(d[21]), "+f"(d[22]), "+f"(d[23]), "+f"(d[24]), "+f"(d[25]), "+f"(d[26]), "+f"(d[27]), "+f"(d[28]), "+f"(d[29]), "+f"(d[30]), "+f"(d[31]), "+f"(d[32]), "+f"(d[33]), "+f"(d[34]), "+f"(d[35]), "+f"(d[36]), "+f"(d[37]), "+f"(d[38]), "+f"(d[39]), "+f"(d[40]), "+f"(d[41]), "+f"(d[42]), "+f"(d[43]), "+f"(d[44]), "+f"(d[45]), "+f"(d[46]), "+f"(d[47]), "+f"(d[48]), "+f"(d[49]), "+f"(d[50]), "+f"(d[51]), "+f"(d[52]), "+f"(d[53]), "+f"(d[54]), "+f"(d[55]), "+f"(d[56]), "+f"(d[57]), "+f"(d[58]), "+f"(d[59]), "+f"(d[60]), "+f"(d[61]), "+f"(d[62]), "+f"(d[63])
    : "r"(a0), "r"(a1), "r"(a2), "r"(a3), "l"(db), "r"(sd), "n"(TB));
}


template <int N>
__device__ __forceinline__ void feature_shifted(float (&p)[16], const float (&p2)[16], float sc0, float sc1, uint32_t (&o)[N]) {
#pragma unroll 1
  for (int it = 0; it < N / 8; it++) {
    float e[16], s[2];
#pragma unroll
    for (int r = 0; r < 2; r++) {
      const float* x = p + 2 * r;
      const float sc = r ? sc1 : sc0;
      float mx = fmaxf(fmaxf(fmaxf(x[0], x[1]), fmaxf(x[4], x[5])), fmaxf(fmaxf(x[8], x[9]), fmaxf(x[12], x[13])));
      mx = fmaxf(mx, __shfl_xor_sync(0xffffffffu, mx, 1));
      mx = fmaxf(mx, __shfl_xor_sync(0xffffffffu, mx, 2));
      s[r] = 0.f;
#pragma unroll
      for (int i = 0; i < 8; i++) {
        const int n = (i >> 1) * 4 + 2 * r + (i & 1);
        e[n] = ex2((p[n] - mx) * sc);
        s[r] += e[n];
      }
      s[r] += __shfl_xor_sync(0xffffffffu, s[r], 1);
      s[r] += __shfl_xor_sync(0xffffffffu, s[r], 2);
      s[r] = rcp(s[r]);
    }
#pragma unroll
    for (int j = 0; j < N - 8; j++) o[j] = o[j + 8];
#pragma unroll
    for (int j = 0; j < 8; j++) o[N - 8 + j] = pack_bf16(e[2 * j] * s[j & 1], e[2 * j + 1] * s[j & 1]);
#pragma unroll
    for (int i = 0; i < 16; i++) p[i] = (N > 16 && (it & 1)) ? p2[i] : -p[i];
  }
}
constexpr float FAST_LIMIT = RCPG == 2 ? 0x1p60f : RCPG == 4 ? 0x1p30f : 0x1p15f;
template <bool FULL, class H>
__device__ __forceinline__ float feature_fast(const float* p, float sc0, float sc1, uint32_t* o, float (&sp)[2], H hook) {
  float e[16], r[8], sm[2] = {0.f, 0.f};
  sp[0] = 0.f; sp[1] = 0.f;
#pragma unroll
  for (int i = 0; i < 16; i++) e[i] = ex2(p[i] * ((i & 2) ? sc1 : sc0));
#pragma unroll
  for (int i = 0; i < 8; i++) r[i] = e[2 * i] * e[2 * i + 1];
#pragma unroll
  for (int i = 0; i < 2; i++) {
    if (RCPG == 2) {
#pragma unroll
      for (int j = 0; j < 4; j++) r[2 * j + i] = rcp(r[2 * j + i]);
    } else {
      float u = r[i] * r[2 + i], w = r[4 + i] * r[6 + i];
      if (RCPG == 4) { u = rcp(u); w = rcp(w); }
      else { const float z = rcp(u * w), y = z * u; u = z * w; w = y; }
      const float c = u * r[i], d = w * r[4 + i];
      r[i] = u * r[2 + i]; r[2 + i] = c; r[4 + i] = w * r[6 + i]; r[6 + i] = d;
    }
  }
#pragma unroll
  for (int i = 0; i < 8; i++) {
    const float t = e[2 * i] + e[2 * i + 1];
    sp[i & 1] += t; sm[i & 1] = fmaf(t, r[i], sm[i & 1]);
  }
  const float tot = (sp[0] + sp[1]) + (sm[0] + sm[1]);
#pragma unroll
  for (int m = 1; m <= 2; m <<= 1)
#pragma unroll
    for (int i = 0; i < 2; i++) { sp[i] += __shfl_xor_sync(0xffffffffu, sp[i], m); sm[i] += __shfl_xor_sync(0xffffffffu, sm[i], m); }
  hook();
#pragma unroll
  for (int i = 0; i < 2; i++) {
    if (FULL && RCPG > 2) {
      const float z = rcp(sp[i] * sm[i]), y = z * sp[i];
      sp[i] = z * sm[i]; sm[i] = y;
    } else {
      sm[i] = FULL ? rcp(sm[i]) : sp[i] * rcp(sm[i]);
      if (FULL) sp[i] = rcp(sp[i]);
    }
  }
#pragma unroll
  for (int i = 0; i < 8; i++) {
    const float c = r[i] * sm[i & 1];
    o[i] = FULL ? pack_bf16(e[2 * i] * sp[i & 1], e[2 * i + 1] * sp[i & 1]) : pack_bf16(e[2 * i], e[2 * i + 1]);
    o[8 + i] = pack_bf16(e[2 * i + 1] * c, e[2 * i] * c);
  }
  return tot;
}
__device__ __forceinline__ bool warp_fails(bool ok) { return __builtin_expect(!__all_sync(0xffffffffu, ok), 0); }
constexpr uint32_t OTAG = 0x00010001u;
__device__ __forceinline__ void attn_out(const float (&u)[20], const float (&sp)[2], uint32_t tg, uint32_t sdst, uint4* dst) {
  const float d0 = rcp(fmaf(sp[0], 1e-6f, u[16])), d1 = rcp(fmaf(sp[1], 1e-6f, u[18]));
  uint32_t r[8];
#pragma unroll
  for (int j = 0; j < 8; j++) r[j] = pack_bf16(u[2 * j] * ((j & 1) ? d1 : d0), u[2 * j + 1] * ((j & 1) ? d1 : d0));
  r[0] = (r[0] & ~OTAG) | tg; r[4] = (r[4] & ~OTAG) | tg;
  st_rec16(dst, r[0], r[1], r[2], r[3]);
  st_rec16(dst + 32, r[4], r[5], r[6], r[7]);
  sts_u4(sdst, r[0], r[1], r[2], r[3]);
  sts_u4(sdst + 512, r[4], r[5], r[6], r[7]);
}

constexpr float L2E = 1.4426950408889634f;

__device__ __forceinline__ int pc_chunk(int j, int cb) {
  const int c = j > 8, e = j - 2 - 7 * c;
  return j < 2 ? 2 * cb + j : 2 * (e == cb ? 7 : e) + c;
}
constexpr unsigned long long Q_ASLOTS = 0x9763097630976309ull, Q_BSLOTS = 0x1854218542185421ull;
constexpr unsigned long long Q_CHUNKS = 0xBA9876543210EDCFull;
constexpr unsigned long long PC_ASLOTS = 0x20BA20BA20BA20BAull, PC_BSLOTS = 0x3765437654376543ull;
constexpr unsigned long long FFN_SLOTS = 0xBA9854C11987ull;
constexpr unsigned long long FFN_ORDER = 0xBA7654983210ull;
constexpr unsigned long long FFN_WAIT0 = 0x7C4B4A493F3F3E3Eull, FFN_WAIT1 = 0x6C6B6C6Bull;
constexpr unsigned long long FFN_PACE0 = 0x6A69939291907F44ull, FFN_PACE1 = 0x97969594ull;
constexpr unsigned long long WO_WAIT0 = 0x626160483D3D3C3Cull, WO_WAIT1 = 0x6A69686766656463ull;
constexpr unsigned long long WO_PACE0 = 0x527F502Full, WO_PACE1 = 0x0ull;
constexpr int X_PACE = 81;
__device__ __forceinline__ uint32_t tab4(unsigned long long t, int i) { return (uint32_t)(t >> (4 * i)) & 15u; }
__device__ __forceinline__ uint32_t tab8(unsigned long long lo, unsigned long long hi, int i) { return (uint32_t)((i < 8 ? lo : hi) >> (8 * (i & 7))) & 255u; }

__device__ __forceinline__ float sum8(uint4 v) {
  return ((bf_lo(v.x) + bf_hi(v.x)) + (bf_lo(v.y) + bf_hi(v.y))) + ((bf_lo(v.z) + bf_hi(v.z)) + (bf_lo(v.w) + bf_hi(v.w)));
}
__device__ __forceinline__ void acc2(uint32_t v, float sh, float& s, float& q) {
  const float a = bf_lo(v) - sh, c = bf_hi(v) - sh;
  s += a + c; q = fmaf(a, a, fmaf(c, c, q));
}
__device__ __forceinline__ float warp_sum(float s) {
#pragma unroll
  for (int m = 16; m >= 1; m >>= 1) s += __shfl_xor_sync(0xffffffffu, s, m);
  return s;
}
__device__ __forceinline__ uint32_t ln_res(uint32_t h, float a, float c, uint32_t& n) {
  const float l = bf_lo(h), u = bf_hi(h);
  n = pack_bf16(fmaf(l, a, c), fmaf(u, a, c));
  return pack_bf16(l + bf_lo(n), u + bf_hi(n));
}

__device__ __forceinline__ uint64_t ext_a(uint32_t sb, uint32_t row) { return mk_desc(sb + 12 * SLOT + 4096 + row * 16, 4096 - row * 16, 128, 0); }
__device__ __forceinline__ uint64_t ext_b(uint32_t sb, uint32_t part) { return mk_desc(sb + 12 * SLOT + part * 2048, 1024, 0, 1); }
__device__ __forceinline__ uint32_t split_bf16(float v) { return pack_bf16(v, v - bf_round(v)); }

__global__ void __launch_bounds__(NTHREADS, 1) fused_kernel(const __grid_constant__ Params P) {
  extern __shared__ __align__(1024) uint8_t smem_raw[];
  const uint32_t sb = smem_u32(smem_raw);
  const uint32_t bars = sb + OFF_BAR;
  const int tid = threadIdx.x;
  const int wg = __shfl_sync(0xffffffffu, tid >> 7, 0);
  const int warp = __shfl_sync(0xffffffffu, (tid >> 5) & 3, 0);
  const int lane = tid & 31;
  const int b = (blockIdx.x & 1) * 64 + (blockIdx.x >> 1);
  const bool ffn = (blockIdx.x & 7) != 7;
  const int fi = blockIdx.x - (blockIdx.x >> 3);
  const int rbk = b >> 4, hp = b & 15;
  const int rb = b >> 3, cb = b & 7;
#define BAR(i) (bars + 8u * (uint32_t)(i))
#define MMA_IDS \
    const int tid = fresh_tid(), lane = tid & 31; \
    const bool leader = (tid & 127) == 0; \
    const uint32_t srow = (uint32_t)(warp * 16 + (lane & 7) + ((lane >> 3) & 1) * 8); \
    const uint32_t sx = (uint32_t)(lane >> 4) ^ (srow & 7); \
    const int c2 = (lane & 3) * 2, lr = warp * 16 + (lane >> 2); \
    (void)leader; (void)sx; (void)c2; (void)lr;

  auto load_kv = [&](int it) {
    const uint32_t s = sb + (uint32_t)(it & 3) * 3 * SLOT, fb = BAR(B_FKV + it);
    mbar_expect_tx(fb, 3 * SLOT);
    tma_load_2d(s, &P.mX, fb, it * 64, rb * 128);
    tma_load_2d(s + SLOT, &P.mX, fb, it * 64, (rb ^ 1) * 128);
    tma_load_2d(s + 2 * SLOT, &P.mW, fb, 1024 + hp * 64, it * 64);
    tma_load_2d(s + 2 * SLOT + 8192, &P.mW, fb, 2048 + hp * 64, it * 64);
  };
  auto prefetch = [&](int c) {
    if (c < 2) { l2_prefetch(P.wo + b * 8192 + c * 4096, 8192); return; }
    if (!ffn) return;
    const int e = c - 2;
    if (e < 16) {
      asm volatile("cp.async.bulk.prefetch.tensor.2d.L2.global.tile [%0, {%1, %2}];"
                   :: "l"((e & 1) ? &P.mWuP : &P.mWgP), "r"((fi >> 1) * 64), "r"((e >> 1) * 128 + (fi & 1) * 64) : "memory");
    } else {
      l2_prefetch(P.wd + (size_t)fi * 32768 + (e - 16) * 4096, 8192);
    }
  };

  {
    const int w16 = wg * 4 + warp;
    const uint32_t cnt = w16 == 14 ? 128u : ((0x300Cu >> w16) & 1u) + 1u;
    if (elect()) {
      if (w16 == 11) {
#pragma unroll
        for (int i = 0; i < 4; i++) mbar_init(BAR(B_FKV + i), 1u);
        asm volatile("fence.mbarrier_init.release.cluster;" ::: "memory");
        load_kv(0);
      }
#pragma unroll
      for (int i = 0; i < 8; i++)
        if (w16 || i >= 4) mbar_init(BAR(w16 * 8 + i), w16 == 15 ? (uint32_t)(MISC_COUNTS >> (8 * i)) & 255u : cnt);
      mbar_init(BAR(B_FS + w16), w16 >= 14 ? 2u : 1u);
      mbar_init(BAR(B_FW + w16), 1u);
      asm volatile("fence.mbarrier_init.release.cluster;" ::: "memory");
    }
    __syncwarp();
    if (w16 == 11 && elect()) {
#pragma unroll 1
      for (int i = 1; i < 4; i++) load_kv(i);
    }
    __syncwarp();
  }

  if (wg >= 2) {
    if (wg == 3) {
      asm volatile("setmaxnreg.dec.sync.aligned.u32 64;");
      asm volatile("barrier.sync 0;" ::: "memory");
        if (warp) {
          const int q = 3 * b + warp - 1, cg = q % 96, kq = q / 96;
          const uint32_t buf = sb + (warp == 3 ? OFF_PHIQ : 12 * SLOT + (warp - 1) * 8192);
          const uint32_t fb = BAR(B_FS + (warp - 1) * 4);
          mbar_wait(BAR(B_FKV + 5));
          if (elect()) {
#pragma unroll
            for (int p = 0; p < 2; p++) { mbar_expect_tx(fb + p * 8, 4096); tma_load_2d(buf + p * 4096, &P.mWs, fb + p * 8, cg * 32, kq * 256 + p * 64); }
          }
          float cs[8];
#pragma unroll
          for (int i = 0; i < 8; i++) cs[i] = 0.f;
          const unsigned ep = ld_relaxed(&g_epoch);
#pragma unroll 1
          for (int p = 0; p < 4; p++) {
            mbar_wait(fb + p * 8);
            uint4 v[8];
#pragma unroll
            for (int i = 0; i < 8; i++) v[i] = lds_u4(buf + (p & 1) * 4096 + i * 512 + lane * 16);
            if (p < 2) {
              uint32_t dep = 0;
#pragma unroll
              for (int i = 0; i < 8; i++) dep ^= v[i].x;
              const int n = p + 2 + (int)__shfl_sync(0xffffffffu, zero_after(dep), 0);
              if (elect()) {
                mbar_expect_tx(fb + n * 8, 4096);
                tma_load_2d(buf + (n & 1) * 4096, &P.mWs, fb + n * 8, cg * 32, kq * 256 + n * 64);
              }
            }
#pragma unroll
            for (int i = 0; i < 8; i += 2) {
              cs[0] += bf_lo(v[i].x) + bf_lo(v[i + 1].x); cs[1] += bf_hi(v[i].x) + bf_hi(v[i + 1].x);
              cs[2] += bf_lo(v[i].y) + bf_lo(v[i + 1].y); cs[3] += bf_hi(v[i].y) + bf_hi(v[i + 1].y);
              cs[4] += bf_lo(v[i].z) + bf_lo(v[i + 1].z); cs[5] += bf_hi(v[i].z) + bf_hi(v[i + 1].z);
              cs[6] += bf_lo(v[i].w) + bf_lo(v[i + 1].w); cs[7] += bf_hi(v[i].w) + bf_hi(v[i + 1].w);
            }
          }
          {
            const bool u4 = lane & 16, u2 = lane & 8, u1 = lane & 4;
#pragma unroll
            for (int i = 0; i < 4; i++) cs[i] = (u4 ? cs[4 + i] : cs[i]) + __shfl_xor_sync(0xffffffffu, u4 ? cs[i] : cs[4 + i], 16);
#pragma unroll
            for (int i = 0; i < 2; i++) cs[i] = (u2 ? cs[2 + i] : cs[i]) + __shfl_xor_sync(0xffffffffu, u2 ? cs[i] : cs[2 + i], 8);
            cs[0] = (u1 ? cs[1] : cs[0]) + __shfl_xor_sync(0xffffffffu, u1 ? cs[0] : cs[1], 4);
          }
          if (warp == 3 && elect()) {
            mbar_expect_tx(BAR(B_PHI), 12288);
            tma_load_2d(sb + OFF_PHIK, &P.mPhi, BAR(B_PHI), 0, hp * 64);
            tma_load_2d(sb + OFF_PHIQ, &P.mPhi, BAR(B_PHI), (int)zero_after(__float_as_uint(cs[0])), cb * 128);
            tma_load_2d(sb + OFF_PHIQ + 4096, &P.mPhi, BAR(B_PHI), (int)zero_after(__float_as_uint(cs[0])), cb * 128 + 64);
          }
          st_rec8(&g_colsum[kq][cg * 32 + (lane & 3) * 8 + (lane >> 2)], __float_as_uint(cs[0]), ep + 1);
          if (lane == 0) mbar_arrive(BAR(B_CSD));
        }
      asm volatile("setmaxnreg.dec.sync.aligned.u32 32;");
      if (warp == 0) {
#pragma unroll 1
        for (int it = 4; it < 16; it++) {
          mbar_wait(BAR(B_DKV + it - 4));
          if (elect()) load_kv(it);
        }
#pragma unroll 1
        for (int it = 0; it < 16; it++) {
          const uint32_t fb = BAR(B_FQ + it), s = sb + tab4(Q_BSLOTS, it) * SLOT;
          const int kc = (int)tab4(Q_CHUNKS, it) * 64;
          if (it == 5) mbar_wait(BAR(B_DKV + 15));
          mbar_wait(it >= 5 ? BAR(B_DQ + it - 5) : BAR(B_DKV + 12 + (it >> 1)));
          if (elect()) {
            mbar_expect_tx(fb, it < 4 ? SLOT : 2 * SLOT);
            if (it >= 4) tma_load_2d(sb + tab4(Q_ASLOTS, it) * SLOT, &P.mX, fb, kc, rb * 128);
            tma_load_2d(s, &P.mW, fb, cb * 128, kc);
            tma_load_2d(s + 8192, &P.mW, fb, cb * 128 + 64, kc);
          }
        }
        mbar_wait(BAR(B_DQ + 11));
        mbar_wait(BAR(X_PACE));
        if (elect()) {
          mbar_expect_tx(BAR(B_FX), 2 * SLOT);
          tma_load_2d(sb, &P.mX, BAR(B_FX), cb * 128, rb * 128);
          tma_load_2d(sb + 2 * SLOT, &P.mX, BAR(B_FX), cb * 128 + 64, rb * 128);
        }
      } else {
        if (warp == 1) {
#pragma unroll 1
          for (int j = 0; j < 16; j++) {
            const uint32_t s = sb + tab4(PC_BSLOTS, j) * SLOT, fb = BAR(B_FB + j);
            const int kc = pc_chunk(j, cb);
            mbar_wait(BAR(tab8(WO_WAIT0, WO_WAIT1, j)));
            mbar_wait(BAR(tab8(WO_PACE0, WO_PACE1, j)));
            if (elect()) {
              mbar_expect_tx(fb, SLOT);
              tma_load_2d(s, &P.mWo, fb, cb * 128, kc * 64);
              tma_load_2d(s + 8192, &P.mWo, fb, cb * 128 + 64, kc * 64);
            }
          }
        } else if (warp == 3) {
#pragma unroll 1
          for (int c = 0; c < 26; c++) {
            mbar_wait(BAR(c < 8 ? B_DKV + 8 + c : B_DQ + ((c - 8) >> 1)));
            if (elect()) prefetch(c);
            if (ORST == 2 && c >= ORS0 && c < ORS0 + 8) {
#pragma unroll
              for (int i = 0; i < 8; i++) st_rec16(&g_o[rb * 8 + c - ORS0][2 * cb][i][lane], 0u, 0u, 0u, 0u);
            }
          }
          __syncwarp();
          if (ORST > 2) {
            mbar_wait(BAR(B_DQ + ORST));
#pragma unroll 8
            for (int i = 0; i < 64; i++) st_rec16(&g_o[rb * 8 + (i >> 3)][2 * cb][i & 7][lane], 0u, 0u, 0u, 0u);
            __syncwarp();
          }
          if (lane == 0) mbar_arrive(BAR(B_KVRDY));
          mbar_wait(BAR(B_DC + 10));
#pragma unroll 1
          for (int i = 0; i < 4; i++) st_rec16(&g_hstat[rb][cb][i * 32 + lane], 0u, 0u, 0u, 0u);
          st_rec16(reinterpret_cast<uint4*>(&g_candx[rb][cb * 64]) + lane, 0u, 0u, 0u, 0u);
          if (lane < 2) st_rec16(reinterpret_cast<uint4*>(&g_key[cb][rb][0]) + lane, 0u, 0u, 0u, 0u);
          __syncwarp();
          if (lane == 0) mbar_arrive(BAR(B_RESET2));
        } else {
          mbar_wait(BAR(B_DQ + RSTQ));
#pragma unroll 1
          for (int i = 0; i < 12; i++) {
            st_rec16(&g_kvp[2 * hp][rbk][0][i * 32 + lane], 0u, 0u, 0u, 0u);
            st_rec16(&g_kvp[2 * hp + 1][rbk][0][i * 32 + lane], 0u, 0u, 0u, 0u);
          }
#pragma unroll 1
          for (int i = 0; i < 3; i++) st_rec16(&g_kvr[2 * hp + (lane >> 4)][i][rbk * 16 + (lane & 15)], 0u, 0u, 0u, 0u);
          __syncwarp();
          if (lane == 0) mbar_arrive(BAR(B_RESET));
          if (ffn) {
#pragma unroll 1
            for (int n = 0; n < 12; n++) {
              const int i = (int)tab4(FFN_ORDER, n);
              const uint32_t s = sb + tab4(FFN_SLOTS, i) * SLOT, fb = BAR(B_FW + i);
              mbar_wait(BAR(tab8(FFN_WAIT0, FFN_WAIT1, n)));
              mbar_wait(BAR(tab8(FFN_PACE0, FFN_PACE1, n)));
              if (elect()) {
                mbar_expect_tx(fb, SLOT);
                if (i < 8) tma_load_2d_ef(s, (i & 1) ? &P.mWu : &P.mWg, fb, fi * 32, (i >> 1) * 256);
                else {
#pragma unroll
                  for (int e = 0; e < 4; e++) tma_load_2d_ef(s + e * 4096, &P.mWd, fb, (i - 8) * 256 + e * 64, fi * 32);
                }
              }
            }
          }
        }
      }
    } else {
      asm volatile("barrier.sync 0;" ::: "memory");
      const int t = tid - 256;
      const unsigned tag = ld_relaxed(&g_epoch) + 1;
      if (warp == 0) {
        float s = 0.f;
#pragma unroll
        for (int i = 0; i < 4; i++) s += sum8(ldg_nc16(P.wr + i * 256 + lane * 8));
        const uint2 w = *reinterpret_cast<const uint2*>(P.wr + cb * 128 + lane * 4);
        s = warp_sum(s);
        if (lane == 0) { sts_f(sb + OFF_RED, s); sts_u(sb + OFF_RED + 4, tag); }
        sts_f2(sb + OFF_WR + lane * 16, bf_lo(w.x), bf_hi(w.x));
        sts_f2(sb + OFF_WR + lane * 16 + 8, bf_lo(w.y), bf_hi(w.y));
      }
      __syncwarp();
      uint4 xv[16];
#pragma unroll
      for (int i = 0; i < 16; i++) {
        if (i == 0) mbar_wait(BAR(B_FKV + 5));
        xv[i] = ldg_nc16(P.x + (size_t)(b * 16 + warp * 4 + (lane >> 3)) * DM + i * 64 + (lane & 7) * 8);
      }
      {
        const float sh = __shfl_sync(0xffffffffu, bf_lo(xv[0].x), lane & 24);
        float s0 = 0.f, q0 = 0.f, s1 = 0.f, q1 = 0.f;
#pragma unroll
        for (int i = 0; i < 16; i++) { acc2(xv[i].x, sh, s0, q0); acc2(xv[i].y, sh, s1, q1); acc2(xv[i].z, sh, s0, q0); acc2(xv[i].w, sh, s1, q1); }
        s0 += s1; q0 += q1;
#pragma unroll
        for (int m = 4; m >= 1; m >>= 1) { s0 += __shfl_xor_sync(0xffffffffu, s0, m); q0 += __shfl_xor_sync(0xffffffffu, q0, m); }
        s0 *= (1.f / DM);
        const float var = fmaxf(q0 * (1.f / DM) - s0 * s0, 0.f);
        if ((lane & 7) == 0) st_rec16(&g_rowstat[b * 16 + warp * 4 + (lane >> 3)], __float_as_uint(rsq(var + 1e-5f)), __float_as_uint(-(s0 + sh)), 0u, tag);
      }
      {
        const uint4* rp = &g_rowstat[rb * 128 + t];
        const uint4* rq = &g_rowstat[(rb ^ 1) * 128 + t];
        const uint2* c0 = &g_colsum[0][1024 + (t >> 6) * 1024 + hp * 64 + (t & 63)];
        const uint2* c1 = &g_colsum[0][cb * 128 + t];
        uint4 v0, v1; uint2 u[8];
#pragma unroll 1
        for (int it = 0; it < SPIN; it++) {
          v0 = ld_rec16(rp); v1 = ld_rec16(rq);
          bool ok = true;
#pragma unroll
          for (int i = 0; i < 4; i++) { u[i] = ld_rec8(c0 + i * 3072); u[4 + i] = ld_rec8(c1 + i * 3072); }
#pragma unroll
          for (int i = 0; i < 8; i++) ok = ok && u[i].y == tag;
          if (__all_sync(0xffffffffu, ok && v0.w == tag && v1.w == tag)) break;
          __nanosleep(100);
        }
        sts_u(sb + OFF_RSTAT + t * 8, v0.x); sts_u(sb + OFF_RSTAT + (t + 128) * 8, v1.x);
        mbar_wait(BAR(B_CSD));
        {
          const uint32_t m0 = split_bf16(__uint_as_float(v0.y)), m1 = split_bf16(__uint_as_float(v1.y));
          sts_u4(sb + 12 * SLOT + 4096 + t * 16, m0, m0 & 0xFFFFu, 0u, 0u);
          sts_u4(sb + 12 * SLOT + 6144 + t * 16, m1, m1 & 0xFFFFu, 0u, 0u);
          sts_u2(sb + 12 * SLOT + 8192 + t * 8, 0u, 0u);
        }
#pragma unroll
        for (int e = 0; e < 2; e++) {
          const uint32_t hl = split_bf16((__uint_as_float(u[4 * e].x) + __uint_as_float(u[4 * e + 1].x)) + (__uint_as_float(u[4 * e + 2].x) + __uint_as_float(u[4 * e + 3].x)));
          const uint32_t a = sb + 12 * SLOT + e * 2048 + (t >> 6) * 1024 + (t & 7) * 2, ch = (uint32_t)(t >> 3) & 7u;
#pragma unroll
          for (uint32_t r = 0; r < 8; r++) sts_h(a + r * 128 + ((ch ^ r) << 4), r < 2 ? hl : r == 2 ? hl >> 16 : 0u);
        }
        sts_u(sb + OFF_ONES + t * 4, 0x3F803F80u);
        sts_u(sb + OFF_ONES + 512 + t * 4, 0x3F803F80u);
        fence_async_smem();
        bar_sync(3, 128);
      }
      asm volatile("setmaxnreg.inc.sync.aligned.u32 160;");
      {
        float a0[64], a1[64];
        {
          wg_fence();
          wg_n128<0, 1>(a0, ext_a(sb, 0), ext_b(sb, 1), 0);
          wg_n128<0, 1>(a1, ext_a(sb, 64), ext_b(sb, 1), 0);
          wg_commit();
          wg_wait<0>();
          mbar_arrive(BAR(B_STAT));
        }
        {
          const bool leader = (tid & 127) == 0;
#pragma unroll 1
          for (int it = 12; it < 16; it++) mbar_wait(BAR(B_FKV + it));
          mbar_wait(BAR(B_QGO));
          unsigned long long ta = Q_ASLOTS, tb = Q_BSLOTS;
          const uint32_t d0 = (uint32_t)mk_desc(sb, 16, 1024, 1), d1 = (uint32_t)mk_desc(sb, 8192, 1024, 1);
          uint32_t na = d0 + tab4(ta, 0) * 1024, nb = d1 + tab4(tb, 0) * 1024;
#pragma unroll 1
          for (int it = 0; it < 16; it++) {
            mbar_wait(BAR(B_FQ + it));
            const uint64_t da = QPRE ? mk_desc(0, 0, 1024, 1) | na : mk_desc(sb + tab4(Q_ASLOTS, it) * SLOT, 16, 1024, 1);
            const uint64_t db = QPRE ? mk_desc(0, 0, 1024, 1) | nb : mk_desc(sb + tab4(Q_BSLOTS, it) * SLOT, 8192, 1024, 1);
#pragma unroll
            for (int hf = 0; hf < 2; hf++) {
              int yt = THR > hf ? fresh_tid() : tid;
              if (hf && THR > 1) asm volatile("mov.u32 %0, %%tid.y;" : "=r"(yt));
              wg_fence();
#pragma unroll
              for (int kk = 2 * hf; kk < 2 * hf + 2; kk++) {
                wg_n128<0, 1>(a0, da + kk * 2, db + kk * 128, 1);
                if (THR > 2 && kk == 2 * hf && yt == 8192) pin_order();
                wg_n128<0, 1>(a1, da + kk * 2 + 512, db + kk * 128, 1);
              }
              wg_commit();
              if (QPRE && hf == 0) {
                ta >>= 4; tb >>= 4;
                asm volatile("mad.lo.u32 %0, %2, 1024, %4;\nmad.lo.u32 %1, %3, 1024, %5;" : "=r"(na), "=r"(nb) : "r"((uint32_t)ta & 15u), "r"((uint32_t)tb & 15u), "r"(d0), "r"(d1));
              }
              wg_wait<1>();
              if (hf == 0 && it > 0 && (yt & 127) == 0) mbar_arrive(BAR(B_DQ + it - 1));
              if (hf == 1 && THR > 1 && yt == 4096) mbar_arrive(BAR(B_F1));
            }
          }
          mbar_wait(BAR(B_KVFREE));
          wg_wait<0>();
          if (leader) mbar_arrive(BAR(B_DQ + 15));
        }
        MMA_IDS
#pragma unroll
        for (int c = 0; c < 2; c++) {
#pragma unroll
          for (int jj = 0; jj < 4; jj++)
#pragma unroll
            for (int mb = 0; mb < 2; mb++) {
              const float* a = mb ? &a1[32 * c + 8 * jj] : &a0[32 * c + 8 * jj];
              stsm_x4(sb + (10 + c) * SLOT + mb * 8192 + srow * 128 + ((sx ^ (2 * jj)) << 4),
                      pack_bf16(a[0], a[1]), pack_bf16(a[2], a[3]), pack_bf16(a[4], a[5]), pack_bf16(a[6], a[7]));
            }
          fence_async_smem();
          mbar_arrive(BAR(B_QD + c));
        }
        uint4 a[12];
#pragma unroll
        for (int i = 0; i < 12; i++) a[i] = make_uint4(0u, 0u, 0u, tag - 1);
#pragma unroll 1
        for (int it = 0; it < SPIN; it++) {
          bool ok = true;
#pragma unroll
          for (int i = 0; i < 12; i++) ld_rec16_stale(a[i], &g_kvr[4 * cb][i][tid & 127], tag);
#pragma unroll
          for (int i = 0; i < 12; i++) ok = ok && a[i].w == tag;
          if (__all_sync(0xffffffffu, ok)) break;
        }
        const uint32_t kx = (uint32_t)(lane >> 4) ^ ((srow >> 1) & 3);
#pragma unroll
        for (int h = 0; h < 4; h++) {
          const uint32_t base = sb + 12 * SLOT + h * 4096 + srow * 64;
          stsm_x4(base + (kx << 4), a[3 * h].x, a[3 * h].y, a[3 * h].z, a[3 * h + 1].x);
          stsm_x4(base + ((kx ^ 2) << 4), a[3 * h + 1].y, a[3 * h + 1].z, a[3 * h + 2].x, a[3 * h + 2].y);
          if (h & 1)
            stsm_x4(sb + 13 * SLOT + srow * 64 + ((kx ^ (h - 1)) << 4), (a[3 * h - 1].z & 0xFFFFu) | 0x3F800000u, (a[3 * h - 1].z >> 16) | 0x3F800000u,
                    (a[3 * h + 2].z & 0xFFFFu) | 0x3F800000u, (a[3 * h + 2].z >> 16) | 0x3F800000u);
        }
        fence_async_smem();
        __syncwarp();
        if (lane == 0) mbar_arrive(BAR(B_KVRDY));
      }
    }
    if (wg == 3) mbar_wait(BAR(B_DC + 15));
    asm volatile("setmaxnreg.inc.sync.aligned.u32 160;");
    const int w8 = (wg - 2) * 4 + warp;
    uint32_t wf[32][4], wd[16][4];
    if (ffn) {
      const int lane = fresh_tid() & 31;
      const uint32_t mrow = (uint32_t)((lane & 7) + (lane >> 4) * 8), mch = (uint32_t)(lane >> 3) & 1u;
      mbar_wait(BAR(B_FW + w8));
      const uint32_t wsm = sb + tab4(FFN_SLOTS, w8) * SLOT + mrow * 64;
      const uint32_t sw = (mrow >> 1) & 3;
#pragma unroll
      for (int i = 0; i < 16; i++) {
        ldsm_x4_t(wf[2 * i], wsm + i * 1024 + ((mch ^ sw) << 4));
        ldsm_x4_t(wf[2 * i + 1], wsm + i * 1024 + (((2 + mch) ^ sw) << 4));
      }
      uint32_t dep = 0;
#pragma unroll
      for (int i = 0; i < 32; i++) dep ^= wf[i][0];
      if (w8 < 4 && lane == 0) mbar_arrive(BAR(B_REL + w8) + zero_after(dep));
    } else if (w8 == 0 && elect()) {
      mbar_arrive(BAR(B_REL));
    }
    if (ffn) {
      const int lane = fresh_tid() & 31;
      if (wg == 2) mbar_wait(BAR(B_DC + 12));
#pragma unroll
      for (int i = 0; i < 2; i++) st_rec16(reinterpret_cast<uint4*>(&g_ypart[w8 * 16 + i * 8 + (lane >> 2)][fi][0]) + (lane & 3), 0u, 0u, 0u, 0u);
      __syncwarp();
    }
    mbar_wait(BAR(B_DC + 15));
    asm volatile("setmaxnreg.inc.sync.aligned.u32 224;");
    if (ffn) {
      const int lane = fresh_tid() & 31;
      const uint32_t mrow = (uint32_t)((lane & 7) + (lane >> 4) * 8), mch = (uint32_t)(lane >> 3) & 1u;
      mbar_wait(BAR(B_FW + 8 + (w8 >> 1)));
      const uint32_t dsm = sb + tab4(FFN_SLOTS, 8 + (w8 >> 1)) * SLOT + (w8 & 1) * 8192 + mrow * 128;
#pragma unroll
      for (int i = 0; i < 8; i++) {
        const uint32_t a = dsm + (i >> 2) * 4096 + ((((uint32_t)(i & 3) * 2 + mch) ^ (mrow & 7)) << 4);
        ldsm_x4_t(wd[2 * i], a);
        ldsm_x4_t(wd[2 * i + 1], a + 2048);
      }
    }
    {
      const int t = fresh_tid() - 256, lane = t & 31;
      const uint32_t xs = sb + OFF_PHIQ + w8 * 512;
      const unsigned tag = lds_u(sb + OFF_RED + 4);
      uint32_t wkey;
      {
        uint2 v;
#pragma unroll 1
        for (int it = 0; it < SPIN; it++) {
          v = ld_rec8(&g_key[cb][lane & 15][0]);
          if (__all_sync(0xffffffffu, v.y == tag)) break;
        }
        wkey = __reduce_max_sync(0xffffffffu, v.x);
      }
      const int wrow = (0xFFFF - (int)(wkey & 0xFFFFu)) & (SEQ - 1);
      {
        const uint4* src = reinterpret_cast<const uint4*>(&g_candx[wrow >> 7][(w8 >> 1) * 128]) + lane;
        uint4 v0, v1;
#pragma unroll 1
        for (int it = 0; it < SPIN; it++) {
          v0 = ld_rec16(src); v1 = ld_rec16(src + 32);
          if (__all_sync(0xffffffffu, v0.y == tag && v0.w == tag && v1.y == tag && v1.w == tag)) break;
        }
        const uint32_t a = xs + (lane >> 3) * 64 + (lane & 1) * 32 + ((lane >> 1) & 3) * 4;
        sts_u(a, v0.x); sts_u(a + 16, v0.z); sts_u(a + 256, v1.x); sts_u(a + 272, v1.z);
        __syncwarp();
      }
      if (t == 0) mbar_arrive(BAR(B_ROW));
      if (b == 0 && t == 0) g_epoch = tag;
      if (ffn) {
        {
          uint4 xb[8];
#pragma unroll
          for (int i = 0; i < 8; i++) xb[i] = lds_u4(xs + i * 64 + (lane & 3) * 16);
          float d[16];
#pragma unroll
          for (int i = 0; i < 16; i++) d[i] = 0.f;
#pragma unroll
          for (int i = 0; i < 8; i++) {
            mma_bf16(&d[0], wf[4 * i], xb[i].x, xb[i].y); mma_bf16(&d[4], wf[4 * i + 1], xb[i].x, xb[i].y);
            mma_bf16(&d[8], wf[4 * i + 2], xb[i].z, xb[i].w); mma_bf16(&d[12], wf[4 * i + 3], xb[i].z, xb[i].w);
          }
          const int c = lane & 3;
          const float v = c == 0 ? d[0] + d[8] : c == 1 ? d[2] + d[10] : c == 2 ? d[4] + d[12] : d[6] + d[14];
          sts_f(sb + OFF_CS + (uint32_t)(w8 * 32 + c * 8 + (lane >> 2)) * 4, v);
        }
        bar_sync(2, 256);
        uint32_t ab[4];
        {
          const uint32_t pr = sb + OFF_CS + lane * 4;
          const float g = (lds_f(pr) + lds_f(pr + 256)) + (lds_f(pr + 512) + lds_f(pr + 768));
          const float u = (lds_f(pr + 128) + lds_f(pr + 384)) + (lds_f(pr + 640) + lds_f(pr + 896));
          const float act = g * rcp(1.f + ex2(-g * L2E)) * u;
          const uint32_t pair = pack_bf16(act, __shfl_down_sync(0xffffffffu, act, 1));
#pragma unroll
          for (int i = 0; i < 4; i++) ab[i] = __shfl_sync(0xffffffffu, pair, i * 8 + (lane & 3) * 2);
        }
        float d[32];
#pragma unroll
        for (int i = 0; i < 32; i++) d[i] = 0.f;
        {
#pragma unroll
          for (int i = 0; i < 8; i++) mma_bf16(&d[4 * i], wd[2 * i], ab[0], ab[1]);
#pragma unroll
          for (int i = 0; i < 8; i++) mma_bf16(&d[4 * i], wd[2 * i + 1], ab[2], ab[3]);
        }
        const int c = lane & 3;
#pragma unroll
        for (int i = 0; i < 4; i++) {
          const float v = c == 0 ? d[8 * i] : c == 1 ? d[8 * i + 2] : c == 2 ? d[8 * i + 4] : d[8 * i + 6];
          st_rec8(&g_ypart[w8 * 16 + i * 4 + c][fi][lane >> 2], __float_as_uint(v), tag);
        }
      }
      float y0 = 0.f, y1 = 0.f;
      uint4 fin;
      if (w8 == 7) {
#pragma unroll 1
        for (int it = 0; it < SPIN; it++) {
          fin = ld_rec16(&g_cand[wrow >> 7][b * 4 + (lane & 3)]);
          if (__all_sync(0xffffffffu, fin.w == tag)) break;
        }
      } else {
        const uint4* yp = reinterpret_cast<const uint4*>(&g_ypart[b][0][0]) + t;
        uint4 v0, v1;
#pragma unroll 1
        for (int it = 0; it < SPIN; it++) {
          v0 = ld_rec16(yp); v1 = ld_rec16(yp + 2 * NFFN);
          if (__all_sync(0xffffffffu, v0.y == tag && v0.w == tag && v1.y == tag && v1.w == tag)) break;
        }
        y0 = __uint_as_float(v0.x) + __uint_as_float(v1.x); y1 = __uint_as_float(v0.z) + __uint_as_float(v1.z);
      }
#pragma unroll
      for (int m = 4; m <= 16; m <<= 1) { y0 += __shfl_xor_sync(0xffffffffu, y0, m); y1 += __shfl_xor_sync(0xffffffffu, y1, m); }
      if (lane < 4) sts_f2(sb + OFF_RED + 64 + (uint32_t)(w8 * 8 + lane * 2) * 4, y0, y1);
      uint32_t u = wkey >> 16;
      u = (u & 0x8000u) ? (u & 0x7FFFu) : (~u & 0xFFFFu);
      const float sig = rcp(1.f + ex2(-__uint_as_float(u << 16) * L2E));
      bar_sync(2, 256);
      if (w8 == 7) {
        float2 v = lds_f2(sb + OFF_RED + 64 + lane * 8);
#pragma unroll
        for (int m = 4; m <= 16; m <<= 1) { v.x += __shfl_xor_sync(0xffffffffu, v.x, m); v.y += __shfl_xor_sync(0xffffffffu, v.y, m); }
        if (lane < 4)
          *reinterpret_cast<uint32_t*>(P.out + (size_t)wrow * DM + b * 8 + lane * 2) =
              pack_bf16(bf_lo(fin.y) + fmaf(v.x, sig, bf_lo(fin.x)), bf_hi(fin.y) + fmaf(v.y, sig, bf_hi(fin.x)));
      }
    }
  } else {
    asm volatile("setmaxnreg.inc.sync.aligned.u32 160;");
    asm volatile("barrier.sync 0;" ::: "memory");
    {
      const bool leader = (tid & 127) == 0;
      {
        float a0[64], a1[64];
#pragma unroll 1
        for (int it = 0; it < 16; it++) {
          mbar_wait(BAR(B_FKV + it));
          const uint32_t s = sb + (uint32_t)(it & 3) * 3 * SLOT;
          const uint64_t da = mk_desc(s + wg * SLOT, 16, 1024, 1), db = mk_desc(s + 2 * SLOT, 8192, 1024, 1);
          wg_fence();
#pragma unroll
          for (int kk = 0; kk < 4; kk++) {
            wg_n128<0, 1>(a0, da + kk * 2, db + kk * 128, (it | kk) != 0);
            wg_n128<0, 1>(a1, da + kk * 2 + 512, db + kk * 128, (it | kk) != 0);
          }
          wg_commit();
          wg_wait<1>();
          if (it > 0 && leader) mbar_arrive(BAR(B_DKV + it - 1));
        }
        mbar_wait(BAR(B_STAT));
        wg_fence();
        wg_n128<0, 1>(a0, ext_a(sb, wg * 128), ext_b(sb, 0), 1);
        wg_n128<0, 1>(a1, ext_a(sb, wg * 128 + 64), ext_b(sb, 0), 1);
        wg_commit();
        if (QG == 0 && leader) mbar_arrive(BAR(B_QGO));
        mbar_wait(BAR(B_PHI));
        wg_wait<0>();
        if (leader) mbar_arrive(BAR(B_DKV + 15));
        if (QG == 1 && leader) mbar_arrive(BAR(B_QGO));
        if (PIN & 2) pin_order();
        if (EXPV == 1) asm volatile("setmaxnreg.inc.sync.aligned.u32 200;");
        MMA_IDS
        const uint32_t rs = sb + OFF_RSTAT + (uint32_t)(wg * 128 + lr) * 8;
        const uint32_t vt = sb + 12 * SLOT + wg * 4096 + srow * 64 + (((uint32_t)(lane >> 4) ^ ((srow >> 1) & 3)) << 4);
        float pa[16], pb[16];
        uint32_t vp[16];
        const uint64_t dw = mk_desc(sb + OFF_PHIK, 16, 512, 2);
        auto pack_v = [&](const float* a, int mb) {
          const float r0 = lds_f(rs + mb * 512), r1 = lds_f(rs + mb * 512 + 64);
#pragma unroll
          for (int i = 0; i < 16; i++) vp[i] = pack_bf16(a[32 + 2 * i] * ((i & 1) ? r1 : r0), a[33 + 2 * i] * ((i & 1) ? r1 : r0));
        };
        auto put_v = [&]() {
#pragma unroll
          for (int jj = 0; jj < 4; jj++) stsm_x4((vt + (jj >> 1) * 8192) ^ (32 * (jj & 1)), vp[4 * jj], vp[4 * jj + 1], vp[4 * jj + 2], vp[4 * jj + 3]);
        };
        bar_sync(1, 256);
        pack_v(a0, 0);
        put_v();
        auto logits = [&](const uint32_t (&k)[16]) {
          wg_fence();
          wg_n32_rs<1>(pa, k[0], k[1], k[2], k[3], dw, 0);
          wg_n32_rs<1>(pb, k[8], k[9], k[10], k[11], dw + 128, 0);
          wg_n32_rs<1>(pa, k[4], k[5], k[6], k[7], dw + 64, 1);
          wg_n32_rs<1>(pb, k[12], k[13], k[14], k[15], dw + 192, 1);
          wg_commit();
        };
        uint32_t k0[16], k1[16];
        pin_order();
#pragma unroll
        for (int i = 0; i < 16; i++) k0[i] = pack_pin(a0[2 * i], a0[2 * i + 1]);
        logits(k0);
        if (leader) mbar_arrive(BAR(B_QGO2));
#pragma unroll
        for (int i = 0; i < 16; i++) k1[i] = pack_pin(a1[2 * i], a1[2 * i + 1]);
        pack_v(a1, 1);
        if (PIN & 1) pin_order();
        wg_wait<0>();
        float kv[20];
        auto half = [&](float (&p0)[16], float (&p1)[16], int mb) {
          const float sc0 = lds_f(rs + mb * 512) * L2E, sc1 = lds_f(rs + mb * 512 + 64) * L2E;
          const uint32_t ft = sb + 10 * SLOT + wg * 8192 + srow * 128 + (sx << 4);
          uint32_t fo[32];
          auto put = [&](int h) {
#pragma unroll
            for (int g = 4 * h; g < 4 * h + 4; g++) stsm_x4((ft + h * SLOT) ^ (32 * (g & 3)), fo[4 * g], fo[4 * g + 1], fo[4 * g + 2], fo[4 * g + 3]);
          };
          float sp[2];
          float tot = feature_fast<true>(p0, sc0, sc1, &fo[0], sp, [&]() {
            if (mb && KW == 0) {
              if (PIN & 128) pin_order();
              wg_wait<0>();
              bar_arrive(6 + wg, 256);
            }
          });
          if (mb) {
            if (KW == 1) {
#pragma unroll
              for (int i = 0; i < 16; i++) asm volatile("" : "+r"(fo[i]));
              wg_wait<0>();
              bar_arrive(6 + wg, 256);
            }
            bar_sync(7 - wg, 256);
            put_v();
          }
          put(0);
          tot += feature_fast<true>(p1, sc0, sc1, &fo[16], sp, []() {});
          put(1);
          if (warp_fails(tot < FAST_LIMIT)) {
            feature_shifted(p0, p1, sc0, sc1, fo);
            put(0);
            put(1);
          }
          if (mb == 0) logits(k1);
          fence_async_smem();
          bar_sync(1, 256);
          if (PIN & 4) pin_order();
          if (KIL && mb == 0) wg_wait<0>();
          const uint64_t d = mk_desc(sb + (10 + wg) * SLOT, 16, 1024, 1);
          const uint64_t e = mk_desc(sb + 12 * SLOT + wg * 8192, OFF_ONES - 12 * SLOT - wg * 8192, 512, 2);
          wg_fence();
#pragma unroll
          for (int kk = 0; kk < 8; kk++) wg_n40<1, 1>(kv, d + kk * 128, e + kk * (64 - (64 << 16)), (mb | kk) != 0);
          wg_commit();
        };
        half(pa, pb, 0);
        if (!KIL) wg_wait<1>();
        half(pa, pb, 1);
        mbar_wait(BAR(B_RESET));
        const unsigned tag = lds_u(sb + OFF_RED + 4);
        uint4* dst = &g_kvp[2 * hp + wg][rbk][0][tid & 127];
        const uint4* src = &g_kvp[2 * hp + (lane >> 4)][0][warp][rbk * 16 + (lane & 15)];
        uint4 a[8];
        if (wg == 0 && warp < 3) {
#pragma unroll
          for (int p = 0; p < 8; p++) a[p] = ld_rec16(src + p * 384);
        }
        wg_wait<0>();
        if (PIN & 8) pin_order();
        kv[17] = kv[18];
#pragma unroll
        for (int i = 0; i < 3; i++)
          st_rec16(dst + i * 128, pack_bf16(kv[6 * i], kv[6 * i + 1]), pack_bf16(kv[6 * i + 2], kv[6 * i + 3]), pack_bf16(kv[6 * i + 4], kv[6 * i + 5]), tag);
        if (leader) mbar_arrive(BAR(B_KVFREE));
        if (wg == 0 && warp < 3) {
#pragma unroll 1
          for (int it = 0; it < SPIN; it++) {
            bool ok = true;
#pragma unroll
            for (int p = 0; p < 8; p++) ld_rec16_stale(a[p], src + p * 384, tag);
#pragma unroll
            for (int p = 0; p < 8; p++) ok = ok && a[p].w == tag;
            if (__all_sync(0xffffffffu, ok)) break;
          }
          float v[6] = {0.f, 0.f, 0.f, 0.f, 0.f, 0.f};
#pragma unroll
          for (int p = 0; p < 8; p++) {
            v[0] += bf_lo(a[p].x); v[1] += bf_hi(a[p].x); v[2] += bf_lo(a[p].y); v[3] += bf_hi(a[p].y); v[4] += bf_lo(a[p].z); v[5] += bf_hi(a[p].z);
          }
          st_rec16(&g_kvr[2 * hp + (lane >> 4)][warp][rbk * 16 + (lane & 15)], pack_bf16(v[0], v[1]), pack_bf16(v[2], v[3]), pack_bf16(v[4], v[5]), tag);
        }
        if (ORST == 1) {
#pragma unroll
          for (int i = 0; i < 8; i++) st_rec16(&g_o[rb * 8 + wg * 4 + warp][2 * cb][i][lane], 0u, 0u, 0u, 0u);
        }
      }
    }
    if (EXPV == 1) asm volatile("setmaxnreg.dec.sync.aligned.u32 160;");
    const uint32_t stg = sb + wg * 8192;
    float s0 = 0.f, q0 = 0.f, d0 = 0.f, s1 = 0.f, q1 = 0.f, d1 = 0.f;
    {
      MMA_IDS
      const unsigned tag = lds_u(sb + OFF_RED + 4);
      const uint32_t t3 = tag % 3u + 1u, tg = (t3 & 1u) | ((t3 & 2u) << 15);
      const int ln = __shfl_sync(0xffffffffu, lane, lane);
      uint4* const og = &g_o[rb * 8 + wg * 4 + warp][0][0][ln];
      const uint32_t af = sb + (uint32_t)(wg * 4 + warp) * 2048 + ln * 16;
      auto request = [&](int j) {
        if (j < 16) {
          const uint4* p = og + pc_chunk(j, cb) * 128;
          const uint32_t s = af + tab4(PC_ASLOTS, j) * SLOT;
#pragma unroll
          for (int i = 0; i < 4; i++) cp_async16(s + i * 512, p + i * 32);
        }
        cp_commit();
      };
      float acc[64];
      auto tile_addr = [&]() {
        uint32_t l = ln;
        asm volatile("" : "+r"(l));
        return stg + (uint32_t)warp * 2048 + (l & 15) * 128 + (((l >> 4) ^ (l & 7)) << 4);
      };
      auto load_x = [&]() {
        const uint32_t xa = tile_addr();
        mbar_wait(BAR(B_FX));
#pragma unroll
        for (int jj = 0; jj < 8; jj++) {
          uint32_t x0, x1, x2, x3;
          ldsm_x4(x0, x1, x2, x3, (xa ^ (32 * (jj & 3))) + (jj >> 2) * 2 * SLOT);
          acc[8 * jj] = bf_lo(x0); acc[8 * jj + 1] = bf_hi(x0); acc[8 * jj + 2] = bf_lo(x1); acc[8 * jj + 3] = bf_hi(x1);
          acc[8 * jj + 4] = bf_lo(x2); acc[8 * jj + 5] = bf_hi(x2); acc[8 * jj + 6] = bf_lo(x3); acc[8 * jj + 7] = bf_hi(x3);
          if (XH == 2 && (jj & 3) == 3) {
#pragma unroll
            for (int i = 8 * jj - 24; i < 8 * jj + 8; i += 8) asm volatile("" : "+f"(acc[i]));
            __syncwarp();
            request(2 + (jj >> 2));
          }
        }
      };
      {
        const float sc0 = lds_f(sb + OFF_RSTAT + (uint32_t)(wg * 64 + lr) * 8) * L2E, sc1 = lds_f(sb + OFF_RSTAT + (uint32_t)(wg * 64 + lr + 8) * 8) * L2E;
        auto logits = [&](float (&p0)[16], float (&p1)[16], int c) {
          const uint64_t dq = mk_desc(sb + (10 + c) * SLOT + wg * 8192, 16, 1024, 1), dw = mk_desc(sb + OFF_PHIQ + c * 4096, 16, 512, 2);
          mbar_wait(BAR(B_QD + c));
          wg_fence();
          wg_n32<0, 1>(p0, dq, dw, 0);
          wg_n32<0, 1>(p1, dq + 4, dw + 128, 0);
          wg_n32<0, 1>(p0, dq + 2, dw + 64, 1);
          wg_n32<0, 1>(p1, dq + 6, dw + 192, 1);
          wg_commit();
        };
        auto feature = [&](float (&p)[16], uint32_t (&f)[16], float (&sp)[2]) {
          if (warp_fails(feature_fast<false>(p, sc0, sc1, f, sp, []() {}) < FAST_LIMIT)) {
            feature_shifted(p, p, sc0, sc1, f);
            sp[0] = 1.f; sp[1] = 1.f;
          }
        };
        auto apply = [&](float (&u)[20], const uint32_t (&f)[16], int h) {
          const uint64_t d = mk_desc(sb + 12 * SLOT + h * 4096, SLOT - h * 4096 + h * 16, 512, 2);
          wg_fence();
#pragma unroll
          for (int s = 0; s < 4; s++) wg_n40_rs<1>(u, f[4 * s], f[4 * s + 1], f[4 * s + 2], f[4 * s + 3], d + s * 64, s != 0);
          wg_commit();
        };
        float pa[16], pb[16], pc[16], pd[16], u0[20], u1[20], u2[20], n0[2], n1[2], n2[2], n3[2];
        uint32_t f0[16], f1[16], f2[16];
        uint4* const od = og + cb * 256;
        const uint32_t os = af + 10 * SLOT;
        logits(pa, pb, 0);
        wg_wait<0>();
        feature(pa, f0, n0);
        if (PIN & 64) pin_order();
        logits(pc, pd, 1);
        feature(pb, f1, n1);
        if (QORD == 1) {
          uint32_t f3[16];
          wg_wait<0>();
          feature(pc, f2, n2);
          mbar_wait(BAR(B_KVRDY));
          apply(u0, f0, 0);
          apply(u1, f1, 1);
          feature(pd, f3, n3);
          wg_wait<0>();
          apply(u2, f2, 2);
          attn_out(u0, n0, tg, os, od);
          apply(u0, f3, 3);
          attn_out(u1, n1, tg, os + 1024, od + 64);
          if (PIN & 16) pin_order();
          wg_wait<1>();
          if (XH) load_x();
          attn_out(u2, n2, tg, os + SLOT, od + 128);
          wg_wait<0>();
          attn_out(u0, n3, tg, os + SLOT + 1024, od + 192);
        } else if (QORD == 2) {
          wg_wait<0>();
          feature(pc, f2, n2);
          mbar_wait(BAR(B_KVRDY));
          apply(u0, f0, 0);
          apply(u1, f1, 1);
          apply(u2, f2, 2);
          wg_wait<2>();
          attn_out(u0, n0, tg, os, od);
          wg_wait<1>();
          attn_out(u1, n1, tg, os + 1024, od + 64);
          if (PIN & 16) pin_order();
          feature(pd, f1, n3);
          apply(u1, f1, 3);
          wg_wait<1>();
          if (XH) load_x();
          attn_out(u2, n2, tg, os + SLOT, od + 128);
          wg_wait<0>();
          attn_out(u1, n3, tg, os + SLOT + 1024, od + 192);
        } else {
        wg_wait<0>();
        mbar_wait(BAR(B_KVRDY));
        if (PIN & 32) pin_order();
        apply(u0, f0, 0);
        apply(u1, f1, 1);
        feature(pc, f2, n2);
        wg_wait<0>();
        apply(u2, f2, 2);
        attn_out(u0, n0, tg, os, od);
        attn_out(u1, n1, tg, os + 1024, od + 64);
        if (PIN & 16) pin_order();
        feature(pd, f1, n3);
        apply(u1, f1, 3);
        wg_wait<1>();
        if (XH) load_x();
        attn_out(u2, n2, tg, os + SLOT, od + 128);
        wg_wait<0>();
        attn_out(u1, n3, tg, os + SLOT + 1024, od + 192);
        }
      }
      uint32_t A[2][16];
      auto take = [&](uint32_t (&a)[16], int j) {
        const uint32_t s = af + tab4(PC_ASLOTS, j) * SLOT;
        cp_wait<3>();
#pragma unroll
        for (int i = 0; i < 4; i++) {
          const uint4 v = lds_u4(s + i * 512);
          a[4 * i] = v.x; a[4 * i + 1] = v.y; a[4 * i + 2] = v.z; a[4 * i + 3] = v.w;
        }
      };
      auto check = [&](uint32_t (&a)[16], int j) {
        if (PIN & 256) pin_order();
#pragma unroll
        for (int i = 0; i < 4; i++) a[4 * i] ^= tg;
        if (warp_fails((((a[0] | a[4]) | (a[8] | a[12])) & OTAG) == 0)) {
          const uint4* p = og + pc_chunk(j, cb) * 128;
#pragma unroll 1
          for (int it = 0; it < SPIN; it++) {
#pragma unroll
            for (int i = 0; i < 4; i++) {
              const uint4 v = ld_rec16(p + i * 32);
              a[4 * i] = v.x ^ tg; a[4 * i + 1] = v.y; a[4 * i + 2] = v.z; a[4 * i + 3] = v.w;
            }
            if (__all_sync(0xffffffffu, (((a[0] | a[4]) | (a[8] | a[12])) & OTAG) == 0)) break;
          }
        }
      };
      if (!XH) load_x();
#pragma unroll
      for (int i = 0; i < 64; i++) asm volatile("" : "+f"(acc[i]));
      if (XH < 2) {
        __syncwarp();
        request(2);
        request(3);
      }
      take(A[0], 0);
      check(A[0], 0);
      const bool lead = warp == 0 && ln == 0;
      if (lead) mbar_arrive(BAR(B_XDONE));
      if (PCU) {
        unsigned long long ct = 0xDB97531CA864ull ^ (cb < 7 ? (((unsigned long long)(14 - 2 * cb) << 28) | (14 - 2 * cb)) << (4 * cb) >> 8 : 0ull);
        uint32_t bt = (uint32_t)mk_desc(sb + 3 * SLOT, 8192, 1024, 1);
        const uint32_t bl = bt + 4096;
#pragma unroll 1
        for (int m = 0; m < 16; m += 4) {
#pragma unroll
          for (int e = 0; e < 4; e++) {
            const int j = m + e;
            const uint32_t (&a)[16] = A[e & 1];
            mbar_wait(BAR(B_FB + j));
            const uint64_t db = (mk_desc(0, 0, 1024, 1)) | bt;
            wg_fence();
#pragma unroll
            for (int kk = 0; kk < 4; kk++) {
              wg_n128_rs<1>(acc, a[4 * kk], a[4 * kk + 1], a[4 * kk + 2], a[4 * kk + 3], db + kk * 128, 1);
              if (kk == PSPL) {
                wg_commit();
                if (m < 12) {
                  const uint4* p = og + (((uint32_t)ct >> (4 * e)) & 15u) * 128;
#pragma unroll
                  for (int i = 0; i < 4; i++) cp_async16(af + tab4(PC_ASLOTS, e) * SLOT + i * 512, p + i * 32);
                }
                cp_commit();
                wg_wait<1>();
                take(A[(e & 1) ^ 1], (e + 1) & 3);
                if (j > 0 && lead) mbar_arrive(BAR(B_DC + j - 1));
                wg_fence();
              }
            }
            wg_commit();
            asm volatile("{\n.reg .pred p;\nsetp.eq.u32 p, %0, %1;\nadd.u32 %0, %0, 1024;\n@p sub.u32 %0, %0, 5120;\n}\n" : "+r"(bt) : "r"(bl));
            if (e < 3 || m < 12) check(A[(e & 1) ^ 1], j + 1);
          }
          ct >>= 16;
        }
      } else {
#pragma unroll
      for (int j = 0; j < 16; j++) {
        const uint32_t (&a)[16] = A[j & 1];
        mbar_wait(BAR(B_FB + j));
        const uint64_t db = mk_desc(sb + tab4(PC_BSLOTS, j) * SLOT, 8192, 1024, 1);
        wg_fence();
#pragma unroll
        for (int kk = 0; kk < 4; kk++) {
          wg_n128_rs<1>(acc, a[4 * kk], a[4 * kk + 1], a[4 * kk + 2], a[4 * kk + 3], db + kk * 128, 1);
          if (kk == PSPL) {
            wg_commit();
            request(j + 4);
            wg_wait<1>();
            if (j < 15) take(A[(j & 1) ^ 1], j + 1);
            if (j > 0 && lead) mbar_arrive(BAR(B_DC + j - 1));
            wg_fence();
          }
        }
        wg_commit();
        if (j < 15) check(A[(j & 1) ^ 1], j + 1);
      }
      }
      mbar_wait(BAR(B_RESET2));
      wg_wait<0>();
      if (leader) mbar_arrive(BAR(B_DC + 15));
#pragma unroll
      for (int j = 0; j < 16; j++) {
        const float2 w = lds_f2(sb + OFF_WR + (uint32_t)(j * 8 + c2) * 4);
        float a = acc[4 * j], c = acc[4 * j + 1];
        s0 += a + c; q0 = fmaf(a, a, fmaf(c, c, q0)); d0 = fmaf(a, w.x, fmaf(c, w.y, d0));
        a = acc[4 * j + 2]; c = acc[4 * j + 3];
        s1 += a + c; q1 = fmaf(a, a, fmaf(c, c, q1)); d1 = fmaf(a, w.x, fmaf(c, w.y, d1));
      }
#pragma unroll
      for (int m = 1; m <= 2; m <<= 1) {
        s0 += __shfl_xor_sync(0xffffffffu, s0, m); q0 += __shfl_xor_sync(0xffffffffu, q0, m); d0 += __shfl_xor_sync(0xffffffffu, d0, m);
        s1 += __shfl_xor_sync(0xffffffffu, s1, m); q1 += __shfl_xor_sync(0xffffffffu, q1, m); d1 += __shfl_xor_sync(0xffffffffu, d1, m);
      }
      if ((lane & 2) == 0) {
        const bool hi = lane & 1;
        st_rec16(&g_hstat[rb][cb][wg * 64 + lr + (hi ? 8 : 0)], __float_as_uint(hi ? s1 : s0), __float_as_uint(hi ? q1 : q0), __float_as_uint(hi ? d1 : d0), lds_u(sb + OFF_RED + 4));
      }
      const uint32_t ha = tile_addr();
#pragma unroll
      for (int jj = 0; jj < 8; jj++)
        stsm_x4((ha ^ (32 * (jj & 3))) + (jj >> 2) * 2 * SLOT,
                pack_bf16(acc[8 * jj], acc[8 * jj + 1]), pack_bf16(acc[8 * jj + 2], acc[8 * jj + 3]),
                pack_bf16(acc[8 * jj + 4], acc[8 * jj + 5]), pack_bf16(acc[8 * jj + 6], acc[8 * jj + 7]));
    }
    asm volatile("setmaxnreg.dec.sync.aligned.u32 32;");
    {
    MMA_IDS
    const int grow0 = rb * 128 + wg * 64 + lr;
    const unsigned tag = lds_u(sb + OFF_RED + 4);
    uint32_t key;
    {
      const int trow = wg * 64 + lr;
      uint4 r00, r01, r10, r11;
#pragma unroll 1
      for (int it = 0; it < SPIN; it++) {
        r00 = ld_rec16(&g_hstat[rb][c2][trow]); r01 = ld_rec16(&g_hstat[rb][c2 + 1][trow]);
        r10 = ld_rec16(&g_hstat[rb][c2][trow + 8]); r11 = ld_rec16(&g_hstat[rb][c2 + 1][trow + 8]);
        if (__all_sync(0xffffffffu, r00.w == tag && r01.w == tag && r10.w == tag && r11.w == tag)) break;
      }
      s0 = __uint_as_float(r00.x) + __uint_as_float(r01.x); q0 = __uint_as_float(r00.y) + __uint_as_float(r01.y); d0 = __uint_as_float(r00.z) + __uint_as_float(r01.z);
      s1 = __uint_as_float(r10.x) + __uint_as_float(r11.x); q1 = __uint_as_float(r10.y) + __uint_as_float(r11.y); d1 = __uint_as_float(r10.z) + __uint_as_float(r11.z);
#pragma unroll
      for (int m = 1; m <= 2; m <<= 1) {
        s0 += __shfl_xor_sync(0xffffffffu, s0, m); q0 += __shfl_xor_sync(0xffffffffu, q0, m); d0 += __shfl_xor_sync(0xffffffffu, d0, m);
        s1 += __shfl_xor_sync(0xffffffffu, s1, m); q1 += __shfl_xor_sync(0xffffffffu, q1, m); d1 += __shfl_xor_sync(0xffffffffu, d1, m);
      }
      const float sumw = lds_f(sb + OFF_RED);
      const float mean0 = s0 * (1.f / DM), mean1 = s1 * (1.f / DM);
      const float rstd0 = rsq(fmaxf(q0 * (1.f / DM) - mean0 * mean0, 0.f) + 1e-5f);
      const float rstd1 = rsq(fmaxf(q1 * (1.f / DM) - mean1 * mean1, 0.f) + 1e-5f);
      const uint32_t rr = pack_bf16(rstd0 * (d0 - mean0 * sumw), rstd1 * (d1 - mean1 * sumw));
      uint32_t u0 = rr & 0xFFFFu, u1 = rr >> 16;
      u0 = (u0 & 0x8000u) ? (~u0 & 0xFFFFu) : (u0 | 0x8000u);
      u1 = (u1 & 0x8000u) ? (~u1 & 0xFFFFu) : (u1 | 0x8000u);
      const uint32_t k0 = (u0 << 16) | (uint32_t)(0xFFFF - grow0), k1 = (u1 << 16) | (uint32_t)(0xFFFF - (grow0 + 8));
      key = __reduce_max_sync(0xffffffffu, max(k0, k1));
      if (lane == 0) sts_u(sb + OFF_RED + 16 + (uint32_t)(wg * 4 + warp) * 4, key);
      if ((lane & 3) == 0) {
        sts_f2(sb + OFF_RSTAT + trow * 8, rstd0, -mean0 * rstd0);
        sts_f2(sb + OFF_RSTAT + (trow + 8) * 8, rstd1, -mean1 * rstd1);
      }
      bar_sync(1, 256);
      const uint4 ka = lds_u4(sb + OFF_RED + 16), kb = lds_u4(sb + OFF_RED + 32);
      key = max(max(max(ka.x, ka.y), max(ka.z, ka.w)), max(max(kb.x, kb.y), max(kb.z, kb.w)));
    }
    if (tid == 0) st_rec8(&g_key[cb][rb][0], key, tag);
    const int crow = (0xFFFF - (int)(key & 0xFFFFu)) & 127;
    const bool own = (crow >> 4) == wg * 4 + warp;
    uint32_t co0 = 0, co1 = 0;
    if (own) {
      const uint32_t r = (uint32_t)(crow & 63);
      const float2 st = lds_f2(sb + OFF_RSTAT + crow * 8);
      const uint32_t a = stg + r * 128 + ((((uint32_t)lane >> 2) ^ (r & 7)) << 4) + (lane & 3) * 4;
      const uint32_t h0 = lds_u(a), h1 = lds_u(a + 2 * SLOT);
      uint32_t n0, n1;
      co0 = ln_res(h0, st.x, st.y, n0); co1 = ln_res(h1, st.x, st.y, n1);
      st_rec8(&g_candx[rb][cb * 64 + lane], n0, tag);
      st_rec8(&g_candx[rb][cb * 64 + 32 + lane], n1, tag);
      st_rec16(&g_cand[rb][cb * 64 + lane], n0, h0, key, tag);
      st_rec16(&g_cand[rb][cb * 64 + 32 + lane], n1, h1, key, tag);
    }
    __nv_bfloat16* ob = P.out + (size_t)(rb * 128 + wg * 64) * DM + cb * 128;
#pragma unroll 4
    for (int i = 0; i < 8; i++) {
      const uint32_t r = (uint32_t)(warp * 16 + (i & 3) * 4 + (lane >> 3));
      const uint32_t a = stg + (i >> 2) * 2 * SLOT + r * 128 + ((((uint32_t)lane & 7) ^ (r & 7)) << 4);
      const uint4 h = lds_u4(a);
      const float2 st = lds_f2(sb + OFF_RSTAT + (wg * 64 + r) * 8);
      uint32_t n;
      uint4 o;
      o.x = ln_res(h.x, st.x, st.y, n); o.y = ln_res(h.y, st.x, st.y, n); o.z = ln_res(h.z, st.x, st.y, n); o.w = ln_res(h.w, st.x, st.y, n);
      if (!own) sts_u4(a, o.x, o.y, o.z, o.w);
      else if ((int)(wg * 64 + r) != crow) stg16(ob + (size_t)r * DM + (i >> 2) * 64 + (lane & 7) * 8, o);
      if ((i & 3) == 3) {
        fence_async_smem();
        __syncwarp();
        if (i == 7) mbar_wait(BAR(B_ROW));
        if (elect()) {
          if (!own) tma_store_2d(&P.mOut, stg + (i >> 2) * 2 * SLOT + warp * 2048, cb * 128 + (i >> 2) * 64, rb * 128 + wg * 64 + warp * 16);
          asm volatile("cp.async.bulk.commit_group;" ::: "memory");
        }
        __syncwarp();
      }
    }
    if (elect()) {
      asm volatile("cp.async.bulk.wait_group.read 0;" ::: "memory");
    }
    __syncwarp();
    if (own) {
      uint2 v;
#pragma unroll 1
      for (int it = 0; it < SPIN; it++) {
        v = ld_rec8(&g_key[cb][lane & 15][0]);
        if (__all_sync(0xffffffffu, v.y == tag)) break;
      }
      if (__reduce_max_sync(0xffffffffu, v.x) != key) {
        uint32_t* op = reinterpret_cast<uint32_t*>(ob + (size_t)(crow & 63) * DM);
        op[lane] = co0; op[32 + lane] = co1;
      }
    }
    }
  }
#undef BAR
}

typedef CUresult (*EncodeFn)(CUtensorMap*, CUtensorMapDataType, cuuint32_t, void*, const cuuint64_t*, const cuuint64_t*,
                             const cuuint32_t*, const cuuint32_t*, CUtensorMapInterleave, CUtensorMapSwizzle,
                             CUtensorMapL2promotion, CUtensorMapFloatOOBfill);

void make_map(EncodeFn fn, CUtensorMap* m, const void* ptr, uint64_t cols, uint64_t rows, uint32_t bc, uint32_t br, CUtensorMapSwizzle swz) {
  cuuint64_t dims[2] = {cols, rows};
  cuuint64_t strides[1] = {cols * 2};
  cuuint32_t box[2] = {bc, br};
  cuuint32_t es[2] = {1, 1};
  fn(m, CU_TENSOR_MAP_DATA_TYPE_BFLOAT16, 2, const_cast<void*>(ptr), dims, strides, box, es, CU_TENSOR_MAP_INTERLEAVE_NONE, swz,
     CU_TENSOR_MAP_L2_PROMOTION_L2_128B, CU_TENSOR_MAP_FLOAT_OOB_FILL_NONE);
}

}

extern "C" void kernel_launch(void* const* d_in, const int* in_sizes, int n_in, void* d_out, int out_size) {
  static EncodeFn fn = nullptr;
  if (!fn) {
    cudaDriverEntryPointQueryResult q;
    cudaGetDriverEntryPoint("cuTensorMapEncodeTiled", (void**)&fn, cudaEnableDefault, &q);
    cudaFuncSetAttribute(fused_kernel, cudaFuncAttributeMaxDynamicSharedMemorySize, SMEM_BYTES);
  }
  Params P;
  P.x = (const __nv_bfloat16*)d_in[0];
  P.wqkv = (const __nv_bfloat16*)d_in[1];
  const __nv_bfloat16* wphi = (const __nv_bfloat16*)d_in[2];
  P.wo = (const __nv_bfloat16*)d_in[3];
  P.wr = (const __nv_bfloat16*)d_in[5];
  P.wg = (const __nv_bfloat16*)d_in[6];
  P.wu = (const __nv_bfloat16*)d_in[7];
  P.wd = (const __nv_bfloat16*)d_in[8];
  P.out = (__nv_bfloat16*)d_out;
  make_map(fn, &P.mX, P.x, DM, SEQ, 64, 128, CU_TENSOR_MAP_SWIZZLE_128B);
  make_map(fn, &P.mW, P.wqkv, 3 * DM, DM, 64, 64, CU_TENSOR_MAP_SWIZZLE_128B);
  make_map(fn, &P.mWo, P.wo, DM, DM, 64, 64, CU_TENSOR_MAP_SWIZZLE_128B);
  make_map(fn, &P.mPhi, wphi, 32, 1024, 32, 64, CU_TENSOR_MAP_SWIZZLE_64B);
  make_map(fn, &P.mWg, P.wg, FF, DM, 32, 256, CU_TENSOR_MAP_SWIZZLE_64B);
  make_map(fn, &P.mWu, P.wu, FF, DM, 32, 256, CU_TENSOR_MAP_SWIZZLE_64B);
  make_map(fn, &P.mWs, P.wqkv, 3 * DM, DM, 32, 64, CU_TENSOR_MAP_SWIZZLE_NONE);
  make_map(fn, &P.mWd, P.wd, DM, FF, 64, 32, CU_TENSOR_MAP_SWIZZLE_128B);
  make_map(fn, &P.mOut, P.out, DM, SEQ, 64, 16, CU_TENSOR_MAP_SWIZZLE_128B);
  make_map(fn, &P.mWgP, P.wg, FF, DM, 64, 64, CU_TENSOR_MAP_SWIZZLE_128B);
  make_map(fn, &P.mWuP, P.wu, FF, DM, 64, 64, CU_TENSOR_MAP_SWIZZLE_128B);
  fused_kernel<<<NCTA, NTHREADS, SMEM_BYTES, cudaStreamPerThread>>>(P);
}
```

```cpp
#include <cuda_runtime.h>
#include <cuda_bf16.h>
#include <cuda.h>
#include <stdint.h>

namespace {

constexpr int SEQ = 2048, DM = 1024, FF = 3584;
constexpr int NCTA = 128, NTHREADS = 512, NFFN = 112;
constexpr int SPIN = 1 << 17;
constexpr int RSTQ = 3;
constexpr int PSPL = 1;
constexpr int PIN = 145;
constexpr int RCPG = 4;
constexpr int THR = 1;
constexpr int QORD = 2;
constexpr int KH2 = 0;
constexpr int KSH = 0;
constexpr int LPUB = 2;
constexpr int PAD = 0;
constexpr int GATE = 0;
constexpr int FLAGP = 2;
constexpr int XMP = 1;
constexpr int FLAGW = 3;
constexpr int LATE = 0x70;

constexpr uint32_t SLOT = 16384;
constexpr uint32_t OFF_MISC = 13 * SLOT;
constexpr uint32_t OFF_PHIK = OFF_MISC;
constexpr uint32_t OFF_PHIQ = OFF_MISC + 4096;
constexpr uint32_t OFF_ONES = OFF_MISC + 12288;
constexpr uint32_t OFF_RSTAT = OFF_MISC + 13312;
constexpr uint32_t OFF_EYE = OFF_MISC + 14336;
constexpr uint32_t OFF_CS = OFF_MISC + 15360;
constexpr uint32_t OFF_WR = OFF_MISC + 16384;
constexpr uint32_t OFF_BAR = OFF_MISC + 16896;
constexpr uint32_t OFF_RED = OFF_MISC + 18304;
constexpr uint32_t OFF_SEL = OFF_RED + 320;
constexpr uint32_t SMEM_BYTES = OFF_MISC + 19456;

enum {
  B_FKV = 0, B_DKV = 16, B_FQ = 32, B_DQ = 48,
  B_PHI = 64, B_RESET = 65, B_RESET2 = 66, B_ROW = 67, B_FX = 68, B_REL = 72,
  B_FB = 80, B_DC = 96, B_QD = 112, B_STAT = 114,
  B_KVFREE = 120, B_QGO = 121, B_QGO2 = 122, B_CSD = 123, B_XDONE = 124, B_XREAD = 126, B_KVRDY = 127,
  B_FS = 128, B_FW = 144
};
constexpr unsigned long long MISC_COUNTS = 0x0502020203020202ull;

struct Params {
  CUtensorMap mX, mW, mWo, mPhi, mWg, mWu, mWs, mWd, mOut, mWgP, mWuP;
  const __nv_bfloat16 *x, *wqkv, *wo, *wr, *wg, *wu, *wd;
  __nv_bfloat16* out;
};

__device__ unsigned g_epoch;
__device__ __align__(128) uint4 g_rowstat[SEQ];
__device__ __align__(128) uint2 g_colsum[4][3 * DM];
__device__ __align__(128) uint4 g_kvp[32][8][3][128];
__device__ __align__(128) uint4 g_kvr[32][3][128];
__device__ __align__(128) uint4 g_o[16][16][8][4][32];
__device__ __align__(128) uint4 g_oflag[16][8][16];
__device__ __align__(128) uint4 g_hstat[16][8][128];
__device__ __align__(128) uint4 g_cand[16][512];
__device__ __align__(128) uint2 g_candx[16][512];
__device__ __align__(128) uint2 g_key[8][16][4];
__device__ __align__(128) uint2 g_ypart[128][NFFN][8];

__device__ __forceinline__ uint32_t smem_u32(const void* p) { return (uint32_t)__cvta_generic_to_shared(p); }
__device__ __forceinline__ bool elect() {
  uint32_t p;
  asm volatile("{\n.reg .pred P;\nelect.sync _|P, 0xffffffff;\nselp.u32 %0, 1, 0, P;\n}\n" : "=r"(p));
  return p != 0;
}
__device__ __forceinline__ void mbar_init(uint32_t bar, uint32_t cnt) { asm volatile("mbarrier.init.shared::cta.b64 [%0], %1;" :: "r"(bar), "r"(cnt)); }
__device__ __forceinline__ void mbar_expect_tx(uint32_t bar, uint32_t bytes) { asm volatile("mbarrier.arrive.expect_tx.shared::cta.b64 _, [%0], %1;" :: "r"(bar), "r"(bytes) : "memory"); }
__device__ __forceinline__ void mbar_arrive(uint32_t bar) { asm volatile("mbarrier.arrive.shared::cta.b64 _, [%0];" :: "r"(bar) : "memory"); }
template <int PARITY = 0>
__device__ __forceinline__ void mbar_wait(uint32_t bar) {
#pragma unroll 1
  for (int it = 0; it < SPIN; it++) {
    uint32_t ok;
    asm volatile("{\n.reg .pred p;\nmbarrier.try_wait.parity.shared::cta.b64 p, [%1], %2;\nselp.u32 %0, 1, 0, p;\n}\n" : "=r"(ok) : "r"(bar), "n"(PARITY) : "memory");
    if (ok) break;
  }
}
__device__ __forceinline__ void tma_load_2d(uint32_t dst, const CUtensorMap* m, uint32_t bar, int c0, int c1) {
  asm volatile("cp.async.bulk.tensor.2d.shared::cluster.global.mbarrier::complete_tx::bytes [%0], [%1, {%3, %4}], [%2];"
    :: "r"(dst), "l"(m), "r"(bar), "r"(c0), "r"(c1) : "memory");
}
__device__ __forceinline__ void tma_load_2d_ef(uint32_t dst, const CUtensorMap* m, uint32_t bar, int c0, int c1) {
  uint64_t pol;
  asm("createpolicy.fractional.L2::evict_first.b64 %0, 1.0;" : "=l"(pol));
  asm volatile("cp.async.bulk.tensor.2d.shared::cluster.global.mbarrier::complete_tx::bytes.L2::cache_hint [%0], [%1, {%3, %4}], [%2], %5;"
    :: "r"(dst), "l"(m), "r"(bar), "r"(c0), "r"(c1), "l"(pol) : "memory");
}
__device__ __forceinline__ void tma_store_2d(const CUtensorMap* m, uint32_t src, int c0, int c1) {
  asm volatile("cp.async.bulk.tensor.2d.global.shared::cta.bulk_group [%0, {%2, %3}], [%1];"
    :: "l"(m), "r"(src), "r"(c0), "r"(c1) : "memory");
}
__device__ __forceinline__ void cp_async16(uint32_t dst, const void* src) { asm volatile("cp.async.cg.shared.global [%0], [%1], 16;" :: "r"(dst), "l"(src) : "memory"); }
__device__ __forceinline__ void cp_commit() { asm volatile("cp.async.commit_group;" ::: "memory"); }
template <int N> __device__ __forceinline__ void cp_wait() { asm volatile("cp.async.wait_group %0;" :: "n"(N) : "memory"); }
__device__ __forceinline__ void l2_prefetch(const void* src, uint32_t bytes) {
  asm volatile("cp.async.bulk.prefetch.L2.global [%0], %1;" :: "l"(src), "r"(bytes) : "memory");
}
__device__ __forceinline__ void wg_fence() { asm volatile("wgmma.fence.sync.aligned;" ::: "memory"); }
__device__ __forceinline__ void wg_commit() { asm volatile("wgmma.commit_group.sync.aligned;" ::: "memory"); }
template <int N> __device__ __forceinline__ void wg_wait() { asm volatile("wgmma.wait_group.sync.aligned %0;" :: "n"(N) : "memory"); }
__device__ __forceinline__ void fence_async_smem() { asm volatile("fence.proxy.async.shared::cta;" ::: "memory"); }
__device__ __forceinline__ void bar_sync(int id, int n) { asm volatile("bar.sync %0, %1;" :: "r"(id), "r"(n) : "memory"); }
__device__ __forceinline__ void bar_arrive(int id, int n) { asm volatile("bar.arrive %0, %1;" :: "r"(id), "r"(n) : "memory"); }
__device__ __forceinline__ uint64_t mk_desc(uint32_t addr, uint32_t lbo, uint32_t sbo, uint32_t swz) {
  return (uint64_t)((addr & 0x3FFFF) >> 4) | ((uint64_t)((lbo & 0x3FFFF) >> 4) << 16) | ((uint64_t)(sbo >> 4) << 32) | ((uint64_t)swz << 62);
}
__device__ __forceinline__ void stsm_x4(uint32_t addr, uint32_t r0, uint32_t r1, uint32_t r2, uint32_t r3) {
  asm volatile("stmatrix.sync.aligned.m8n8.x4.shared.b16 [%0], {%1, %2, %3, %4};" :: "r"(addr), "r"(r0), "r"(r1), "r"(r2), "r"(r3) : "memory");
}
__device__ __forceinline__ void ldsm_x4(uint32_t& r0, uint32_t& r1, uint32_t& r2, uint32_t& r3, uint32_t addr) {
  asm volatile("ldmatrix.sync.aligned.m8n8.x4.shared.b16 {%0, %1, %2, %3}, [%4];" : "=r"(r0), "=r"(r1), "=r"(r2), "=r"(r3) : "r"(addr) : "memory");
}
__device__ __forceinline__ void ldsm_x4_t(uint32_t (&r)[4], uint32_t addr) {
  asm volatile("ldmatrix.sync.aligned.m8n8.x4.trans.shared.b16 {%0, %1, %2, %3}, [%4];" : "=r"(r[0]), "=r"(r[1]), "=r"(r[2]), "=r"(r[3]) : "r"(addr) : "memory");
}
__device__ __forceinline__ void mma_bf16(float* d, const uint32_t (&a)[4], uint32_t b0, uint32_t b1) {
  asm volatile("mma.sync.aligned.m16n8k16.row.col.f32.bf16.bf16.f32 {%0, %1, %2, %3}, {%4, %5, %6, %7}, {%8, %9}, {%0, %1, %2, %3};"
    : "+f"(d[0]), "+f"(d[1]), "+f"(d[2]), "+f"(d[3]) : "r"(a[0]), "r"(a[1]), "r"(a[2]), "r"(a[3]), "r"(b0), "r"(b1));
}
__device__ __forceinline__ uint32_t zero_after(uint32_t v) { uint32_t r; asm volatile("prmt.b32 %0, %1, 0, 0x4444;" : "=r"(r) : "r"(v)); return r; }
__device__ __forceinline__ int fresh_tid() { int v; asm volatile("mov.u32 %0, %%tid.x;" : "=r"(v)); return v; }
template <int ID> __device__ __forceinline__ void pin_at() {
  asm volatile("{\n.reg .pred p;\nsetp.eq.u32 p, %0, %1;\nPIN:\n@p nanosleep.u32 0;\n@p bra.uni PIN;\n}\n" :: "r"(blockIdx.x), "n"(4096 + ID) : "memory");
}
#define pin_order() pin_at<__LINE__>()
__device__ __forceinline__ uint32_t pack_bf16(float lo, float hi) {
  uint32_t r; asm("cvt.rn.bf16x2.f32 %0, %1, %2;" : "=r"(r) : "f"(hi), "f"(lo)); return r;
}
__device__ __forceinline__ uint32_t pack_pin(float lo, float hi) {
  uint32_t r; asm volatile("cvt.rn.bf16x2.f32 %0, %1, %2;" : "=r"(r) : "f"(hi), "f"(lo)); return r;
}
__device__ __forceinline__ uint32_t hadd2(uint32_t a, uint32_t b) { uint32_t r; asm("add.rn.bf16x2 %0, %1, %2;" : "=r"(r) : "r"(a), "r"(b)); return r; }
template <int H> __device__ __forceinline__ uint32_t hmul2(uint32_t a, uint32_t b) {
  uint32_t r;
  if (H) asm("{\n.reg .b16 l, h;\n.reg .b32 t;\nmov.b32 {l, h}, %2;\nmov.b32 t, {h, h};\nmul.rn.bf16x2 %0, %1, t;\n}\n" : "=r"(r) : "r"(a), "r"(b));
  else asm("{\n.reg .b16 l, h;\n.reg .b32 t;\nmov.b32 {l, h}, %2;\nmov.b32 t, {l, l};\nmul.rn.bf16x2 %0, %1, t;\n}\n" : "=r"(r) : "r"(a), "r"(b));
  return r;
}
template <int H> __device__ __forceinline__ uint32_t hfma2(uint32_t a, uint32_t b, uint32_t c) {
  uint32_t r;
  if (H) asm("{\n.reg .b16 l, h;\n.reg .b32 t;\nmov.b32 {l, h}, %2;\nmov.b32 t, {h, h};\nfma.rn.bf16x2 %0, %1, t, %3;\n}\n" : "=r"(r) : "r"(a), "r"(b), "r"(c));
  else asm("{\n.reg .b16 l, h;\n.reg .b32 t;\nmov.b32 {l, h}, %2;\nmov.b32 t, {l, l};\nfma.rn.bf16x2 %0, %1, t, %3;\n}\n" : "=r"(r) : "r"(a), "r"(b), "r"(c));
  return r;
}
__device__ __forceinline__ float bf_lo(uint32_t v) { return __uint_as_float(v << 16); }
__device__ __forceinline__ float bf_hi(uint32_t v) { return __uint_as_float(v & 0xFFFF0000u); }
__device__ __forceinline__ float bf_round(float v) { return bf_lo(pack_bf16(v, 0.f)); }
__device__ __forceinline__ float ex2(float v) { float r; asm("ex2.approx.ftz.f32 %0, %1;" : "=f"(r) : "f"(v)); return r; }
__device__ __forceinline__ float rsq(float v) { float r; asm("rsqrt.approx.ftz.f32 %0, %1;" : "=f"(r) : "f"(v)); return r; }
__device__ __forceinline__ float rcp(float v) { float r; asm("rcp.approx.ftz.f32 %0, %1;" : "=f"(r) : "f"(v)); return r; }
__device__ __forceinline__ void st_rec16(uint4* p, uint32_t a, uint32_t b, uint32_t c, uint32_t d) {
  asm volatile("{\n.reg .b128 r;\n.reg .b64 lo, hi;\nmov.b64 lo, {%1, %2};\nmov.b64 hi, {%3, %4};\nmov.b128 r, {lo, hi};\nst.relaxed.gpu.global.b128 [%0], r;\n}\n"
    :: "l"(p), "r"(a), "r"(b), "r"(c), "r"(d) : "memory");
}
__device__ __forceinline__ uint4 ld_rec16(const uint4* p) {
  uint4 v;
  asm volatile("{\n.reg .b128 r;\n.reg .b64 lo, hi;\nld.relaxed.gpu.global.b128 r, [%4];\nmov.b128 {lo, hi}, r;\nmov.b64 {%0, %1}, lo;\nmov.b64 {%2, %3}, hi;\n}\n"
    : "=r"(v.x), "=r"(v.y), "=r"(v.z), "=r"(v.w) : "l"(p) : "memory");
  return v;
}
__device__ __forceinline__ void ld_rec16_stale(uint4& v, const uint4* p, uint32_t tag) {
  asm volatile("{\n.reg .pred p;\n.reg .b128 r;\n.reg .b64 lo, hi;\nmov.b64 lo, {%0, %1};\nmov.b64 hi, {%2, %3};\nmov.b128 r, {lo, hi};\nsetp.ne.u32 p, %3, %5;\n"
    "@p ld.relaxed.gpu.global.b128 r, [%4];\nmov.b128 {lo, hi}, r;\nmov.b64 {%0, %1}, lo;\nmov.b64 {%2, %3}, hi;\n}\n"
    : "+r"(v.x), "+r"(v.y), "+r"(v.z), "+r"(v.w) : "l"(p), "r"(tag) : "memory");
}
__device__ __forceinline__ void st_rec8(uint2* p, uint32_t a, uint32_t b) {
  asm volatile("{\n.reg .b64 r;\nmov.b64 r, {%1, %2};\nst.relaxed.gpu.global.b64 [%0], r;\n}\n" :: "l"(p), "r"(a), "r"(b) : "memory");
}
__device__ __forceinline__ uint2 ld_rec8(const uint2* p) {
  uint2 v;
  asm volatile("{\n.reg .b64 r;\nld.relaxed.gpu.global.b64 r, [%2];\nmov.b64 {%0, %1}, r;\n}\n" : "=r"(v.x), "=r"(v.y) : "l"(p) : "memory");
  return v;
}
__device__ __forceinline__ unsigned ld_relaxed(const unsigned* p) { unsigned v; asm volatile("ld.relaxed.gpu.global.u32 %0, [%1];" : "=r"(v) : "l"(p) : "memory"); return v; }
__device__ __forceinline__ uint4 ldg_nc16(const void* p) {
  uint4 v; asm volatile("ld.global.nc.L1::no_allocate.v4.u32 {%0, %1, %2, %3}, [%4];" : "=r"(v.x), "=r"(v.y), "=r"(v.z), "=r"(v.w) : "l"(p)); return v;
}
__device__ __forceinline__ void stg16(void* p, uint4 v) { asm volatile("st.global.v4.u32 [%0], {%1, %2, %3, %4};" :: "l"(p), "r"(v.x), "r"(v.y), "r"(v.z), "r"(v.w) : "memory"); }
__device__ __forceinline__ float2 lds_f2(uint32_t a) { float2 v; asm volatile("ld.shared.v2.f32 {%0, %1}, [%2];" : "=f"(v.x), "=f"(v.y) : "r"(a)); return v; }
__device__ __forceinline__ float lds_f(uint32_t a) { float v; asm volatile("ld.shared.f32 %0, [%1];" : "=f"(v) : "r"(a)); return v; }
__device__ __forceinline__ uint32_t lds_u(uint32_t a) { uint32_t v; asm volatile("ld.shared.u32 %0, [%1];" : "=r"(v) : "r"(a)); return v; }
__device__ __forceinline__ uint4 lds_u4(uint32_t a) { uint4 v; asm volatile("ld.shared.v4.u32 {%0, %1, %2, %3}, [%4];" : "=r"(v.x), "=r"(v.y), "=r"(v.z), "=r"(v.w) : "r"(a)); return v; }
__device__ __forceinline__ void sts_f(uint32_t a, float v) { asm volatile("st.shared.f32 [%0], %1;" :: "r"(a), "f"(v) : "memory"); }
__device__ __forceinline__ void sts_f2(uint32_t a, float x, float y) { asm volatile("st.shared.v2.f32 [%0], {%1, %2};" :: "r"(a), "f"(x), "f"(y) : "memory"); }
__device__ __forceinline__ void sts_u2(uint32_t a, uint32_t x, uint32_t y) { asm volatile("st.shared.v2.u32 [%0], {%1, %2};" :: "r"(a), "r"(x), "r"(y) : "memory"); }
__device__ __forceinline__ void sts_u4(uint32_t a, uint32_t x, uint32_t y, uint32_t z, uint32_t w) { asm volatile("st.shared.v4.u32 [%0], {%1, %2, %3, %4};" :: "r"(a), "r"(x), "r"(y), "r"(z), "r"(w) : "memory"); }
__device__ __forceinline__ void sts_h(uint32_t a, uint32_t v) { asm volatile("st.shared.u16 [%0], %1;" :: "r"(a), "h"((uint16_t)v) : "memory"); }
__device__ __forceinline__ void sts_u(uint32_t a, uint32_t v) { asm volatile("st.shared.u32 [%0], %1;" :: "r"(a), "r"(v) : "memory"); }

template <int TA, int TB>
__device__ __forceinline__ void wg_n128(float (&d)[64], uint64_t da, uint64_t db, int sd) {
  asm volatile("{\n.reg .pred p;\nsetp.ne.b32 p, %66, 0;\n"
    "wgmma.mma_async.sync.aligned.m64n128k16.f32.bf16.bf16 {%0, %1, %2, %3, %4, %5, %6, %7, %8, %9, %10, %11, %12, %13, %14, %15, %16, %17, %18, %19, %20, %21, %22, %23, %24, %25, %26, %27, %28, %29, %30, %31, %32, %33, %34, %35, %36, %37, %38, %39, %40, %41, %42, %43, %44, %45, %46, %47, %48, %49, %50, %51, %52, %53, %54, %55, %56, %57, %58, %59, %60, %61, %62, %63}, %64, %65, p, 1, 1, %67, %68;\n}\n"
    : "+f"(d[0]), "+f"(d[1]), "+f"(d[2]), "+f"(d[3]), "+f"(d[4]), "+f"(d[5]), "+f"(d[6]), "+f"(d[7]), "+f"(d[8]), "+f"(d[9]), "+f"(d[10]), "+f"(d[11]), "+f"(d[12]), "+f"(d[13]), "+f"(d[14]), "+f"(d[15]), "+f"(d[16]), "+f"(d[17]), "+f"(d[18]), "+f"(d[19]), "+f"(d[20]), "+f"(d[21]), "+f"(d[22]), "+f"(d[23]), "+f"(d[24]), "+f"(d[25]), "+f"(d[26]), "+f"(d[27]), "+f"(d[28]), "+f"(d[29]), "+f"(d[30]), "+f"(d[31]), "+f"(d[32]), "+f"(d[33]), "+f"(d[34]), "+f"(d[35]), "+f"(d[36]), "+f"(d[37]), "+f"(d[38]), "+f"(d[39]), "+f"(d[40]), "+f"(d[41]), "+f"(d[42]), "+f"(d[43]), "+f"(d[44]), "+f"(d[45]), "+f"(d[46]), "+f"(d[47]), "+f"(d[48]), "+f"(d[49]), "+f"(d[50]), "+f"(d[51]), "+f"(d[52]), "+f"(d[53]), "+f"(d[54]), "+f"(d[55]), "+f"(d[56]), "+f"(d[57]), "+f"(d[58]), "+f"(d[59]), "+f"(d[60]), "+f"(d[61]), "+f"(d[62]), "+f"(d[63])
    : "l"(da), "l"(db), "r"(sd), "n"(TA), "n"(TB));
}

template <int TA, int TB, int O>
__device__ __forceinline__ void wg_n64(float (&d)[64], uint64_t da, uint64_t db, int sd) {
  asm volatile("{\n.reg .pred p;\nsetp.ne.b32 p, %34, 0;\n"
    "wgmma.mma_async.sync.aligned.m64n64k16.f32.bf16.bf16 {%0, %1, %2, %3, %4, %5, %6, %7, %8, %9, %10, %11, %12, %13, %14, %15, %16, %17, %18, %19, %20, %21, %22, %23, %24, %25, %26, %27, %28, %29, %30, %31}, %32, %33, p, 1, 1, %35, %36;\n}\n"
    : "+f"(d[O + 0]), "+f"(d[O + 1]), "+f"(d[O + 2]), "+f"(d[O + 3]), "+f"(d[O + 4]), "+f"(d[O + 5]), "+f"(d[O + 6]), "+f"(d[O + 7]), "+f"(d[O + 8]), "+f"(d[O + 9]), "+f"(d[O + 10]), "+f"(d[O + 11]), "+f"(d[O + 12]), "+f"(d[O + 13]), "+f"(d[O + 14]), "+f"(d[O + 15]), "+f"(d[O + 16]), "+f"(d[O + 17]), "+f"(d[O + 18]), "+f"(d[O + 19]), "+f"(d[O + 20]), "+f"(d[O + 21]), "+f"(d[O + 22]), "+f"(d[O + 23]), "+f"(d[O + 24]), "+f"(d[O + 25]), "+f"(d[O + 26]), "+f"(d[O + 27]), "+f"(d[O + 28]), "+f"(d[O + 29]), "+f"(d[O + 30]), "+f"(d[O + 31])
    : "l"(da), "l"(db), "r"(sd), "n"(TA), "n"(TB));
}

template <int TA, int TB>
__device__ __forceinline__ void wg_n40(float (&d)[20], uint64_t da, uint64_t db, int sd) {
  asm volatile("{\n.reg .pred p;\nsetp.ne.b32 p, %22, 0;\n"
    "wgmma.mma_async.sync.aligned.m64n40k16.f32.bf16.bf16 {%0, %1, %2, %3, %4, %5, %6, %7, %8, %9, %10, %11, %12, %13, %14, %15, %16, %17, %18, %19}, %20, %21, p, 1, 1, %23, %24;\n}\n"
    : "+f"(d[0]), "+f"(d[1]), "+f"(d[2]), "+f"(d[3]), "+f"(d[4]), "+f"(d[5]), "+f"(d[6]), "+f"(d[7]), "+f"(d[8]), "+f"(d[9]), "+f"(d[10]), "+f"(d[11]), "+f"(d[12]), "+f"(d[13]), "+f"(d[14]), "+f"(d[15]), "+f"(d[16]), "+f"(d[17]), "+f"(d[18]), "+f"(d[19])
    : "l"(da), "l"(db), "r"(sd), "n"(TA), "n"(TB));
}

template <int TA, int TB>
__device__ __forceinline__ void wg_n32(float (&d)[16], uint64_t da, uint64_t db, int sd) {
  asm volatile("{\n.reg .pred p;\nsetp.ne.b32 p, %18, 0;\n"
    "wgmma.mma_async.sync.aligned.m64n32k16.f32.bf16.bf16 {%0, %1, %2, %3, %4, %5, %6, %7, %8, %9, %10, %11, %12, %13, %14, %15}, %16, %17, p, 1, 1, %19, %20;\n}\n"
    : "+f"(d[0]), "+f"(d[1]), "+f"(d[2]), "+f"(d[3]), "+f"(d[4]), "+f"(d[5]), "+f"(d[6]), "+f"(d[7]), "+f"(d[8]), "+f"(d[9]), "+f"(d[10]), "+f"(d[11]), "+f"(d[12]), "+f"(d[13]), "+f"(d[14]), "+f"(d[15])
    : "l"(da), "l"(db), "r"(sd), "n"(TA), "n"(TB));
}

template <int TB>
__device__ __forceinline__ void wg_n40_rs(float (&d)[20], uint32_t a0, uint32_t a1, uint32_t a2, uint32_t a3, uint64_t db, int sd) {
  asm volatile("{\n.reg .pred p;\nsetp.ne.b32 p, %25, 0;\n"
    "wgmma.mma_async.sync.aligned.m64n40k16.f32.bf16.bf16 {%0, %1, %2, %3, %4, %5, %6, %7, %8, %9, %10, %11, %12, %13, %14, %15, %16, %17, %18, %19}, {%20, %21, %22, %23}, %24, p, 1, 1, %26;\n}\n"
    : "+f"(d[0]), "+f"(d[1]), "+f"(d[2]), "+f"(d[3]), "+f"(d[4]), "+f"(d[5]), "+f"(d[6]), "+f"(d[7]), "+f"(d[8]), "+f"(d[9]), "+f"(d[10]), "+f"(d[11]), "+f"(d[12]), "+f"(d[13]), "+f"(d[14]), "+f"(d[15]), "+f"(d[16]), "+f"(d[17]), "+f"(d[18]), "+f"(d[19])
    : "r"(a0), "r"(a1), "r"(a2), "r"(a3), "l"(db), "r"(sd), "n"(TB));
}

template <int TB>
__device__ __forceinline__ void wg_n32_rs(float (&d)[16], uint32_t a0, uint32_t a1, uint32_t a2, uint32_t a3, uint64_t db, int sd) {
  asm volatile("{\n.reg .pred p;\nsetp.ne.b32 p, %21, 0;\n"
    "wgmma.mma_async.sync.aligned.m64n32k16.f32.bf16.bf16 {%0, %1, %2, %3, %4, %5, %6, %7, %8, %9, %10, %11, %12, %13, %14, %15}, {%16, %17, %18, %19}, %20, p, 1, 1, %22;\n}\n"
    : "+f"(d[0]), "+f"(d[1]), "+f"(d[2]), "+f"(d[3]), "+f"(d[4]), "+f"(d[5]), "+f"(d[6]), "+f"(d[7]), "+f"(d[8]), "+f"(d[9]), "+f"(d[10]), "+f"(d[11]), "+f"(d[12]), "+f"(d[13]), "+f"(d[14]), "+f"(d[15])
    : "r"(a0), "r"(a1), "r"(a2), "r"(a3), "l"(db), "r"(sd), "n"(TB));
}

template <int TB>
__device__ __forceinline__ void wg_n8_rs(float (&d)[4], uint32_t a0, uint32_t a1, uint32_t a2, uint32_t a3, uint64_t db, int sd) {
  asm volatile("{\n.reg .pred p;\nsetp.ne.b32 p, %9, 0;\n"
    "wgmma.mma_async.sync.aligned.m64n8k16.f32.bf16.bf16 {%0, %1, %2, %3}, {%4, %5, %6, %7}, %8, p, 1, 1, %10;\n}\n"
    : "+f"(d[0]), "+f"(d[1]), "+f"(d[2]), "+f"(d[3])
    : "r"(a0), "r"(a1), "r"(a2), "r"(a3), "l"(db), "r"(sd), "n"(TB));
}

template <int TB>
__device__ __forceinline__ void wg_n128_rs(float (&d)[64], uint32_t a0, uint32_t a1, uint32_t a2, uint32_t a3, uint64_t db, int sd) {
  asm volatile("{\n.reg .pred p;\nsetp.ne.b32 p, %69, 0;\n"
    "wgmma.mma_async.sync.aligned.m64n128k16.f32.bf16.bf16 {%0, %1, %2, %3, %4, %5, %6, %7, %8, %9, %10, %11, %12, %13, %14, %15, %16, %17, %18, %19, %20, %21, %22, %23, %24, %25, %26, %27, %28, %29, %30, %31, %32, %33, %34, %35, %36, %37, %38, %39, %40, %41, %42, %43, %44, %45, %46, %47, %48, %49, %50, %51, %52, %53, %54, %55, %56, %57, %58, %59, %60, %61, %62, %63}, {%64, %65, %66, %67}, %68, p, 1, 1, %70;\n}\n"
    : "+f"(d[0]), "+f"(d[1]), "+f"(d[2]), "+f"(d[3]), "+f"(d[4]), "+f"(d[5]), "+f"(d[6]), "+f"(d[7]), "+f"(d[8]), "+f"(d[9]), "+f"(d[10]), "+f"(d[11]), "+f"(d[12]), "+f"(d[13]), "+f"(d[14]), "+f"(d[15]), "+f"(d[16]), "+f"(d[17]), "+f"(d[18]), "+f"(d[19]), "+f"(d[20]), "+f"(d[21]), "+f"(d[22]), "+f"(d[23]), "+f"(d[24]), "+f"(d[25]), "+f"(d[26]), "+f"(d[27]), "+f"(d[28]), "+f"(d[29]), "+f"(d[30]), "+f"(d[31]), "+f"(d[32]), "+f"(d[33]), "+f"(d[34]), "+f"(d[35]), "+f"(d[36]), "+f"(d[37]), "+f"(d[38]), "+f"(d[39]), "+f"(d[40]), "+f"(d[41]), "+f"(d[42]), "+f"(d[43]), "+f"(d[44]), "+f"(d[45]), "+f"(d[46]), "+f"(d[47]), "+f"(d[48]), "+f"(d[49]), "+f"(d[50]), "+f"(d[51]), "+f"(d[52]), "+f"(d[53]), "+f"(d[54]), "+f"(d[55]), "+f"(d[56]), "+f"(d[57]), "+f"(d[58]), "+f"(d[59]), "+f"(d[60]), "+f"(d[61]), "+f"(d[62]), "+f"(d[63])
    : "r"(a0), "r"(a1), "r"(a2), "r"(a3), "l"(db), "r"(sd), "n"(TB));
}


template <int N>
__device__ __forceinline__ void feature_shifted(const float (&p)[16], const float (&p2)[16], float sc0, float sc1, uint32_t (&o)[N]) {
  __align__(16) float t[N];
  __align__(16) uint32_t w[N];
#pragma unroll
  for (int i = 0; i < N; i++) t[i] = i < 16 ? p[i] : p2[i & 15];
#pragma unroll 1
  for (int it = 0; it < N / 4; it++) {
    const float* x = t + (it >> 2) * 16 + (it & 1) * 2;
    const int h = (it >> 1) & 1;
    const float sg = h ? -1.f : 1.f, sc = (it & 1) ? sc1 : sc0;
    float mx = sg * x[0], s = 0.f;
#pragma unroll 1
    for (int j = 0; j < 16; j += 4) mx = fmaxf(mx, fmaxf(sg * x[j], sg * x[j + 1]));
    mx = fmaxf(mx, __shfl_xor_sync(0xffffffffu, mx, 1));
    mx = fmaxf(mx, __shfl_xor_sync(0xffffffffu, mx, 2));
#pragma unroll 1
    for (int j = 0; j < 32; j += 4) {
      const float a = ex2((sg * x[(j & 15) + h] - mx) * sc), c = ex2((sg * x[(j & 15) + 1 - h] - mx) * sc);
      if (j < 16) s += a + c;
      else w[(it >> 1) * 8 + (j >> 1) - 8 + (it & 1)] = pack_bf16(a * s, c * s);
      if (j == 12) {
        s += __shfl_xor_sync(0xffffffffu, s, 1);
        s += __shfl_xor_sync(0xffffffffu, s, 2);
        s = rcp(s);
      }
    }
  }
#pragma unroll
  for (int i = 0; i < N; i++) o[i] = w[i];
}
constexpr float FAST_LIMIT = RCPG == 2 ? 0x1p60f : RCPG == 4 ? 0x1p30f : 0x1p15f;
__device__ __forceinline__ void feature_exp(const float* p, float sc0, float sc1, uint32_t* o, float (&d)[4], uint64_t sel) {
  float e[16], r[8];
#pragma unroll
  for (int i = 0; i < 16; i++) e[i] = ex2(p[i] * ((i & 2) ? sc1 : sc0));
#pragma unroll
  for (int i = 0; i < 8; i++) r[i] = e[2 * i] * e[2 * i + 1];
#pragma unroll
  for (int i = 0; i < 8; i++) o[i] = pack_bf16(e[2 * i], e[2 * i + 1]);
  uint32_t a[4];
#pragma unroll
  for (int i = 0; i < 2; i++) {
    if (RCPG == 2) {
      o[8 + i] = pack_bf16(rcp(r[i]), rcp(r[2 + i]));
      o[10 + i] = pack_bf16(rcp(r[4 + i]), rcp(r[6 + i]));
    } else {
      float u = r[i] * r[2 + i], w = r[4 + i] * r[6 + i];
      if (RCPG == 4) { u = rcp(u); w = rcp(w); }
      else { const float z = rcp(u * w), y = z * u; u = z * w; w = y; }
      o[8 + i] = pack_bf16(u * r[2 + i], u * r[i]);
      o[10 + i] = pack_bf16(w * r[6 + i], w * r[4 + i]);
    }
    a[i] = hadd2(hadd2(o[i], o[2 + i]), hadd2(o[4 + i], o[6 + i]));
    a[2 + i] = hfma2<1>(o[6 + i], o[10 + i], hfma2<0>(o[4 + i], o[10 + i], hfma2<1>(o[2 + i], o[8 + i], hmul2<0>(o[i], o[8 + i]))));
  }
  wg_fence();
  wg_n8_rs<0>(d, a[0], a[1], a[2], a[3], sel, 0);
  wg_commit();
}
template <bool FULL>
__device__ __forceinline__ float feature_norm(uint32_t* o, const float (&d)[4]) {
  uint32_t c[4];
  if (FULL) {
#pragma unroll
    for (int i = 0; i < 2; i++) {
      const float z = rcp(d[2 * i] * d[2 * i + 1]);
      const uint32_t n = pack_bf16(z * d[2 * i + 1], z * d[2 * i]);
      c[i] = hmul2<1>(o[8 + i], n); c[2 + i] = hmul2<1>(o[10 + i], n);
#pragma unroll
      for (int j = i; j < 8; j += 2) {
        o[8 + j] = (j & 2) ? hmul2<1>(o[j], c[(j >> 2) * 2 + i]) : hmul2<0>(o[j], c[(j >> 2) * 2 + i]);
        o[j] = hmul2<0>(o[j], n);
      }
    }
  } else {
    const uint32_t n = pack_bf16(d[0] * rcp(d[1]), d[2] * rcp(d[3]));
    c[0] = hmul2<0>(o[8], n); c[1] = hmul2<1>(o[9], n); c[2] = hmul2<0>(o[10], n); c[3] = hmul2<1>(o[11], n);
#pragma unroll
    for (int j = 0; j < 8; j++) o[8 + j] = (j & 2) ? hmul2<1>(o[j], c[(j >> 2) * 2 + (j & 1)]) : hmul2<0>(o[j], c[(j >> 2) * 2 + (j & 1)]);
  }
  return (d[0] + d[1]) + (d[2] + d[3]);
}
__device__ __forceinline__ float feature_norm32(const float (&e)[16], const float (&r)[8], const float (&d)[4], uint32_t* o) {
#pragma unroll
  for (int i = 0; i < 2; i++) {
    const float z = rcp(d[2 * i] * d[2 * i + 1]), np = z * d[2 * i + 1], nm = z * d[2 * i];
    if (KH2) {
      const float q = nm * d[2 * i];
      const uint32_t c0 = pack_bf16(r[i] * q, r[2 + i] * q), c1 = pack_bf16(r[4 + i] * q, r[6 + i] * q);
#pragma unroll
      for (int j = i; j < 8; j += 2) {
        o[j] = pack_bf16(e[2 * j] * np, e[2 * j + 1] * np);
        o[8 + j] = (j & 2) ? hmul2<1>(o[j], (j & 4) ? c1 : c0) : hmul2<0>(o[j], (j & 4) ? c1 : c0);
      }
    } else {
#pragma unroll
      for (int j = i; j < 8; j += 2) {
        const float c = r[j] * nm;
        o[j] = pack_bf16(e[2 * j] * np, e[2 * j + 1] * np);
        o[8 + j] = pack_bf16(e[2 * j] * c, e[2 * j + 1] * c);
      }
    }
  }
  return (d[0] + d[1]) + (d[2] + d[3]);
}
template <class H>
__device__ __forceinline__ float feature_fast(const float* p, float sc0, float sc1, uint32_t* o, H hook) {
  float e[16], r[8], sp[2] = {0.f, 0.f}, sm[2] = {0.f, 0.f};
#pragma unroll
  for (int i = 0; i < 16; i++) e[i] = ex2(p[i] * ((i & 2) ? sc1 : sc0));
#pragma unroll
  for (int i = 0; i < 8; i++) r[i] = e[2 * i] * e[2 * i + 1];
#pragma unroll
  for (int i = 0; i < 2; i++) {
    float u = r[i] * r[2 + i], w = r[4 + i] * r[6 + i];
    if (RCPG == 4) { u = rcp(u); w = rcp(w); }
    else { const float z = rcp(u * w), y = z * u; u = z * w; w = y; }
    const float c = u * r[i], d = w * r[4 + i];
    r[i] = u * r[2 + i]; r[2 + i] = c; r[4 + i] = w * r[6 + i]; r[6 + i] = d;
  }
#pragma unroll
  for (int i = 0; i < 8; i++) {
    const float t = e[2 * i] + e[2 * i + 1];
    sp[i & 1] += t; sm[i & 1] = fmaf(t, r[i], sm[i & 1]);
  }
  const float tot = (sp[0] + sp[1]) + (sm[0] + sm[1]);
  if (KSH == 1) {
#pragma unroll
    for (int i = 0; i < 2; i++) {
      uint32_t v = pack_bf16(sp[i], sm[i]);
      v = hadd2(v, __shfl_xor_sync(0xffffffffu, v, 1));
      const uint32_t w = __shfl_xor_sync(0xffffffffu, v, 2);
      sp[i] = bf_lo(v) + bf_lo(w); sm[i] = bf_hi(v) + bf_hi(w);
    }
  } else {
#pragma unroll
    for (int m = 1; m <= 2; m <<= 1)
#pragma unroll
      for (int i = 0; i < 2; i++) { sp[i] += __shfl_xor_sync(0xffffffffu, sp[i], m); sm[i] += __shfl_xor_sync(0xffffffffu, sm[i], m); }
  }
  hook();
  const float d[4] = {sp[0], sm[0], sp[1], sm[1]};
  feature_norm32(e, r, d, o);
  return tot;
}
__device__ __forceinline__ bool warp_fails(bool ok) { return __builtin_expect(!__all_sync(0xffffffffu, ok), 0); }
constexpr uint32_t OTAG = 0x00010001u;
__device__ __forceinline__ void attn_out(const float (&u)[20], uint32_t tg, uint32_t* r, uint4* dst, bool pub) {
  const float d0 = rcp(fmaf(u[17], 0.5e-6f, u[16])), d1 = rcp(fmaf(u[19], 0.5e-6f, u[18]));
#pragma unroll
  for (int j = 0; j < 8; j++) r[j] = pack_bf16(u[2 * j] * ((j & 1) ? d1 : d0), u[2 * j + 1] * ((j & 1) ? d1 : d0));
  r[0] = (r[0] & ~OTAG) | tg; r[4] = (r[4] & ~OTAG) | tg;
  if (pub) {
    st_rec16(dst, r[0], r[1], r[2], r[3]);
    st_rec16(dst + 32, r[4], r[5], r[6], r[7]);
  }
}

constexpr float L2E = 1.4426950408889634f;

__device__ __forceinline__ int pc_chunk(int j, int cb) {
  const int c = j > 8, e = j - 2 - 7 * c;
  return j < 2 ? 2 * cb + j : 2 * (e == cb ? 7 : e) + c;
}
constexpr unsigned long long Q_ASLOTS = 0x9763097630976309ull, Q_BSLOTS = 0x1854218542185421ull;
constexpr unsigned long long Q_CHUNKS = 0xBA9876543210EDCFull;
constexpr unsigned long long PC_ASLOTS = 0xBA20BA20BA20BA20ull, PC_BSLOTS = 0x3765437654376543ull;
constexpr unsigned long long FFN_SLOTS = 0xBA9854C11987ull;
constexpr unsigned long long FFN_ORDER = 0xBA7654983210ull;
constexpr unsigned long long FFN_WAIT0 = 0x7C4B4A493F3F3E3Eull, FFN_WAIT1 = 0x6E6D6C6Bull;
constexpr unsigned long long FFN_PACE0 = 0x6A69989392627F44ull, FFN_PACE1 = 0x97969594ull;
constexpr unsigned long long WO_WAIT0 = 0x626160483D3D3C3Cull, WO_WAIT1 = 0x6A69686766656463ull;
constexpr unsigned long long WO_PACE0 = 0x527F502Full, WO_PACE1 = 0x0ull;
constexpr int X_PACE = 81;
__device__ __forceinline__ uint32_t tab4(unsigned long long t, int i) { return (uint32_t)(t >> (4 * i)) & 15u; }
__device__ __forceinline__ uint32_t tab8(unsigned long long lo, unsigned long long hi, int i) { return (uint32_t)((i < 8 ? lo : hi) >> (8 * (i & 7))) & 255u; }

__device__ __forceinline__ float sum8(uint4 v) {
  return ((bf_lo(v.x) + bf_hi(v.x)) + (bf_lo(v.y) + bf_hi(v.y))) + ((bf_lo(v.z) + bf_hi(v.z)) + (bf_lo(v.w) + bf_hi(v.w)));
}
__device__ __forceinline__ void acc2(uint32_t v, float sh, float& s, float& q) {
  const float a = bf_lo(v) - sh, c = bf_hi(v) - sh;
  s += a + c; q = fmaf(a, a, fmaf(c, c, q));
}
__device__ __forceinline__ float warp_sum(float s) {
#pragma unroll
  for (int m = 16; m >= 1; m >>= 1) s += __shfl_xor_sync(0xffffffffu, s, m);
  return s;
}
__device__ __forceinline__ uint32_t ln_res(uint32_t h, float a, float c, uint32_t& n) {
  const float l = bf_lo(h), u = bf_hi(h);
  n = pack_bf16(fmaf(l, a, c), fmaf(u, a, c));
  return pack_bf16(l + bf_lo(n), u + bf_hi(n));
}

__device__ __forceinline__ uint64_t ext_a(uint32_t sb, uint32_t row) { return mk_desc(sb + 12 * SLOT + 4096 + row * 16, 4096 - row * 16, 128, 0); }
__device__ __forceinline__ uint64_t ext_b(uint32_t sb, uint32_t part) { return mk_desc(sb + 12 * SLOT + part * 2048, 1024, 0, 1); }
__device__ __forceinline__ uint64_t sum_b(uint32_t sb) { return mk_desc(sb + OFF_SEL, 16, 128, 0); }
__device__ __forceinline__ uint32_t split_bf16(float v) { return pack_bf16(v, v - bf_round(v)); }

template <int N> __device__ __forceinline__ void padn() { if constexpr (N > 1) { padn<N / 2>(); padn<N - N / 2>(); } else if constexpr (N == 1) asm volatile("nanosleep.u32 1;"); }
__global__ void __launch_bounds__(NTHREADS, 1) fused_kernel(const __grid_constant__ Params P) {
  extern __shared__ __align__(1024) uint8_t smem_raw[];
  const uint32_t sb = smem_u32(smem_raw);
  const uint32_t bars = sb + OFF_BAR;
  const int tid = threadIdx.x;
  const int wg = __shfl_sync(0xffffffffu, tid >> 7, 0);
  const int warp = __shfl_sync(0xffffffffu, (tid >> 5) & 3, 0);
  const int lane = tid & 31;
  const int b = (blockIdx.x & 1) * 64 + (blockIdx.x >> 1);
  const bool ffn = (blockIdx.x & 7) != 7;
  const int fi = blockIdx.x - (blockIdx.x >> 3);
  const int rbk = b >> 4, hp = b & 15;
  const int rb = b >> 3, cb = b & 7;
#define BAR(i) (bars + 8u * (uint32_t)(i))
#define MMA_IDS \
    const int tid = fresh_tid(), lane = tid & 31; \
    const bool leader = (tid & 127) == 0; \
    const uint32_t srow = (uint32_t)(warp * 16 + (lane & 7) + ((lane >> 3) & 1) * 8); \
    const uint32_t sx = (uint32_t)(lane >> 4) ^ (srow & 7); \
    const int c2 = (lane & 3) * 2, lr = warp * 16 + (lane >> 2); \
    (void)leader; (void)sx; (void)c2; (void)lr;

  auto load_kv = [&](int it) {
    const uint32_t s = sb + (uint32_t)(it & 3) * 3 * SLOT, fb = BAR(B_FKV + it);
    mbar_expect_tx(fb, 3 * SLOT);
    tma_load_2d(s, &P.mX, fb, it * 64, rb * 128);
    tma_load_2d(s + SLOT, &P.mX, fb, it * 64, (rb ^ 1) * 128);
    tma_load_2d(s + 2 * SLOT, &P.mW, fb, 1024 + hp * 64, it * 64);
    tma_load_2d(s + 2 * SLOT + 8192, &P.mW, fb, 2048 + hp * 64, it * 64);
  };
  auto prefetch = [&](int c) {
    if (c < 2) { l2_prefetch(P.wo + b * 8192 + c * 4096, 8192); return; }
    if (!ffn) return;
    const int e = c - 2;
    if (e < 16) {
      asm volatile("cp.async.bulk.prefetch.tensor.2d.L2.global.tile [%0, {%1, %2}];"
                   :: "l"((e & 1) ? &P.mWuP : &P.mWgP), "r"((fi >> 1) * 64), "r"((e >> 1) * 128 + (fi & 1) * 64) : "memory");
    } else {
      l2_prefetch(P.wd + (size_t)fi * 32768 + (e - 16) * 4096, 8192);
    }
  };

  {
    const int w16 = wg * 4 + warp;
    const uint32_t cnt = w16 == 14 ? 128u : ((0x300Cu >> w16) & 1u) + 1u;
    if (elect()) {
      if (w16 == 11) {
#pragma unroll
        for (int i = 0; i < 4; i++) mbar_init(BAR(B_FKV + i), 1u);
        asm volatile("fence.mbarrier_init.release.cluster;" ::: "memory");
        load_kv(0);
      }
#pragma unroll
      for (int i = 0; i < 8; i++)
        if (w16 || i >= 4) mbar_init(BAR(w16 * 8 + i), w16 == 15 ? (uint32_t)(MISC_COUNTS >> (8 * i)) & 255u : cnt);
      mbar_init(BAR(B_FS + w16), w16 >= 14 ? 2u : 1u);
      mbar_init(BAR(B_FW + w16), 1u);
      asm volatile("fence.mbarrier_init.release.cluster;" ::: "memory");
    }
    __syncwarp();
    if (w16 == 11 && elect()) {
#pragma unroll 1
      for (int i = 1; i < 4; i++) load_kv(i);
    }
    __syncwarp();
  }

  if (wg >= 2) {
    if (wg == 3) {
      asm volatile("setmaxnreg.dec.sync.aligned.u32 64;");
      asm volatile("barrier.sync 0;" ::: "memory");
        if (warp) {
          const int q = 3 * b + warp - 1, cg = q % 96, kq = q / 96;
          const uint32_t buf = sb + (warp == 3 ? OFF_PHIQ : 12 * SLOT + (warp - 1) * 8192);
          const uint32_t fb = BAR(B_FS + (warp - 1) * 4);
          mbar_wait(BAR(B_FKV + 5));
          if (elect()) {
#pragma unroll
            for (int p = 0; p < 2; p++) { mbar_expect_tx(fb + p * 8, 4096); tma_load_2d(buf + p * 4096, &P.mWs, fb + p * 8, cg * 32, kq * 256 + p * 64); }
          }
          float cs[8];
#pragma unroll
          for (int i = 0; i < 8; i++) cs[i] = 0.f;
          const unsigned ep = ld_relaxed(&g_epoch);
#pragma unroll 1
          for (int p = 0; p < 4; p++) {
            mbar_wait(fb + p * 8);
            uint4 v[8];
#pragma unroll
            for (int i = 0; i < 8; i++) v[i] = lds_u4(buf + (p & 1) * 4096 + i * 512 + lane * 16);
            if (p < 2) {
              uint32_t dep = 0;
#pragma unroll
              for (int i = 0; i < 8; i++) dep ^= v[i].x;
              const int n = p + 2 + (int)__shfl_sync(0xffffffffu, zero_after(dep), 0);
              if (elect()) {
                mbar_expect_tx(fb + n * 8, 4096);
                tma_load_2d(buf + (n & 1) * 4096, &P.mWs, fb + n * 8, cg * 32, kq * 256 + n * 64);
              }
            }
#pragma unroll
            for (int i = 0; i < 8; i += 2) {
              cs[0] += bf_lo(v[i].x) + bf_lo(v[i + 1].x); cs[1] += bf_hi(v[i].x) + bf_hi(v[i + 1].x);
              cs[2] += bf_lo(v[i].y) + bf_lo(v[i + 1].y); cs[3] += bf_hi(v[i].y) + bf_hi(v[i + 1].y);
              cs[4] += bf_lo(v[i].z) + bf_lo(v[i + 1].z); cs[5] += bf_hi(v[i].z) + bf_hi(v[i + 1].z);
              cs[6] += bf_lo(v[i].w) + bf_lo(v[i + 1].w); cs[7] += bf_hi(v[i].w) + bf_hi(v[i + 1].w);
            }
          }
          {
            const bool u4 = lane & 16, u2 = lane & 8, u1 = lane & 4;
#pragma unroll
            for (int i = 0; i < 4; i++) cs[i] = (u4 ? cs[4 + i] : cs[i]) + __shfl_xor_sync(0xffffffffu, u4 ? cs[i] : cs[4 + i], 16);
#pragma unroll
            for (int i = 0; i < 2; i++) cs[i] = (u2 ? cs[2 + i] : cs[i]) + __shfl_xor_sync(0xffffffffu, u2 ? cs[i] : cs[2 + i], 8);
            cs[0] = (u1 ? cs[1] : cs[0]) + __shfl_xor_sync(0xffffffffu, u1 ? cs[0] : cs[1], 4);
          }
          if (warp == 3 && elect()) {
            mbar_expect_tx(BAR(B_PHI), 12288);
            tma_load_2d(sb + OFF_PHIK, &P.mPhi, BAR(B_PHI), 0, hp * 64);
            tma_load_2d(sb + OFF_PHIQ, &P.mPhi, BAR(B_PHI), (int)zero_after(__float_as_uint(cs[0])), cb * 128);
            tma_load_2d(sb + OFF_PHIQ + 4096, &P.mPhi, BAR(B_PHI), (int)zero_after(__float_as_uint(cs[0])), cb * 128 + 64);
          }
          st_rec8(&g_colsum[kq][cg * 32 + (lane & 3) * 8 + (lane >> 2)], __float_as_uint(cs[0]), ep + 1);
          if (lane == 0) mbar_arrive(BAR(B_CSD));
        }
      asm volatile("setmaxnreg.dec.sync.aligned.u32 32;");
      if (warp == 0) {
#pragma unroll 1
        for (int it = 4; it < 16; it++) {
          mbar_wait(BAR(B_DKV + it - 4));
          if (elect()) load_kv(it);
        }
#pragma unroll 1
        for (int it = 0; it < 16; it++) {
          const uint32_t fb = BAR(B_FQ + it), s = sb + tab4(Q_BSLOTS, it) * SLOT;
          const int kc = (int)tab4(Q_CHUNKS, it) * 64;
          if (it == 5) mbar_wait(BAR(B_DKV + 15));
          mbar_wait(it >= 5 ? BAR(B_DQ + it - 5) : BAR(B_DKV + 12 + (it >> 1)));
          if (elect()) {
            mbar_expect_tx(fb, it < 4 ? SLOT : 2 * SLOT);
            if (it >= 4) tma_load_2d(sb + tab4(Q_ASLOTS, it) * SLOT, &P.mX, fb, kc, rb * 128);
            tma_load_2d(s, &P.mW, fb, cb * 128, kc);
            tma_load_2d(s + 8192, &P.mW, fb, cb * 128 + 64, kc);
          }
        }
        mbar_wait(BAR(B_DQ + 11));
        mbar_wait(BAR(X_PACE));
        if (elect()) {
          mbar_expect_tx(BAR(B_FX), 2 * SLOT);
          tma_load_2d(sb, &P.mX, BAR(B_FX), cb * 128, rb * 128);
          tma_load_2d(sb + 2 * SLOT, &P.mX, BAR(B_FX), cb * 128 + 64, rb * 128);
        }
        mbar_wait(BAR(B_KVRDY));
        const unsigned tag = lds_u(sb + OFF_RED + 4);
        uint32_t seen = 0;
#pragma unroll 1
        for (int j = 2; j < 16; j++) {
          const int kc = pc_chunk(j, cb);
          const uint32_t need = j > 8 ? 0u : GATE ? 0xFFFFu : 3u << kc;
#pragma unroll 1
          for (int it = 0; it < SPIN && (seen & need) != need; it++) {
            seen = __ballot_sync(0xffffffffu, ld_relaxed(&g_oflag[rb][cb][lane & 15].x) == tag);
          }
          mbar_wait(BAR(j < 4 ? B_XDONE : j < 6 ? B_XREAD : B_DC + j - 5));
          if (elect()) {
            mbar_expect_tx(BAR(B_FKV + j), SLOT);
            asm volatile("cp.async.bulk.shared::cluster.global.mbarrier::complete_tx::bytes [%0], [%1], %2, [%3];"
              :: "r"(sb + tab4(PC_ASLOTS, j) * SLOT), "l"(&g_o[rb][kc][0][0][0]), "n"(SLOT), "r"(BAR(B_FKV + j)) : "memory");
          }
        }
      } else {
        if (warp == 1) {
#pragma unroll 1
          for (int j = 0; j < 16; j++) {
            const uint32_t s = sb + tab4(PC_BSLOTS, j) * SLOT, fb = BAR(B_FB + j);
            const int kc = pc_chunk(j, cb);
            mbar_wait(BAR(tab8(WO_WAIT0, WO_WAIT1, j)));
            mbar_wait(BAR(tab8(WO_PACE0, WO_PACE1, j)));
            if (elect()) {
              mbar_expect_tx(fb, SLOT);
              tma_load_2d(s, &P.mWo, fb, cb * 128, kc * 64);
              tma_load_2d(s + 8192, &P.mWo, fb, cb * 128 + 64, kc * 64);
            }
          }
        } else if (warp == 3) {
#pragma unroll 1
          for (int c = 0; c < 26; c++) {
            mbar_wait(BAR(c < 8 ? B_DKV + 8 + c : B_DQ + ((c - 8) >> 1)));
            if (elect()) prefetch(c);
          }
          __syncwarp();
          if (lane == 0) mbar_arrive(BAR(B_KVRDY));
          mbar_wait(BAR(B_DC + 10));
#pragma unroll 1
          for (int i = 0; i < 4; i++) st_rec16(&g_hstat[rb][cb][i * 32 + lane], 0u, 0u, 0u, 0u);
          st_rec16(reinterpret_cast<uint4*>(&g_candx[rb][cb * 64]) + lane, 0u, 0u, 0u, 0u);
          if (lane < 2) st_rec16(reinterpret_cast<uint4*>(&g_key[cb][rb][0]) + lane, 0u, 0u, 0u, 0u);
          __syncwarp();
          if (lane == 0) mbar_arrive(BAR(B_RESET2));
        } else {
          mbar_wait(BAR(B_DQ + RSTQ));
#pragma unroll 1
          for (int i = 0; i < 12; i++) {
            st_rec16(&g_kvp[2 * hp][rbk][0][i * 32 + lane], 0u, 0u, 0u, 0u);
            st_rec16(&g_kvp[2 * hp + 1][rbk][0][i * 32 + lane], 0u, 0u, 0u, 0u);
          }
#pragma unroll 1
          for (int i = 0; i < 3; i++) st_rec16(&g_kvr[2 * hp + (lane >> 4)][i][rbk * 16 + (lane & 15)], 0u, 0u, 0u, 0u);
          if (lane < 16) st_rec16(&g_oflag[rb][lane >> 1][cb * 2 + (lane & 1)], 0u, 0u, 0u, 0u);
          __syncwarp();
          if (lane == 0) mbar_arrive(BAR(B_RESET));
          if (ffn) {
#pragma unroll 1
            for (int n = 0; n < 12; n++) {
              const int i = (int)tab4(FFN_ORDER, n);
              const uint32_t s = sb + tab4(FFN_SLOTS, i) * SLOT, fb = BAR(B_FW + i);
              mbar_wait(BAR(tab8(FFN_WAIT0, FFN_WAIT1, n)));
              mbar_wait(BAR(tab8(FFN_PACE0, FFN_PACE1, n)));
              if (elect()) {
                mbar_expect_tx(fb, SLOT);
                if (i < 8) tma_load_2d_ef(s, (i & 1) ? &P.mWu : &P.mWg, fb, fi * 32, (i >> 1) * 256);
                else {
#pragma unroll
                  for (int e = 0; e < 4; e++) tma_load_2d_ef(s + e * 4096, &P.mWd, fb, (i - 8) * 256 + e * 64, fi * 32);
                }
              }
            }
          }
        }
      }
    } else {
      asm volatile("barrier.sync 0;" ::: "memory");
      const int t = tid - 256;
      const unsigned tag = ld_relaxed(&g_epoch) + 1;
      if (warp == 0) {
        float s = 0.f;
#pragma unroll
        for (int i = 0; i < 4; i++) s += sum8(ldg_nc16(P.wr + i * 256 + lane * 8));
        const uint2 w = *reinterpret_cast<const uint2*>(P.wr + cb * 128 + lane * 4);
        s = warp_sum(s);
        if (lane == 0) { sts_f(sb + OFF_RED, s); sts_u(sb + OFF_RED + 4, tag); }
        sts_f2(sb + OFF_WR + lane * 16, bf_lo(w.x), bf_hi(w.x));
        sts_f2(sb + OFF_WR + lane * 16 + 8, bf_lo(w.y), bf_hi(w.y));
      }
      __syncwarp();
      uint4 xv[16];
#pragma unroll
      for (int i = 0; i < 16; i++) {
        if (i == 0) mbar_wait(BAR(B_FKV + 5));
        xv[i] = ldg_nc16(P.x + (size_t)(b * 16 + warp * 4 + (lane >> 3)) * DM + i * 64 + (lane & 7) * 8);
      }
      {
        const float sh = __shfl_sync(0xffffffffu, bf_lo(xv[0].x), lane & 24);
        float s0 = 0.f, q0 = 0.f, s1 = 0.f, q1 = 0.f;
#pragma unroll
        for (int i = 0; i < 16; i++) { acc2(xv[i].x, sh, s0, q0); acc2(xv[i].y, sh, s1, q1); acc2(xv[i].z, sh, s0, q0); acc2(xv[i].w, sh, s1, q1); }
        s0 += s1; q0 += q1;
#pragma unroll
        for (int m = 4; m >= 1; m >>= 1) { s0 += __shfl_xor_sync(0xffffffffu, s0, m); q0 += __shfl_xor_sync(0xffffffffu, q0, m); }
        s0 *= (1.f / DM);
        const float var = fmaxf(q0 * (1.f / DM) - s0 * s0, 0.f);
        if ((lane & 7) == 0) st_rec16(&g_rowstat[b * 16 + warp * 4 + (lane >> 3)], __float_as_uint(rsq(var + 1e-5f)), __float_as_uint(-(s0 + sh)), 0u, tag);
      }
      {
        const uint4* rp = &g_rowstat[rb * 128 + t];
        const uint4* rq = &g_rowstat[(rb ^ 1) * 128 + t];
        const uint2* c0 = &g_colsum[0][1024 + (t >> 6) * 1024 + hp * 64 + (t & 63)];
        const uint2* c1 = &g_colsum[0][cb * 128 + t];
        uint4 v0, v1; uint2 u[8];
#pragma unroll 1
        for (int it = 0; it < SPIN; it++) {
          v0 = ld_rec16(rp); v1 = ld_rec16(rq);
          bool ok = true;
#pragma unroll
          for (int i = 0; i < 4; i++) { u[i] = ld_rec8(c0 + i * 3072); u[4 + i] = ld_rec8(c1 + i * 3072); }
#pragma unroll
          for (int i = 0; i < 8; i++) ok = ok && u[i].y == tag;
          if (__all_sync(0xffffffffu, ok && v0.w == tag && v1.w == tag)) break;
          __nanosleep(100);
        }
        sts_u(sb + OFF_RSTAT + t * 4, v0.x); sts_u(sb + OFF_RSTAT + (t + 128) * 4, v1.x);
        mbar_wait(BAR(B_CSD));
        {
          const uint32_t m0 = split_bf16(__uint_as_float(v0.y)), m1 = split_bf16(__uint_as_float(v1.y));
          sts_u4(sb + 12 * SLOT + 4096 + t * 16, m0, m0 & 0xFFFFu, 0u, 0u);
          sts_u4(sb + 12 * SLOT + 6144 + t * 16, m1, m1 & 0xFFFFu, 0u, 0u);
          sts_u2(sb + 12 * SLOT + 8192 + t * 8, 0u, 0u);
        }
#pragma unroll
        for (int e = 0; e < 2; e++) {
          const uint32_t hl = split_bf16((__uint_as_float(u[4 * e].x) + __uint_as_float(u[4 * e + 1].x)) + (__uint_as_float(u[4 * e + 2].x) + __uint_as_float(u[4 * e + 3].x)));
          const uint32_t a = sb + 12 * SLOT + e * 2048 + (t >> 6) * 1024 + (t & 7) * 2, ch = (uint32_t)(t >> 3) & 7u;
#pragma unroll
          for (uint32_t r = 0; r < 8; r++) sts_h(a + r * 128 + ((ch ^ r) << 4), r < 2 ? hl : r == 2 ? hl >> 16 : 0u);
        }
        sts_u(sb + OFF_ONES + t * 4, 0x3F803F80u);
        sts_u(sb + OFF_ONES + 512 + t * 4, 0x3F803F80u);
        if (t < 36) sts_u(sb + OFF_SEL + t * 4, (t & 4) ? 0u : 0x3F803F80u);
        {
          const uint32_t one = (t & 56) == 24 ? 0x3F80u << ((t & 1) * 16) : 0u, w = (t >> 1) & 3;
          sts_u4(sb + OFF_EYE + t * 16, w == 0 ? one : 0u, w == 1 ? one : 0u, w == 2 ? one : 0u, w == 3 ? one : 0u);
        }
        fence_async_smem();
        bar_sync(3, 128);
      }
      asm volatile("setmaxnreg.inc.sync.aligned.u32 160;");
      {
        float a0[64], a1[64];
        {
          wg_fence();
          wg_n128<0, 1>(a0, ext_a(sb, 0), ext_b(sb, 1), 0);
          wg_n128<0, 1>(a1, ext_a(sb, 64), ext_b(sb, 1), 0);
          wg_commit();
          wg_wait<0>();
          mbar_arrive(BAR(B_STAT));
        }
        {
          const bool leader = (tid & 127) == 0;
#pragma unroll 1
          for (int it = 12; it < 16; it++) mbar_wait(BAR(B_FKV + it));
          mbar_wait(BAR(B_QGO));
#pragma unroll 1
          for (int it = 0; it < 16; it++) {
            mbar_wait(BAR(B_FQ + it));
            const uint64_t da = mk_desc(sb + tab4(Q_ASLOTS, it) * SLOT, 16, 1024, 1);
            const uint64_t db = mk_desc(sb + tab4(Q_BSLOTS, it) * SLOT, 8192, 1024, 1);
#pragma unroll
            for (int hf = 0; hf < 2; hf++) {
              int yt = THR > hf ? fresh_tid() : tid;
              if (hf && THR > 1) asm volatile("mov.u32 %0, %%tid.y;" : "=r"(yt));
              wg_fence();
#pragma unroll
              for (int kk = 2 * hf; kk < 2 * hf + 2; kk++) {
                wg_n128<0, 1>(a0, da + kk * 2, db + kk * 128, 1);
                if (THR > 2 && kk == 2 * hf && yt == 8192) pin_order();
                wg_n128<0, 1>(a1, da + kk * 2 + 512, db + kk * 128, 1);
              }
              wg_commit();
              wg_wait<1>();
              if (hf == 0 && it > 0 && (yt & 127) == 0) mbar_arrive(BAR(B_DQ + it - 1));
            }
          }
          mbar_wait(BAR(B_KVFREE));
          wg_wait<0>();
          if (leader) mbar_arrive(BAR(B_DQ + 15));
        }
        MMA_IDS
#pragma unroll
        for (int c = 0; c < 2; c++) {
#pragma unroll
          for (int jj = 0; jj < 4; jj++)
#pragma unroll
            for (int mb = 0; mb < 2; mb++) {
              const float* a = mb ? &a1[32 * c + 8 * jj] : &a0[32 * c + 8 * jj];
              stsm_x4(sb + (10 + c) * SLOT + mb * 8192 + srow * 128 + ((sx ^ (2 * jj)) << 4),
                      pack_bf16(a[0], a[1]), pack_bf16(a[2], a[3]), pack_bf16(a[4], a[5]), pack_bf16(a[6], a[7]));
            }
          fence_async_smem();
          mbar_arrive(BAR(B_QD + c));
        }
        uint4 a[12];
#pragma unroll
        for (int i = 0; i < 12; i++) a[i] = make_uint4(0u, 0u, 0u, tag - 1);
#pragma unroll 1
        for (int it = 0; it < SPIN; it++) {
          bool ok = true;
#pragma unroll
          for (int i = 0; i < 12; i++) ld_rec16_stale(a[i], &g_kvr[4 * cb][i][tid & 127], tag);
#pragma unroll
          for (int i = 0; i < 12; i++) ok = ok && a[i].w == tag;
          if (__all_sync(0xffffffffu, ok)) break;
        }
        const uint32_t kx = (uint32_t)(lane >> 4) ^ ((srow >> 1) & 3);
#pragma unroll
        for (int h = 0; h < 4; h++) {
          const uint32_t base = sb + 12 * SLOT + h * 4096 + srow * 64;
          stsm_x4(base + (kx << 4), a[3 * h].x, a[3 * h].y, a[3 * h].z, a[3 * h + 1].x);
          stsm_x4(base + ((kx ^ 2) << 4), a[3 * h + 1].y, a[3 * h + 1].z, a[3 * h + 2].x, a[3 * h + 2].y);
          if (h & 1)
            stsm_x4(sb + 13 * SLOT + srow * 64 + ((kx ^ (h - 1)) << 4), (a[3 * h - 1].z & 0xFFFFu) | 0x3F800000u, (a[3 * h - 1].z >> 16) | 0x3F800000u,
                    (a[3 * h + 2].z & 0xFFFFu) | 0x3F800000u, (a[3 * h + 2].z >> 16) | 0x3F800000u);
        }
        fence_async_smem();
        __syncwarp();
        if (lane == 0) mbar_arrive(BAR(B_KVRDY));
      }
    }
    if (wg == 3) mbar_wait(BAR(B_DC + 15));
    asm volatile("setmaxnreg.inc.sync.aligned.u32 160;");
    const int w8 = (wg - 2) * 4 + warp;
    uint32_t wf[32][4], wd[16][4];
    if (ffn) {
      const int lane = fresh_tid() & 31;
      const uint32_t mrow = (uint32_t)((lane & 7) + (lane >> 4) * 8), mch = (uint32_t)(lane >> 3) & 1u;
      mbar_wait(BAR(B_FW + w8));
      const uint32_t wsm = sb + tab4(FFN_SLOTS, w8) * SLOT + mrow * 64;
      const uint32_t sw = (mrow >> 1) & 3;
#pragma unroll
      for (int i = 0; i < 16; i++) {
        ldsm_x4_t(wf[2 * i], wsm + i * 1024 + ((mch ^ sw) << 4));
        ldsm_x4_t(wf[2 * i + 1], wsm + i * 1024 + (((2 + mch) ^ sw) << 4));
      }
      uint32_t dep = 0;
#pragma unroll
      for (int i = 0; i < 32; i++) dep ^= wf[i][0];
      if (w8 < 4 && lane == 0) mbar_arrive(BAR(B_REL + w8) + zero_after(dep));
    } else if (w8 == 0 && elect()) {
      mbar_arrive(BAR(B_REL));
    }
    if (ffn) {
      const int lane = fresh_tid() & 31;
      if (wg == 2) mbar_wait(BAR(B_DC + 12));
#pragma unroll
      for (int i = 0; i < 2; i++) st_rec16(reinterpret_cast<uint4*>(&g_ypart[w8 * 16 + i * 8 + (lane >> 2)][fi][0]) + (lane & 3), 0u, 0u, 0u, 0u);
      __syncwarp();
    }
    mbar_wait(BAR(B_DC + 15));
    asm volatile("setmaxnreg.inc.sync.aligned.u32 224;");
    if (ffn) {
      const int lane = fresh_tid() & 31;
      const uint32_t mrow = (uint32_t)((lane & 7) + (lane >> 4) * 8), mch = (uint32_t)(lane >> 3) & 1u;
      mbar_wait(BAR(B_FW + 8 + (w8 >> 1)));
      const uint32_t dsm = sb + tab4(FFN_SLOTS, 8 + (w8 >> 1)) * SLOT + (w8 & 1) * 8192 + mrow * 128;
#pragma unroll
      for (int i = 0; i < 8; i++) {
        const uint32_t a = dsm + (i >> 2) * 4096 + ((((uint32_t)(i & 3) * 2 + mch) ^ (mrow & 7)) << 4);
        ldsm_x4_t(wd[2 * i], a);
        ldsm_x4_t(wd[2 * i + 1], a + 2048);
      }
    }
    {
      const int t = fresh_tid() - 256, lane = t & 31;
      const uint32_t xs = sb + OFF_PHIQ + w8 * 512;
      const unsigned tag = lds_u(sb + OFF_RED + 4);
      uint32_t wkey;
      {
        uint2 v;
#pragma unroll 1
        for (int it = 0; it < SPIN; it++) {
          v = ld_rec8(&g_key[cb][lane & 15][0]);
          if (__all_sync(0xffffffffu, v.y == tag)) break;
        }
        wkey = __reduce_max_sync(0xffffffffu, v.x);
      }
      const int wrow = (0xFFFF - (int)(wkey & 0xFFFFu)) & (SEQ - 1);
      {
        const uint4* src = reinterpret_cast<const uint4*>(&g_candx[wrow >> 7][(w8 >> 1) * 128]) + lane;
        uint4 v0, v1;
#pragma unroll 1
        for (int it = 0; it < SPIN; it++) {
          v0 = ld_rec16(src); v1 = ld_rec16(src + 32);
          if (__all_sync(0xffffffffu, v0.y == tag && v0.w == tag && v1.y == tag && v1.w == tag)) break;
        }
        const uint32_t a = xs + (lane >> 3) * 64 + (lane & 1) * 32 + ((lane >> 1) & 3) * 4;
        sts_u(a, v0.x); sts_u(a + 16, v0.z); sts_u(a + 256, v1.x); sts_u(a + 272, v1.z);
        __syncwarp();
      }
      if (t == 0) mbar_arrive(BAR(B_ROW));
      if (b == 0 && t == 0) g_epoch = tag;
      if (ffn) {
        {
          uint4 xb[8];
#pragma unroll
          for (int i = 0; i < 8; i++) xb[i] = lds_u4(xs + i * 64 + (lane & 3) * 16);
          float d[16];
#pragma unroll
          for (int i = 0; i < 16; i++) d[i] = 0.f;
#pragma unroll
          for (int i = 0; i < 8; i++) {
            mma_bf16(&d[0], wf[4 * i], xb[i].x, xb[i].y); mma_bf16(&d[4], wf[4 * i + 1], xb[i].x, xb[i].y);
            mma_bf16(&d[8], wf[4 * i + 2], xb[i].z, xb[i].w); mma_bf16(&d[12], wf[4 * i + 3], xb[i].z, xb[i].w);
          }
          const int c = lane & 3;
          const float v = c == 0 ? d[0] + d[8] : c == 1 ? d[2] + d[10] : c == 2 ? d[4] + d[12] : d[6] + d[14];
          sts_f(sb + OFF_CS + (uint32_t)(w8 * 32 + c * 8 + (lane >> 2)) * 4, v);
        }
        bar_sync(2, 256);
        uint32_t ab[4];
        {
          const uint32_t pr = sb + OFF_CS + lane * 4;
          const float g = (lds_f(pr) + lds_f(pr + 256)) + (lds_f(pr + 512) + lds_f(pr + 768));
          const float u = (lds_f(pr + 128) + lds_f(pr + 384)) + (lds_f(pr + 640) + lds_f(pr + 896));
          const float act = g * rcp(1.f + ex2(-g * L2E)) * u;
          const uint32_t pair = pack_bf16(act, __shfl_down_sync(0xffffffffu, act, 1));
#pragma unroll
          for (int i = 0; i < 4; i++) ab[i] = __shfl_sync(0xffffffffu, pair, i * 8 + (lane & 3) * 2);
        }
        float d[32];
#pragma unroll
        for (int i = 0; i < 32; i++) d[i] = 0.f;
        {
#pragma unroll
          for (int i = 0; i < 8; i++) mma_bf16(&d[4 * i], wd[2 * i], ab[0], ab[1]);
#pragma unroll
          for (int i = 0; i < 8; i++) mma_bf16(&d[4 * i], wd[2 * i + 1], ab[2], ab[3]);
        }
        const int c = lane & 3;
#pragma unroll
        for (int i = 0; i < 4; i++) {
          const float v = c == 0 ? d[8 * i] : c == 1 ? d[8 * i + 2] : c == 2 ? d[8 * i + 4] : d[8 * i + 6];
          st_rec8(&g_ypart[w8 * 16 + i * 4 + c][fi][lane >> 2], __float_as_uint(v), tag);
        }
      }
      float y0 = 0.f, y1 = 0.f;
      uint4 fin;
      if (w8 == 7) {
#pragma unroll 1
        for (int it = 0; it < SPIN; it++) {
          fin = ld_rec16(&g_cand[wrow >> 7][b * 4 + (lane & 3)]);
          if (__all_sync(0xffffffffu, fin.w == tag)) break;
        }
      } else {
        const uint4* yp = reinterpret_cast<const uint4*>(&g_ypart[b][0][0]) + t;
        uint4 v0, v1;
#pragma unroll 1
        for (int it = 0; it < SPIN; it++) {
          v0 = ld_rec16(yp); v1 = ld_rec16(yp + 2 * NFFN);
          if (__all_sync(0xffffffffu, v0.y == tag && v0.w == tag && v1.y == tag && v1.w == tag)) break;
        }
        y0 = __uint_as_float(v0.x) + __uint_as_float(v1.x); y1 = __uint_as_float(v0.z) + __uint_as_float(v1.z);
      }
#pragma unroll
      for (int m = 4; m <= 16; m <<= 1) { y0 += __shfl_xor_sync(0xffffffffu, y0, m); y1 += __shfl_xor_sync(0xffffffffu, y1, m); }
      if (lane < 4) sts_f2(sb + OFF_RED + 64 + (uint32_t)(w8 * 8 + lane * 2) * 4, y0, y1);
      uint32_t u = wkey >> 16;
      u = (u & 0x8000u) ? (u & 0x7FFFu) : (~u & 0xFFFFu);
      const float sig = rcp(1.f + ex2(-__uint_as_float(u << 16) * L2E));
      bar_sync(2, 256);
      if (w8 == 7) {
        float2 v = lds_f2(sb + OFF_RED + 64 + lane * 8);
#pragma unroll
        for (int m = 4; m <= 16; m <<= 1) { v.x += __shfl_xor_sync(0xffffffffu, v.x, m); v.y += __shfl_xor_sync(0xffffffffu, v.y, m); }
        if (lane < 4)
          *reinterpret_cast<uint32_t*>(P.out + (size_t)wrow * DM + b * 8 + lane * 2) =
              pack_bf16(bf_lo(fin.y) + fmaf(v.x, sig, bf_lo(fin.x)), bf_hi(fin.y) + fmaf(v.y, sig, bf_hi(fin.x)));
      }
    }
  } else {
    if (PAD && blockIdx.x == 5000) padn<PAD>();
    asm volatile("setmaxnreg.inc.sync.aligned.u32 160;");
    asm volatile("barrier.sync 0;" ::: "memory");
    {
      const bool leader = (tid & 127) == 0;
      {
        float a0[64], a1[64];
#pragma unroll 1
        for (int it = 0; it < 16; it++) {
          mbar_wait(BAR(B_FKV + it));
          const uint32_t s = sb + (uint32_t)(it & 3) * 3 * SLOT;
          const uint64_t da = mk_desc(s + wg * SLOT, 16, 1024, 1), db = mk_desc(s + 2 * SLOT, 8192, 1024, 1);
          wg_fence();
#pragma unroll
          for (int kk = 0; kk < 4; kk++) {
            wg_n128<0, 1>(a0, da + kk * 2, db + kk * 128, (it | kk) != 0);
            wg_n128<0, 1>(a1, da + kk * 2 + 512, db + kk * 128, (it | kk) != 0);
          }
          wg_commit();
          wg_wait<1>();
          if (it > 0 && leader) mbar_arrive(BAR(B_DKV + it - 1));
        }
        mbar_wait(BAR(B_STAT));
        wg_fence();
        wg_n128<0, 1>(a0, ext_a(sb, wg * 128), ext_b(sb, 0), 1);
        wg_n128<0, 1>(a1, ext_a(sb, wg * 128 + 64), ext_b(sb, 0), 1);
        wg_commit();
        if (leader) mbar_arrive(BAR(B_QGO));
        mbar_wait(BAR(B_PHI));
        wg_wait<0>();
        if (leader) mbar_arrive(BAR(B_DKV + 15));
        if (PIN & 2) pin_order();
        MMA_IDS
        const uint32_t rs = sb + OFF_RSTAT + (uint32_t)(wg * 128 + lr) * 4;
        const uint32_t vt = sb + 12 * SLOT + wg * 4096 + srow * 64 + (((uint32_t)(lane >> 4) ^ ((srow >> 1) & 3)) << 4);
        float pa[16], pb[16];
        uint32_t vp[16];
        const uint64_t dw = mk_desc(sb + OFF_PHIK, 16, 512, 2);
        auto pack_v = [&](const float* a, int mb) {
          const float r0 = lds_f(rs + mb * 256), r1 = lds_f(rs + mb * 256 + 32);
#pragma unroll
          for (int i = 0; i < 16; i++) vp[i] = pack_bf16(a[32 + 2 * i] * ((i & 1) ? r1 : r0), a[33 + 2 * i] * ((i & 1) ? r1 : r0));
        };
        auto put_v = [&]() {
#pragma unroll
          for (int jj = 0; jj < 4; jj++) stsm_x4((vt + (jj >> 1) * 8192) ^ (32 * (jj & 1)), vp[4 * jj], vp[4 * jj + 1], vp[4 * jj + 2], vp[4 * jj + 3]);
        };
        bar_sync(1, 256);
        pack_v(a0, 0);
        put_v();
        auto logits = [&](const uint32_t (&k)[16]) {
          wg_fence();
          wg_n32_rs<1>(pa, k[0], k[1], k[2], k[3], dw, 0);
          wg_n32_rs<1>(pb, k[8], k[9], k[10], k[11], dw + 128, 0);
          wg_n32_rs<1>(pa, k[4], k[5], k[6], k[7], dw + 64, 1);
          wg_n32_rs<1>(pb, k[12], k[13], k[14], k[15], dw + 192, 1);
          wg_commit();
        };
        uint32_t k0[16], k1[16];
        pin_order();
#pragma unroll
        for (int i = 0; i < 16; i++) k0[i] = pack_pin(a0[2 * i], a0[2 * i + 1]);
        logits(k0);
        if (leader) mbar_arrive(BAR(B_QGO2));
#pragma unroll
        for (int i = 0; i < 16; i++) k1[i] = pack_pin(a1[2 * i], a1[2 * i + 1]);
        pack_v(a1, 1);
        if (PIN & 1) pin_order();
        wg_wait<0>();
        float kv[20];
        auto half = [&](float (&p0)[16], float (&p1)[16], int mb) {
          const float sc0 = lds_f(rs + mb * 256) * L2E, sc1 = lds_f(rs + mb * 256 + 32) * L2E;
          const uint32_t ft = sb + 10 * SLOT + wg * 8192 + srow * 128 + (sx << 4);
          uint32_t fo[32];
          auto put = [&](int h) {
#pragma unroll
            for (int g = 4 * h; g < 4 * h + 4; g++) stsm_x4((ft + h * SLOT) ^ (32 * (g & 3)), fo[4 * g], fo[4 * g + 1], fo[4 * g + 2], fo[4 * g + 3]);
          };
          float tot;
          {
            tot = feature_fast(p0, sc0, sc1, &fo[0], [&]() {
              if (mb) {
                if (PIN & 128) pin_order();
                wg_wait<0>();
                bar_arrive(6 + wg, 256);
              }
            });
            if (mb) {
              bar_sync(7 - wg, 256);
              put_v();
            }
            put(0);
            tot += feature_fast(p1, sc0, sc1, &fo[16], []() {});
          }
          put(1);
          if (warp_fails(tot < FAST_LIMIT)) {
            feature_shifted(p0, p1, sc0, sc1, fo);
            put(0);
            put(1);
          }
          if (mb == 0) logits(k1);
          fence_async_smem();
          bar_sync(1, 256);
          if (PIN & 4) pin_order();
          const uint64_t d = mk_desc(sb + (10 + wg) * SLOT, 16, 1024, 1);
          const uint64_t e = mk_desc(sb + 12 * SLOT + wg * 8192, OFF_ONES - 12 * SLOT - wg * 8192, 512, 2);
          wg_fence();
#pragma unroll
          for (int kk = 0; kk < 8; kk++) wg_n40<1, 1>(kv, d + kk * 128, e + kk * (64 - (64 << 16)), (mb | kk) != 0);
          wg_commit();
        };
        half(pa, pb, 0);
        wg_wait<1>();
        half(pa, pb, 1);
        mbar_wait(BAR(B_RESET));
        const unsigned tag = lds_u(sb + OFF_RED + 4);
        uint4* dst = &g_kvp[2 * hp + wg][rbk][0][tid & 127];
        const uint4* src = &g_kvp[2 * hp + (lane >> 4)][0][warp][rbk * 16 + (lane & 15)];
        uint4 a[8];
        if (wg == 0 && warp < 3) {
#pragma unroll
          for (int p = 0; p < 8; p++) a[p] = ld_rec16(src + p * 384);
        }
        wg_wait<0>();
        if (PIN & 8) pin_order();
        kv[17] = kv[18];
#pragma unroll
        for (int i = 0; i < 3; i++)
          st_rec16(dst + i * 128, pack_bf16(kv[6 * i], kv[6 * i + 1]), pack_bf16(kv[6 * i + 2], kv[6 * i + 3]), pack_bf16(kv[6 * i + 4], kv[6 * i + 5]), tag);
        if (leader) mbar_arrive(BAR(B_KVFREE));
        if (wg == 0 && warp < 3) {
#pragma unroll 1
          for (int it = 0; it < SPIN; it++) {
            bool ok = true;
#pragma unroll
            for (int p = 0; p < 8; p++) ld_rec16_stale(a[p], src + p * 384, tag);
#pragma unroll
            for (int p = 0; p < 8; p++) ok = ok && a[p].w == tag;
            if (__all_sync(0xffffffffu, ok)) break;
          }
          float v[6] = {0.f, 0.f, 0.f, 0.f, 0.f, 0.f};
#pragma unroll
          for (int p = 0; p < 8; p++) {
            v[0] += bf_lo(a[p].x); v[1] += bf_hi(a[p].x); v[2] += bf_lo(a[p].y); v[3] += bf_hi(a[p].y); v[4] += bf_lo(a[p].z); v[5] += bf_hi(a[p].z);
          }
          st_rec16(&g_kvr[2 * hp + (lane >> 4)][warp][rbk * 16 + (lane & 15)], pack_bf16(v[0], v[1]), pack_bf16(v[2], v[3]), pack_bf16(v[4], v[5]), tag);
        }
      }
    }
    const uint32_t stg = sb + wg * 8192;
    float s0 = 0.f, q0 = 0.f, d0 = 0.f, s1 = 0.f, q1 = 0.f, d1 = 0.f;
    {
      MMA_IDS
      const unsigned tag = lds_u(sb + OFF_RED + 4);
      const uint32_t t3 = tag % 3u + 1u, tg = (t3 & 1u) | ((t3 & 2u) << 15);
      const int ln = __shfl_sync(0xffffffffu, lane, lane);
      uint4* const og = &g_o[rb][0][wg * 4 + warp][0][ln];
      const uint32_t af = sb + (uint32_t)(wg * 4 + warp) * 2048 + ln * 16;
      float acc[64];
      auto tile_addr = [&]() {
        uint32_t l = ln;
        asm volatile("" : "+r"(l));
        return stg + (uint32_t)warp * 2048 + (l & 15) * 128 + (((l >> 4) ^ (l & 7)) << 4);
      };
      auto add_x = [&]() {
        mbar_wait(BAR(B_FX));
        const uint64_t da = mk_desc(sb + OFF_EYE + 384, 512, 128, 0), db = mk_desc(stg, 2 * SLOT, 4096, 1);
        wg_fence();
#pragma unroll
        for (int s = 0; s < 4; s++) wg_n128<0, 1>(acc, da - s * 8, db + s * 64, s != 0);
        wg_commit();
      };
      auto announce = [&]() {
        if (warp == FLAGW && ln < 8) asm volatile("st.relaxed.gpu.global.u32 [%0], %1;" :: "l"(&g_oflag[rb][ln][cb * 2 + wg].x), "r"(tag) : "memory");
      };
      const bool early = !((LATE >> cb) & 1);
      uint32_t A[2][16];
      const bool lead = warp == 0 && ln == 0;
      {
        const float sc0 = lds_f(sb + OFF_RSTAT + (uint32_t)(wg * 64 + lr) * 4) * L2E, sc1 = lds_f(sb + OFF_RSTAT + (uint32_t)(wg * 64 + lr + 8) * 4) * L2E;
        auto logits = [&](float (&p0)[16], float (&p1)[16], int c) {
          const uint64_t dq = mk_desc(sb + (10 + c) * SLOT + wg * 8192, 16, 1024, 1), dw = mk_desc(sb + OFF_PHIQ + c * 4096, 16, 512, 2);
          mbar_wait(BAR(B_QD + c));
          wg_fence();
          wg_n32<0, 1>(p0, dq, dw, 0);
          wg_n32<0, 1>(p1, dq + 4, dw + 128, 0);
          wg_n32<0, 1>(p0, dq + 2, dw + 64, 1);
          wg_n32<0, 1>(p1, dq + 6, dw + 192, 1);
          wg_commit();
        };
        auto norm = [&](float (&p)[16], uint32_t (&f)[16], const float (&d)[4]) {
          if (warp_fails(feature_norm<false>(f, d) < FAST_LIMIT)) feature_shifted(p, p, sc0, sc1, f);
        };
        auto apply = [&](float (&u)[20], const uint32_t (&f)[16], int h) {
          const uint64_t d = mk_desc(sb + 12 * SLOT + h * 4096, SLOT - h * 4096 + h * 16, 512, 2);
          wg_fence();
#pragma unroll
          for (int s = 0; s < 4; s++) wg_n40_rs<1>(u, f[4 * s], f[4 * s + 1], f[4 * s + 2], f[4 * s + 3], d + s * 64, s != 0);
          wg_commit();
        };
        float pa[16], pb[16], pc[16], pd[16], u0[20], u1[20], u2[20], u3[20], da[4], db[4];
        uint32_t f0[16], f1[16], f2[16], f3[16];
        uint4* const od = og + cb * 2048;
        logits(pa, pb, 0);
        wg_wait<0>();
        feature_exp(pa, sc0, sc1, f0, da, sum_b(sb));
        if (PIN & 64) pin_order();
        logits(pc, pd, 1);
        feature_exp(pb, sc0, sc1, f1, db, sum_b(sb));
        wg_wait<1>();
        norm(pa, f0, da);
        feature_exp(pc, sc0, sc1, f2, da, sum_b(sb));
        wg_wait<1>();
        norm(pb, f1, db);
        wg_wait<0>();
        norm(pc, f2, da);
        if (QORD == 1) {
          feature_exp(pd, sc0, sc1, f3, db, sum_b(sb));
          wg_wait<0>();
          norm(pd, f3, db);
        }
        mbar_wait(BAR(B_KVRDY));
        if (FLAGP == 0 && early) announce();
        apply(u0, f0, 0);
        apply(u1, f1, 1);
        if (QORD == 0) {
          feature_exp(pd, sc0, sc1, f3, db, sum_b(sb));
          wg_wait<1>();
          apply(u2, f2, 2);
        } else {
          wg_wait<1>();
        }
        if (FLAGP == 1 && early) announce();
        attn_out(u0, tg, &A[0][0], od, early);
        if (FLAGP == 2 && early) announce();
        if (QORD) {
          wg_wait<0>();
          apply(u2, f2, 2);
        }
        attn_out(u1, tg, &A[0][8], od + 64, early);
        if (FLAGP == 3 && early) announce();
        if (PIN & 16) pin_order();
        if (QORD == 2) {
          feature_exp(pd, sc0, sc1, f3, db, sum_b(sb));
          wg_wait<1>();
          attn_out(u2, tg, &A[1][0], od + 1024, !LPUB);
          wg_wait<0>();
          norm(pd, f3, db);
          apply(u3, f3, 3);
          if (XMP < 2) { add_x(); wg_wait<1>(); } else wg_wait<0>();
        } else {
          if (QORD == 0) {
            wg_wait<1>();
            norm(pd, f3, db);
          }
          apply(u3, f3, 3);
          if (XMP == 0) { add_x(); wg_wait<2>(); } else wg_wait<1>();
          attn_out(u2, tg, &A[1][0], od + 1024, !LPUB);
          if (XMP == 1) add_x();
          if (XMP < 2) wg_wait<1>(); else wg_wait<0>();
        }
        if (lead) mbar_arrive(BAR(B_XDONE));
        attn_out(u3, tg, &A[1][8], od + 1088, !LPUB);
        if (!early) {
#pragma unroll
          for (int i = 0; i < 4; i++) st_rec16(od + i * 32, A[0][4 * i], A[0][4 * i + 1], A[0][4 * i + 2], A[0][4 * i + 3]);
          announce();
        }
      }
      auto take = [&](uint32_t (&a)[16], int j) {
        const uint32_t s = af + tab4(PC_ASLOTS, j) * SLOT;
#pragma unroll
        for (int i = 0; i < 4; i++) {
          const uint4 v = lds_u4(s + i * 512);
          a[4 * i] = v.x; a[4 * i + 1] = v.y; a[4 * i + 2] = v.z; a[4 * i + 3] = v.w;
        }
      };
      auto check = [&](uint32_t (&a)[16], int j) {
        if (PIN & 256) pin_order();
#pragma unroll
        for (int i = 0; i < 4; i++) a[4 * i] ^= tg;
        if (warp_fails((((a[0] | a[4]) | (a[8] | a[12])) & OTAG) == 0)) {
          const uint4* p = og + pc_chunk(j, cb) * 1024;
#pragma unroll 1
          for (int it = 0; it < SPIN; it++) {
#pragma unroll
            for (int i = 0; i < 4; i++) {
              const uint4 v = ld_rec16(p + i * 32);
              a[4 * i] = v.x ^ tg; a[4 * i + 1] = v.y; a[4 * i + 2] = v.z; a[4 * i + 3] = v.w;
            }
            if (__all_sync(0xffffffffu, (((a[0] | a[4]) | (a[8] | a[12])) & OTAG) == 0)) break;
          }
        }
      };
      if (XMP == 2) add_x();
#pragma unroll
      for (int i = 0; i < 4; i++) A[0][4 * i] ^= tg;
      {
        uint32_t bt = (uint32_t)mk_desc(sb + 3 * SLOT, 8192, 1024, 1);
        const uint32_t bl = bt + 4096;
#pragma unroll 1
        for (int m = 0; m < 16; m += 4) {
#pragma unroll
          for (int e = 0; e < 4; e++) {
            const int j = m + e;
            const uint32_t (&a)[16] = A[e & 1];
            mbar_wait(BAR(B_FB + j));
            const uint64_t db = (mk_desc(0, 0, 1024, 1)) | bt;
            wg_fence();
#pragma unroll
            for (int kk = 0; kk < 4; kk++) {
              wg_n128_rs<1>(acc, a[4 * kk], a[4 * kk + 1], a[4 * kk + 2], a[4 * kk + 3], db + kk * 128, 1);
              if (kk == PSPL) {
                wg_commit();
                wg_wait<1>();
                if (lead) mbar_arrive(BAR(j ? B_DC + j - 1 : B_XREAD));
                if (e || m) {
                  if (e < 3 || m < 12) mbar_wait<1>(BAR(B_FKV + j + 1));
                  take(A[(e & 1) ^ 1], (e + 1) & 3);
                }
                else if (LPUB == 1) {
#pragma unroll
                  for (int i = 0; i < 4; i++) st_rec16(og + cb * 2048 + 1024 + i * 32, A[1][4 * i], A[1][4 * i + 1], A[1][4 * i + 2], A[1][4 * i + 3]);
                }
                if (LPUB == 2 && e == 1 && m == 0) {
#pragma unroll
                  for (int i = 0; i < 4; i++) st_rec16(og + cb * 2048 + 1024 + i * 32, A[1][4 * i] ^ tg, A[1][4 * i + 1], A[1][4 * i + 2], A[1][4 * i + 3]);
                }
                wg_fence();
              }
            }
            wg_commit();
            asm volatile("{\n.reg .pred p;\nsetp.eq.u32 p, %0, %1;\nadd.u32 %0, %0, 1024;\n@p sub.u32 %0, %0, 5120;\n}\n" : "+r"(bt) : "r"(bl));
            if (e < 3 || m < 12) check(A[(e & 1) ^ 1], j + 1);
          }
        }
      }
      mbar_wait(BAR(B_RESET2));
      wg_wait<0>();
      if (leader) mbar_arrive(BAR(B_DC + 15));
#pragma unroll
      for (int j = 0; j < 16; j++) {
        const float2 w = lds_f2(sb + OFF_WR + (uint32_t)(j * 8 + c2) * 4);
        float a = acc[4 * j], c = acc[4 * j + 1];
        s0 += a + c; q0 = fmaf(a, a, fmaf(c, c, q0)); d0 = fmaf(a, w.x, fmaf(c, w.y, d0));
        a = acc[4 * j + 2]; c = acc[4 * j + 3];
        s1 += a + c; q1 = fmaf(a, a, fmaf(c, c, q1)); d1 = fmaf(a, w.x, fmaf(c, w.y, d1));
      }
#pragma unroll
      for (int m = 1; m <= 2; m <<= 1) {
        s0 += __shfl_xor_sync(0xffffffffu, s0, m); q0 += __shfl_xor_sync(0xffffffffu, q0, m); d0 += __shfl_xor_sync(0xffffffffu, d0, m);
        s1 += __shfl_xor_sync(0xffffffffu, s1, m); q1 += __shfl_xor_sync(0xffffffffu, q1, m); d1 += __shfl_xor_sync(0xffffffffu, d1, m);
      }
      if ((lane & 2) == 0) {
        const bool hi = lane & 1;
        st_rec16(&g_hstat[rb][cb][wg * 64 + lr + (hi ? 8 : 0)], __float_as_uint(hi ? s1 : s0), __float_as_uint(hi ? q1 : q0), __float_as_uint(hi ? d1 : d0), lds_u(sb + OFF_RED + 4));
      }
      const uint32_t ha = tile_addr();
#pragma unroll
      for (int jj = 0; jj < 8; jj++)
        stsm_x4((ha ^ (32 * (jj & 3))) + (jj >> 2) * 2 * SLOT,
                pack_bf16(acc[8 * jj], acc[8 * jj + 1]), pack_bf16(acc[8 * jj + 2], acc[8 * jj + 3]),
                pack_bf16(acc[8 * jj + 4], acc[8 * jj + 5]), pack_bf16(acc[8 * jj + 6], acc[8 * jj + 7]));
    }
    asm volatile("setmaxnreg.dec.sync.aligned.u32 32;");
    {
    MMA_IDS
    const int grow0 = rb * 128 + wg * 64 + lr;
    const unsigned tag = lds_u(sb + OFF_RED + 4);
    uint32_t key;
    {
      const int trow = wg * 64 + lr;
      uint4 r00, r01, r10, r11;
#pragma unroll 1
      for (int it = 0; it < SPIN; it++) {
        r00 = ld_rec16(&g_hstat[rb][c2][trow]); r01 = ld_rec16(&g_hstat[rb][c2 + 1][trow]);
        r10 = ld_rec16(&g_hstat[rb][c2][trow + 8]); r11 = ld_rec16(&g_hstat[rb][c2 + 1][trow + 8]);
        if (__all_sync(0xffffffffu, r00.w == tag && r01.w == tag && r10.w == tag && r11.w == tag)) break;
      }
      s0 = __uint_as_float(r00.x) + __uint_as_float(r01.x); q0 = __uint_as_float(r00.y) + __uint_as_float(r01.y); d0 = __uint_as_float(r00.z) + __uint_as_float(r01.z);
      s1 = __uint_as_float(r10.x) + __uint_as_float(r11.x); q1 = __uint_as_float(r10.y) + __uint_as_float(r11.y); d1 = __uint_as_float(r10.z) + __uint_as_float(r11.z);
#pragma unroll
      for (int m = 1; m <= 2; m <<= 1) {
        s0 += __shfl_xor_sync(0xffffffffu, s0, m); q0 += __shfl_xor_sync(0xffffffffu, q0, m); d0 += __shfl_xor_sync(0xffffffffu, d0, m);
        s1 += __shfl_xor_sync(0xffffffffu, s1, m); q1 += __shfl_xor_sync(0xffffffffu, q1, m); d1 += __shfl_xor_sync(0xffffffffu, d1, m);
      }
      const float sumw = lds_f(sb + OFF_RED);
      const float mean0 = s0 * (1.f / DM), mean1 = s1 * (1.f / DM);
      const float rstd0 = rsq(fmaxf(q0 * (1.f / DM) - mean0 * mean0, 0.f) + 1e-5f);
      const float rstd1 = rsq(fmaxf(q1 * (1.f / DM) - mean1 * mean1, 0.f) + 1e-5f);
      const uint32_t rr = pack_bf16(rstd0 * (d0 - mean0 * sumw), rstd1 * (d1 - mean1 * sumw));
      uint32_t u0 = rr & 0xFFFFu, u1 = rr >> 16;
      u0 = (u0 & 0x8000u) ? (~u0 & 0xFFFFu) : (u0 | 0x8000u);
      u1 = (u1 & 0x8000u) ? (~u1 & 0xFFFFu) : (u1 | 0x8000u);
      const uint32_t k0 = (u0 << 16) | (uint32_t)(0xFFFF - grow0), k1 = (u1 << 16) | (uint32_t)(0xFFFF - (grow0 + 8));
      key = __reduce_max_sync(0xffffffffu, max(k0, k1));
      if (lane == 0) sts_u(sb + OFF_RED + 16 + (uint32_t)(wg * 4 + warp) * 4, key);
      if ((lane & 3) == 0) {
        sts_f2(sb + OFF_RSTAT + trow * 8, rstd0, -mean0 * rstd0);
        sts_f2(sb + OFF_RSTAT + (trow + 8) * 8, rstd1, -mean1 * rstd1);
      }
      bar_sync(1, 256);
      const uint4 ka = lds_u4(sb + OFF_RED + 16), kb = lds_u4(sb + OFF_RED + 32);
      key = max(max(max(ka.x, ka.y), max(ka.z, ka.w)), max(max(kb.x, kb.y), max(kb.z, kb.w)));
    }
    if (tid == 0) st_rec8(&g_key[cb][rb][0], key, tag);
    const int crow = (0xFFFF - (int)(key & 0xFFFFu)) & 127;
    const bool own = (crow >> 4) == wg * 4 + warp;
    uint32_t co0 = 0, co1 = 0;
    if (own) {
      const uint32_t r = (uint32_t)(crow & 63);
      const float2 st = lds_f2(sb + OFF_RSTAT + crow * 8);
      const uint32_t a = stg + r * 128 + ((((uint32_t)lane >> 2) ^ (r & 7)) << 4) + (lane & 3) * 4;
      const uint32_t h0 = lds_u(a), h1 = lds_u(a + 2 * SLOT);
      uint32_t n0, n1;
      co0 = ln_res(h0, st.x, st.y, n0); co1 = ln_res(h1, st.x, st.y, n1);
      st_rec8(&g_candx[rb][cb * 64 + lane], n0, tag);
      st_rec8(&g_candx[rb][cb * 64 + 32 + lane], n1, tag);
      st_rec16(&g_cand[rb][cb * 64 + lane], n0, h0, key, tag);
      st_rec16(&g_cand[rb][cb * 64 + 32 + lane], n1, h1, key, tag);
    }
    __nv_bfloat16* ob = P.out + (size_t)(rb * 128 + wg * 64) * DM + cb * 128;
#pragma unroll 4
    for (int i = 0; i < 8; i++) {
      const uint32_t r = (uint32_t)(warp * 16 + (i & 3) * 4 + (lane >> 3));
      const uint32_t a = stg + (i >> 2) * 2 * SLOT + r * 128 + ((((uint32_t)lane & 7) ^ (r & 7)) << 4);
      const uint4 h = lds_u4(a);
      const float2 st = lds_f2(sb + OFF_RSTAT + (wg * 64 + r) * 8);
      uint32_t n;
      uint4 o;
      o.x = ln_res(h.x, st.x, st.y, n); o.y = ln_res(h.y, st.x, st.y, n); o.z = ln_res(h.z, st.x, st.y, n); o.w = ln_res(h.w, st.x, st.y, n);
      if (!own) sts_u4(a, o.x, o.y, o.z, o.w);
      else if ((int)(wg * 64 + r) != crow) stg16(ob + (size_t)r * DM + (i >> 2) * 64 + (lane & 7) * 8, o);
      if ((i & 3) == 3) {
        fence_async_smem();
        __syncwarp();
        if (i == 7) mbar_wait(BAR(B_ROW));
        if (elect()) {
          if (!own) tma_store_2d(&P.mOut, stg + (i >> 2) * 2 * SLOT + warp * 2048, cb * 128 + (i >> 2) * 64, rb * 128 + wg * 64 + warp * 16);
          asm volatile("cp.async.bulk.commit_group;" ::: "memory");
        }
        __syncwarp();
      }
    }
    if (elect()) {
      asm volatile("cp.async.bulk.wait_group.read 0;" ::: "memory");
    }
    __syncwarp();
    if (own) {
      uint2 v;
#pragma unroll 1
      for (int it = 0; it < SPIN; it++) {
        v = ld_rec8(&g_key[cb][lane & 15][0]);
        if (__all_sync(0xffffffffu, v.y == tag)) break;
      }
      if (__reduce_max_sync(0xffffffffu, v.x) != key) {
        uint32_t* op = reinterpret_cast<uint32_t*>(ob + (size_t)(crow & 63) * DM);
        op[lane] = co0; op[32 + lane] = co1;
      }
    }
    }
  }
#undef BAR
}

typedef CUresult (*EncodeFn)(CUtensorMap*, CUtensorMapDataType, cuuint32_t, void*, const cuuint64_t*, const cuuint64_t*,
                             const cuuint32_t*, const cuuint32_t*, CUtensorMapInterleave, CUtensorMapSwizzle,
                             CUtensorMapL2promotion, CUtensorMapFloatOOBfill);

void make_map(EncodeFn fn, CUtensorMap* m, const void* ptr, uint64_t cols, uint64_t rows, uint32_t bc, uint32_t br, CUtensorMapSwizzle swz) {
  cuuint64_t dims[2] = {cols, rows};
  cuuint64_t strides[1] = {cols * 2};
  cuuint32_t box[2] = {bc, br};
  cuuint32_t es[2] = {1, 1};
  fn(m, CU_TENSOR_MAP_DATA_TYPE_BFLOAT16, 2, const_cast<void*>(ptr), dims, strides, box, es, CU_TENSOR_MAP_INTERLEAVE_NONE, swz,
     CU_TENSOR_MAP_L2_PROMOTION_L2_128B, CU_TENSOR_MAP_FLOAT_OOB_FILL_NONE);
}

}

extern "C" void kernel_launch(void* const* d_in, const int* in_sizes, int n_in, void* d_out, int out_size) {
  static EncodeFn fn = nullptr;
  if (!fn) {
    cudaDriverEntryPointQueryResult q;
    cudaGetDriverEntryPoint("cuTensorMapEncodeTiled", (void**)&fn, cudaEnableDefault, &q);
    cudaFuncSetAttribute(fused_kernel, cudaFuncAttributeMaxDynamicSharedMemorySize, SMEM_BYTES);
  }
  Params P;
  P.x = (const __nv_bfloat16*)d_in[0];
  P.wqkv = (const __nv_bfloat16*)d_in[1];
  const __nv_bfloat16* wphi = (const __nv_bfloat16*)d_in[2];
  P.wo = (const __nv_bfloat16*)d_in[3];
  P.wr = (const __nv_bfloat16*)d_in[5];
  P.wg = (const __nv_bfloat16*)d_in[6];
  P.wu = (const __nv_bfloat16*)d_in[7];
  P.wd = (const __nv_bfloat16*)d_in[8];
  P.out = (__nv_bfloat16*)d_out;
  make_map(fn, &P.mX, P.x, DM, SEQ, 64, 128, CU_TENSOR_MAP_SWIZZLE_128B);
  make_map(fn, &P.mW, P.wqkv, 3 * DM, DM, 64, 64, CU_TENSOR_MAP_SWIZZLE_128B);
  make_map(fn, &P.mWo, P.wo, DM, DM, 64, 64, CU_TENSOR_MAP_SWIZZLE_128B);
  make_map(fn, &P.mPhi, wphi, 32, 1024, 32, 64, CU_TENSOR_MAP_SWIZZLE_64B);
  make_map(fn, &P.mWg, P.wg, FF, DM, 32, 256, CU_TENSOR_MAP_SWIZZLE_64B);
  make_map(fn, &P.mWu, P.wu, FF, DM, 32, 256, CU_TENSOR_MAP_SWIZZLE_64B);
  make_map(fn, &P.mWs, P.wqkv, 3 * DM, DM, 32, 64, CU_TENSOR_MAP_SWIZZLE_NONE);
  make_map(fn, &P.mWd, P.wd, DM, FF, 64, 32, CU_TENSOR_MAP_SWIZZLE_128B);
  make_map(fn, &P.mOut, P.out, DM, SEQ, 64, 16, CU_TENSOR_MAP_SWIZZLE_128B);
  make_map(fn, &P.mWgP, P.wg, FF, DM, 64, 64, CU_TENSOR_MAP_SWIZZLE_128B);
  make_map(fn, &P.mWuP, P.wu, FF, DM, 64, 64, CU_TENSOR_MAP_SWIZZLE_128B);
  fused_kernel<<<NCTA, NTHREADS, SMEM_BYTES, cudaStreamPerThread>>>(P);
}
```

```cpp
#include <cuda_runtime.h>
#include <cuda_bf16.h>
#include <cuda.h>
#include <stdint.h>

namespace {

constexpr int SEQ = 2048, DM = 1024, FF = 3584;
constexpr int NCTA = 128, NTHREADS = 512, NFFN = 112;
constexpr int SPIN = 1 << 17;
constexpr int RSTQ = 3;
constexpr int PSPL = 1;
constexpr int PIN = 145;
constexpr int RCPG = 4;
constexpr int THR = 1;
constexpr int QORD = 2;
constexpr int KH2 = 0;
constexpr int KSH = 0;
constexpr int LPUB = 2;
constexpr int PAD = 0;
constexpr int GATE = 0;
constexpr int FLAGP = 2;
constexpr int XMP = 1;
constexpr int FLAGW = 3;
constexpr int LATE = 0x78;
constexpr int QRD = 1;
constexpr int SXN = 4;
constexpr int SX0 = 2;
constexpr int SXD = 2;
constexpr int CSW = 0x65431234;
constexpr int HST = 0;
constexpr int KREP = 0;
constexpr int KGATE = 1;

constexpr uint32_t SLOT = 16384;
constexpr uint32_t OFF_MISC = 13 * SLOT;
constexpr uint32_t OFF_PHIK = OFF_MISC;
constexpr uint32_t OFF_PHIQ = OFF_MISC + 4096;
constexpr uint32_t OFF_ONES = OFF_MISC + 12288;
constexpr uint32_t OFF_RSTAT = OFF_MISC + 13312;
constexpr uint32_t OFF_EYE = OFF_MISC + 14336;
constexpr uint32_t OFF_CS = OFF_MISC + 15360;
constexpr uint32_t OFF_WR = OFF_MISC + 16384;
constexpr uint32_t OFF_BAR = OFF_MISC + 16896;
constexpr uint32_t OFF_RED = OFF_MISC + 18304;
constexpr uint32_t OFF_SEL = OFF_RED + 320;
constexpr uint32_t SMEM_BYTES = OFF_MISC + 19456;

enum {
  B_FKV = 0, B_DKV = 16, B_FQ = 32, B_DQ = 48,
  B_PHI = 64, B_RESET = 65, B_RESET2 = 66, B_ROW = 67, B_FX = 68, B_KEY = 69, B_REL = 72,
  B_FB = 80, B_DC = 96, B_QD = 112, B_STAT = 114,
  B_KVFREE = 120, B_QGO = 121, B_QGO2 = 122, B_CSD = 123, B_XDONE = 124, B_QREAD = 125, B_XREAD = 126, B_KVRDY = 127,
  B_FS = 128, B_FW = 144
};
constexpr unsigned long long MISC_COUNTS = 0x0502020203020202ull;

struct Params {
  CUtensorMap mX, mW, mWo, mPhi, mWg, mWu, mWs, mWd, mOut, mWgP, mWuP;
  const __nv_bfloat16 *x, *wqkv, *wo, *wr, *wg, *wu, *wd;
  __nv_bfloat16* out;
};

__device__ unsigned g_epoch;
__device__ __align__(128) uint4 g_rowstat[SEQ];
__device__ __align__(128) uint2 g_colsum[4][3 * DM];
__device__ __align__(128) uint4 g_kvp[32][8][3][128];
__device__ __align__(128) uint4 g_kvr[32][3][128];
__device__ __align__(128) uint4 g_o[16][16][8][4][32];
__device__ __align__(128) uint4 g_oflag[16][8][16];
__device__ __align__(128) uint4 g_hstat[16][8][128];
__device__ __align__(128) uint4 g_cand[16][512];
__device__ __align__(128) uint2 g_candx[16][512];
__device__ __align__(128) uint2 g_key[8][16][16];
__device__ __align__(128) uint4 g_ypart[128][NFFN][2];

__device__ __forceinline__ uint32_t smem_u32(const void* p) { return (uint32_t)__cvta_generic_to_shared(p); }
__device__ __forceinline__ bool elect() {
  uint32_t p;
  asm volatile("{\n.reg .pred P;\nelect.sync _|P, 0xffffffff;\nselp.u32 %0, 1, 0, P;\n}\n" : "=r"(p));
  return p != 0;
}
__device__ __forceinline__ void mbar_init(uint32_t bar, uint32_t cnt) { asm volatile("mbarrier.init.shared::cta.b64 [%0], %1;" :: "r"(bar), "r"(cnt)); }
__device__ __forceinline__ void mbar_expect_tx(uint32_t bar, uint32_t bytes) { asm volatile("mbarrier.arrive.expect_tx.shared::cta.b64 _, [%0], %1;" :: "r"(bar), "r"(bytes) : "memory"); }
__device__ __forceinline__ void mbar_arrive(uint32_t bar) { asm volatile("mbarrier.arrive.shared::cta.b64 _, [%0];" :: "r"(bar) : "memory"); }
template <int PARITY = 0>
__device__ __forceinline__ void mbar_wait(uint32_t bar) {
#pragma unroll 1
  for (int it = 0; it < SPIN; it++) {
    uint32_t ok;
    asm volatile("{\n.reg .pred p;\nmbarrier.try_wait.parity.shared::cta.b64 p, [%1], %2;\nselp.u32 %0, 1, 0, p;\n}\n" : "=r"(ok) : "r"(bar), "n"(PARITY) : "memory");
    if (ok) break;
  }
}
__device__ __forceinline__ void tma_load_2d(uint32_t dst, const CUtensorMap* m, uint32_t bar, int c0, int c1) {
  asm volatile("cp.async.bulk.tensor.2d.shared::cluster.global.mbarrier::complete_tx::bytes [%0], [%1, {%3, %4}], [%2];"
    :: "r"(dst), "l"(m), "r"(bar), "r"(c0), "r"(c1) : "memory");
}
__device__ __forceinline__ void tma_load_2d_ef(uint32_t dst, const CUtensorMap* m, uint32_t bar, int c0, int c1) {
  uint64_t pol;
  asm("createpolicy.fractional.L2::evict_first.b64 %0, 1.0;" : "=l"(pol));
  asm volatile("cp.async.bulk.tensor.2d.shared::cluster.global.mbarrier::complete_tx::bytes.L2::cache_hint [%0], [%1, {%3, %4}], [%2], %5;"
    :: "r"(dst), "l"(m), "r"(bar), "r"(c0), "r"(c1), "l"(pol) : "memory");
}
__device__ __forceinline__ void tma_store_2d(const CUtensorMap* m, uint32_t src, int c0, int c1) {
  asm volatile("cp.async.bulk.tensor.2d.global.shared::cta.bulk_group [%0, {%2, %3}], [%1];"
    :: "l"(m), "r"(src), "r"(c0), "r"(c1) : "memory");
}
__device__ __forceinline__ void cp_async16(uint32_t dst, const void* src) { asm volatile("cp.async.cg.shared.global [%0], [%1], 16;" :: "r"(dst), "l"(src) : "memory"); }
__device__ __forceinline__ void cp_commit() { asm volatile("cp.async.commit_group;" ::: "memory"); }
template <int N> __device__ __forceinline__ void cp_wait() { asm volatile("cp.async.wait_group %0;" :: "n"(N) : "memory"); }
__device__ __forceinline__ void l2_prefetch(const void* src, uint32_t bytes) {
  asm volatile("cp.async.bulk.prefetch.L2.global [%0], %1;" :: "l"(src), "r"(bytes) : "memory");
}
__device__ __forceinline__ void wg_fence() { asm volatile("wgmma.fence.sync.aligned;" ::: "memory"); }
__device__ __forceinline__ void wg_commit() { asm volatile("wgmma.commit_group.sync.aligned;" ::: "memory"); }
template <int N> __device__ __forceinline__ void wg_wait() { asm volatile("wgmma.wait_group.sync.aligned %0;" :: "n"(N) : "memory"); }
__device__ __forceinline__ void fence_async_smem() { asm volatile("fence.proxy.async.shared::cta;" ::: "memory"); }
__device__ __forceinline__ void bar_sync(int id, int n) { asm volatile("bar.sync %0, %1;" :: "r"(id), "r"(n) : "memory"); }
__device__ __forceinline__ void bar_arrive(int id, int n) { asm volatile("bar.arrive %0, %1;" :: "r"(id), "r"(n) : "memory"); }
__device__ __forceinline__ uint64_t mk_desc(uint32_t addr, uint32_t lbo, uint32_t sbo, uint32_t swz) {
  return (uint64_t)((addr & 0x3FFFF) >> 4) | ((uint64_t)((lbo & 0x3FFFF) >> 4) << 16) | ((uint64_t)(sbo >> 4) << 32) | ((uint64_t)swz << 62);
}
__device__ __forceinline__ void stsm_x4(uint32_t addr, uint32_t r0, uint32_t r1, uint32_t r2, uint32_t r3) {
  asm volatile("stmatrix.sync.aligned.m8n8.x4.shared.b16 [%0], {%1, %2, %3, %4};" :: "r"(addr), "r"(r0), "r"(r1), "r"(r2), "r"(r3) : "memory");
}
__device__ __forceinline__ void ldsm_x4(uint32_t& r0, uint32_t& r1, uint32_t& r2, uint32_t& r3, uint32_t addr) {
  asm volatile("ldmatrix.sync.aligned.m8n8.x4.shared.b16 {%0, %1, %2, %3}, [%4];" : "=r"(r0), "=r"(r1), "=r"(r2), "=r"(r3) : "r"(addr) : "memory");
}
__device__ __forceinline__ void ldsm_x4_t(uint32_t (&r)[4], uint32_t addr) {
  asm volatile("ldmatrix.sync.aligned.m8n8.x4.trans.shared.b16 {%0, %1, %2, %3}, [%4];" : "=r"(r[0]), "=r"(r[1]), "=r"(r[2]), "=r"(r[3]) : "r"(addr) : "memory");
}
__device__ __forceinline__ void mma_bf16(float* d, const uint32_t (&a)[4], uint32_t b0, uint32_t b1) {
  asm volatile("mma.sync.aligned.m16n8k16.row.col.f32.bf16.bf16.f32 {%0, %1, %2, %3}, {%4, %5, %6, %7}, {%8, %9}, {%0, %1, %2, %3};"
    : "+f"(d[0]), "+f"(d[1]), "+f"(d[2]), "+f"(d[3]) : "r"(a[0]), "r"(a[1]), "r"(a[2]), "r"(a[3]), "r"(b0), "r"(b1));
}
__device__ __forceinline__ uint32_t zero_after(uint32_t v) { uint32_t r; asm volatile("prmt.b32 %0, %1, 0, 0x4444;" : "=r"(r) : "r"(v)); return r; }
__device__ __forceinline__ int fresh_tid() { int v; asm volatile("mov.u32 %0, %%tid.x;" : "=r"(v)); return v; }
template <int ID> __device__ __forceinline__ void pin_at() {
  asm volatile("{\n.reg .pred p;\nsetp.eq.u32 p, %0, %1;\nPIN:\n@p nanosleep.u32 0;\n@p bra.uni PIN;\n}\n" :: "r"(blockIdx.x), "n"(4096 + ID) : "memory");
}
#define pin_order() pin_at<__LINE__>()
__device__ __forceinline__ uint32_t pack_bf16(float lo, float hi) {
  uint32_t r; asm("cvt.rn.bf16x2.f32 %0, %1, %2;" : "=r"(r) : "f"(hi), "f"(lo)); return r;
}
__device__ __forceinline__ uint32_t pack_pin(float lo, float hi) {
  uint32_t r; asm volatile("cvt.rn.bf16x2.f32 %0, %1, %2;" : "=r"(r) : "f"(hi), "f"(lo)); return r;
}
__device__ __forceinline__ uint32_t hadd2(uint32_t a, uint32_t b) { uint32_t r; asm("add.rn.bf16x2 %0, %1, %2;" : "=r"(r) : "r"(a), "r"(b)); return r; }
template <int H> __device__ __forceinline__ uint32_t hmul2(uint32_t a, uint32_t b) {
  uint32_t r;
  if (H) asm("{\n.reg .b16 l, h;\n.reg .b32 t;\nmov.b32 {l, h}, %2;\nmov.b32 t, {h, h};\nmul.rn.bf16x2 %0, %1, t;\n}\n" : "=r"(r) : "r"(a), "r"(b));
  else asm("{\n.reg .b16 l, h;\n.reg .b32 t;\nmov.b32 {l, h}, %2;\nmov.b32 t, {l, l};\nmul.rn.bf16x2 %0, %1, t;\n}\n" : "=r"(r) : "r"(a), "r"(b));
  return r;
}
template <int H> __device__ __forceinline__ uint32_t hfma2(uint32_t a, uint32_t b, uint32_t c) {
  uint32_t r;
  if (H) asm("{\n.reg .b16 l, h;\n.reg .b32 t;\nmov.b32 {l, h}, %2;\nmov.b32 t, {h, h};\nfma.rn.bf16x2 %0, %1, t, %3;\n}\n" : "=r"(r) : "r"(a), "r"(b), "r"(c));
  else asm("{\n.reg .b16 l, h;\n.reg .b32 t;\nmov.b32 {l, h}, %2;\nmov.b32 t, {l, l};\nfma.rn.bf16x2 %0, %1, t, %3;\n}\n" : "=r"(r) : "r"(a), "r"(b), "r"(c));
  return r;
}
__device__ __forceinline__ uint32_t hsq2(uint32_t a, uint32_t c) { uint32_t r; asm("fma.rn.bf16x2 %0, %1, %1, %2;" : "=r"(r) : "r"(a), "r"(c)); return r; }
__device__ __forceinline__ float bf_lo_p(uint32_t v) { float r; asm("prmt.b32 %0, %1, 0, 0x1044;" : "=f"(r) : "r"(v)); return r; }
__device__ __forceinline__ float bf_lo(uint32_t v) { return __uint_as_float(v << 16); }
__device__ __forceinline__ float bf_hi(uint32_t v) { return __uint_as_float(v & 0xFFFF0000u); }
__device__ __forceinline__ float bf_round(float v) { return bf_lo(pack_bf16(v, 0.f)); }
__device__ __forceinline__ float ex2(float v) { float r; asm("ex2.approx.ftz.f32 %0, %1;" : "=f"(r) : "f"(v)); return r; }
__device__ __forceinline__ float rsq(float v) { float r; asm("rsqrt.approx.ftz.f32 %0, %1;" : "=f"(r) : "f"(v)); return r; }
__device__ __forceinline__ float rcp(float v) { float r; asm("rcp.approx.ftz.f32 %0, %1;" : "=f"(r) : "f"(v)); return r; }
__device__ __forceinline__ void st_rec16(uint4* p, uint32_t a, uint32_t b, uint32_t c, uint32_t d) {
  asm volatile("{\n.reg .b128 r;\n.reg .b64 lo, hi;\nmov.b64 lo, {%1, %2};\nmov.b64 hi, {%3, %4};\nmov.b128 r, {lo, hi};\nst.relaxed.gpu.global.b128 [%0], r;\n}\n"
    :: "l"(p), "r"(a), "r"(b), "r"(c), "r"(d) : "memory");
}
__device__ __forceinline__ uint4 ld_rec16(const uint4* p) {
  uint4 v;
  asm volatile("{\n.reg .b128 r;\n.reg .b64 lo, hi;\nld.relaxed.gpu.global.b128 r, [%4];\nmov.b128 {lo, hi}, r;\nmov.b64 {%0, %1}, lo;\nmov.b64 {%2, %3}, hi;\n}\n"
    : "=r"(v.x), "=r"(v.y), "=r"(v.z), "=r"(v.w) : "l"(p) : "memory");
  return v;
}
__device__ __forceinline__ void ld_rec16_stale(uint4& v, const uint4* p, uint32_t tag) {
  asm volatile("{\n.reg .pred p;\n.reg .b128 r;\n.reg .b64 lo, hi;\nmov.b64 lo, {%0, %1};\nmov.b64 hi, {%2, %3};\nmov.b128 r, {lo, hi};\nsetp.ne.u32 p, %3, %5;\n"
    "@p ld.relaxed.gpu.global.b128 r, [%4];\nmov.b128 {lo, hi}, r;\nmov.b64 {%0, %1}, lo;\nmov.b64 {%2, %3}, hi;\n}\n"
    : "+r"(v.x), "+r"(v.y), "+r"(v.z), "+r"(v.w) : "l"(p), "r"(tag) : "memory");
}
__device__ __forceinline__ void st_rec8(uint2* p, uint32_t a, uint32_t b) {
  asm volatile("{\n.reg .b64 r;\nmov.b64 r, {%1, %2};\nst.relaxed.gpu.global.b64 [%0], r;\n}\n" :: "l"(p), "r"(a), "r"(b) : "memory");
}
__device__ __forceinline__ uint2 ld_rec8(const uint2* p) {
  uint2 v;
  asm volatile("{\n.reg .b64 r;\nld.relaxed.gpu.global.b64 r, [%2];\nmov.b64 {%0, %1}, r;\n}\n" : "=r"(v.x), "=r"(v.y) : "l"(p) : "memory");
  return v;
}
__device__ __forceinline__ unsigned ld_relaxed(const unsigned* p) { unsigned v; asm volatile("ld.relaxed.gpu.global.u32 %0, [%1];" : "=r"(v) : "l"(p) : "memory"); return v; }
__device__ __forceinline__ uint4 ldg_nc16(const void* p) {
  uint4 v; asm volatile("ld.global.nc.L1::no_allocate.v4.u32 {%0, %1, %2, %3}, [%4];" : "=r"(v.x), "=r"(v.y), "=r"(v.z), "=r"(v.w) : "l"(p)); return v;
}
__device__ __forceinline__ void stg16(void* p, uint4 v) { asm volatile("st.global.v4.u32 [%0], {%1, %2, %3, %4};" :: "l"(p), "r"(v.x), "r"(v.y), "r"(v.z), "r"(v.w) : "memory"); }
__device__ __forceinline__ float2 lds_f2(uint32_t a) { float2 v; asm volatile("ld.shared.v2.f32 {%0, %1}, [%2];" : "=f"(v.x), "=f"(v.y) : "r"(a)); return v; }
__device__ __forceinline__ float lds_f(uint32_t a) { float v; asm volatile("ld.shared.f32 %0, [%1];" : "=f"(v) : "r"(a)); return v; }
__device__ __forceinline__ uint32_t lds_u(uint32_t a) { uint32_t v; asm volatile("ld.shared.u32 %0, [%1];" : "=r"(v) : "r"(a)); return v; }
__device__ __forceinline__ uint4 lds_u4(uint32_t a) { uint4 v; asm volatile("ld.shared.v4.u32 {%0, %1, %2, %3}, [%4];" : "=r"(v.x), "=r"(v.y), "=r"(v.z), "=r"(v.w) : "r"(a)); return v; }
__device__ __forceinline__ void sts_f(uint32_t a, float v) { asm volatile("st.shared.f32 [%0], %1;" :: "r"(a), "f"(v) : "memory"); }
__device__ __forceinline__ void sts_f2(uint32_t a, float x, float y) { asm volatile("st.shared.v2.f32 [%0], {%1, %2};" :: "r"(a), "f"(x), "f"(y) : "memory"); }
__device__ __forceinline__ void sts_u2(uint32_t a, uint32_t x, uint32_t y) { asm volatile("st.shared.v2.u32 [%0], {%1, %2};" :: "r"(a), "r"(x), "r"(y) : "memory"); }
__device__ __forceinline__ void sts_u4(uint32_t a, uint32_t x, uint32_t y, uint32_t z, uint32_t w) { asm volatile("st.shared.v4.u32 [%0], {%1, %2, %3, %4};" :: "r"(a), "r"(x), "r"(y), "r"(z), "r"(w) : "memory"); }
__device__ __forceinline__ void sts_h(uint32_t a, uint32_t v) { asm volatile("st.shared.u16 [%0], %1;" :: "r"(a), "h"((uint16_t)v) : "memory"); }
__device__ __forceinline__ void sts_u(uint32_t a, uint32_t v) { asm volatile("st.shared.u32 [%0], %1;" :: "r"(a), "r"(v) : "memory"); }

template <int TA, int TB>
__device__ __forceinline__ void wg_n128(float (&d)[64], uint64_t da, uint64_t db, int sd) {
  asm volatile("{\n.reg .pred p;\nsetp.ne.b32 p, %66, 0;\n"
    "wgmma.mma_async.sync.aligned.m64n128k16.f32.bf16.bf16 {%0, %1, %2, %3, %4, %5, %6, %7, %8, %9, %10, %11, %12, %13, %14, %15, %16, %17, %18, %19, %20, %21, %22, %23, %24, %25, %26, %27, %28, %29, %30, %31, %32, %33, %34, %35, %36, %37, %38, %39, %40, %41, %42, %43, %44, %45, %46, %47, %48, %49, %50, %51, %52, %53, %54, %55, %56, %57, %58, %59, %60, %61, %62, %63}, %64, %65, p, 1, 1, %67, %68;\n}\n"
    : "+f"(d[0]), "+f"(d[1]), "+f"(d[2]), "+f"(d[3]), "+f"(d[4]), "+f"(d[5]), "+f"(d[6]), "+f"(d[7]), "+f"(d[8]), "+f"(d[9]), "+f"(d[10]), "+f"(d[11]), "+f"(d[12]), "+f"(d[13]), "+f"(d[14]), "+f"(d[15]), "+f"(d[16]), "+f"(d[17]), "+f"(d[18]), "+f"(d[19]), "+f"(d[20]), "+f"(d[21]), "+f"(d[22]), "+f"(d[23]), "+f"(d[24]), "+f"(d[25]), "+f"(d[26]), "+f"(d[27]), "+f"(d[28]), "+f"(d[29]), "+f"(d[30]), "+f"(d[31]), "+f"(d[32]), "+f"(d[33]), "+f"(d[34]), "+f"(d[35]), "+f"(d[36]), "+f"(d[37]), "+f"(d[38]), "+f"(d[39]), "+f"(d[40]), "+f"(d[41]), "+f"(d[42]), "+f"(d[43]), "+f"(d[44]), "+f"(d[45]), "+f"(d[46]), "+f"(d[47]), "+f"(d[48]), "+f"(d[49]), "+f"(d[50]), "+f"(d[51]), "+f"(d[52]), "+f"(d[53]), "+f"(d[54]), "+f"(d[55]), "+f"(d[56]), "+f"(d[57]), "+f"(d[58]), "+f"(d[59]), "+f"(d[60]), "+f"(d[61]), "+f"(d[62]), "+f"(d[63])
    : "l"(da), "l"(db), "r"(sd), "n"(TA), "n"(TB));
}

template <int TA, int TB, int O>
__device__ __forceinline__ void wg_n64(float (&d)[64], uint64_t da, uint64_t db, int sd) {
  asm volatile("{\n.reg .pred p;\nsetp.ne.b32 p, %34, 0;\n"
    "wgmma.mma_async.sync.aligned.m64n64k16.f32.bf16.bf16 {%0, %1, %2, %3, %4, %5, %6, %7, %8, %9, %10, %11, %12, %13, %14, %15, %16, %17, %18, %19, %20, %21, %22, %23, %24, %25, %26, %27, %28, %29, %30, %31}, %32, %33, p, 1, 1, %35, %36;\n}\n"
    : "+f"(d[O + 0]), "+f"(d[O + 1]), "+f"(d[O + 2]), "+f"(d[O + 3]), "+f"(d[O + 4]), "+f"(d[O + 5]), "+f"(d[O + 6]), "+f"(d[O + 7]), "+f"(d[O + 8]), "+f"(d[O + 9]), "+f"(d[O + 10]), "+f"(d[O + 11]), "+f"(d[O + 12]), "+f"(d[O + 13]), "+f"(d[O + 14]), "+f"(d[O + 15]), "+f"(d[O + 16]), "+f"(d[O + 17]), "+f"(d[O + 18]), "+f"(d[O + 19]), "+f"(d[O + 20]), "+f"(d[O + 21]), "+f"(d[O + 22]), "+f"(d[O + 23]), "+f"(d[O + 24]), "+f"(d[O + 25]), "+f"(d[O + 26]), "+f"(d[O + 27]), "+f"(d[O + 28]), "+f"(d[O + 29]), "+f"(d[O + 30]), "+f"(d[O + 31])
    : "l"(da), "l"(db), "r"(sd), "n"(TA), "n"(TB));
}

template <int TA, int TB>
__device__ __forceinline__ void wg_n40(float (&d)[20], uint64_t da, uint64_t db, int sd) {
  asm volatile("{\n.reg .pred p;\nsetp.ne.b32 p, %22, 0;\n"
    "wgmma.mma_async.sync.aligned.m64n40k16.f32.bf16.bf16 {%0, %1, %2, %3, %4, %5, %6, %7, %8, %9, %10, %11, %12, %13, %14, %15, %16, %17, %18, %19}, %20, %21, p, 1, 1, %23, %24;\n}\n"
    : "+f"(d[0]), "+f"(d[1]), "+f"(d[2]), "+f"(d[3]), "+f"(d[4]), "+f"(d[5]), "+f"(d[6]), "+f"(d[7]), "+f"(d[8]), "+f"(d[9]), "+f"(d[10]), "+f"(d[11]), "+f"(d[12]), "+f"(d[13]), "+f"(d[14]), "+f"(d[15]), "+f"(d[16]), "+f"(d[17]), "+f"(d[18]), "+f"(d[19])
    : "l"(da), "l"(db), "r"(sd), "n"(TA), "n"(TB));
}

template <int TA, int TB>
__device__ __forceinline__ void wg_n32(float (&d)[16], uint64_t da, uint64_t db, int sd) {
  asm volatile("{\n.reg .pred p;\nsetp.ne.b32 p, %18, 0;\n"
    "wgmma.mma_async.sync.aligned.m64n32k16.f32.bf16.bf16 {%0, %1, %2, %3, %4, %5, %6, %7, %8, %9, %10, %11, %12, %13, %14, %15}, %16, %17, p, 1, 1, %19, %20;\n}\n"
    : "+f"(d[0]), "+f"(d[1]), "+f"(d[2]), "+f"(d[3]), "+f"(d[4]), "+f"(d[5]), "+f"(d[6]), "+f"(d[7]), "+f"(d[8]), "+f"(d[9]), "+f"(d[10]), "+f"(d[11]), "+f"(d[12]), "+f"(d[13]), "+f"(d[14]), "+f"(d[15])
    : "l"(da), "l"(db), "r"(sd), "n"(TA), "n"(TB));
}

template <int TB>
__device__ __forceinline__ void wg_n40_rs(float (&d)[20], uint32_t a0, uint32_t a1, uint32_t a2, uint32_t a3, uint64_t db, int sd) {
  asm volatile("{\n.reg .pred p;\nsetp.ne.b32 p, %25, 0;\n"
    "wgmma.mma_async.sync.aligned.m64n40k16.f32.bf16.bf16 {%0, %1, %2, %3, %4, %5, %6, %7, %8, %9, %10, %11, %12, %13, %14, %15, %16, %17, %18, %19}, {%20, %21, %22, %23}, %24, p, 1, 1, %26;\n}\n"
    : "+f"(d[0]), "+f"(d[1]), "+f"(d[2]), "+f"(d[3]), "+f"(d[4]), "+f"(d[5]), "+f"(d[6]), "+f"(d[7]), "+f"(d[8]), "+f"(d[9]), "+f"(d[10]), "+f"(d[11]), "+f"(d[12]), "+f"(d[13]), "+f"(d[14]), "+f"(d[15]), "+f"(d[16]), "+f"(d[17]), "+f"(d[18]), "+f"(d[19])
    : "r"(a0), "r"(a1), "r"(a2), "r"(a3), "l"(db), "r"(sd), "n"(TB));
}

template <int TB>
__device__ __forceinline__ void wg_n32_rs(float (&d)[16], uint32_t a0, uint32_t a1, uint32_t a2, uint32_t a3, uint64_t db, int sd) {
  asm volatile("{\n.reg .pred p;\nsetp.ne.b32 p, %21, 0;\n"
    "wgmma.mma_async.sync.aligned.m64n32k16.f32.bf16.bf16 {%0, %1, %2, %3, %4, %5, %6, %7, %8, %9, %10, %11, %12, %13, %14, %15}, {%16, %17, %18, %19}, %20, p, 1, 1, %22;\n}\n"
    : "+f"(d[0]), "+f"(d[1]), "+f"(d[2]), "+f"(d[3]), "+f"(d[4]), "+f"(d[5]), "+f"(d[6]), "+f"(d[7]), "+f"(d[8]), "+f"(d[9]), "+f"(d[10]), "+f"(d[11]), "+f"(d[12]), "+f"(d[13]), "+f"(d[14]), "+f"(d[15])
    : "r"(a0), "r"(a1), "r"(a2), "r"(a3), "l"(db), "r"(sd), "n"(TB));
}

template <int TB>
__device__ __forceinline__ void wg_n8_rs(float (&d)[4], uint32_t a0, uint32_t a1, uint32_t a2, uint32_t a3, uint64_t db, int sd) {
  asm volatile("{\n.reg .pred p;\nsetp.ne.b32 p, %9, 0;\n"
    "wgmma.mma_async.sync.aligned.m64n8k16.f32.bf16.bf16 {%0, %1, %2, %3}, {%4, %5, %6, %7}, %8, p, 1, 1, %10;\n}\n"
    : "+f"(d[0]), "+f"(d[1]), "+f"(d[2]), "+f"(d[3])
    : "r"(a0), "r"(a1), "r"(a2), "r"(a3), "l"(db), "r"(sd), "n"(TB));
}

template <int TB>
__device__ __forceinline__ void wg_n128_rs(float (&d)[64], uint32_t a0, uint32_t a1, uint32_t a2, uint32_t a3, uint64_t db, int sd) {
  asm volatile("{\n.reg .pred p;\nsetp.ne.b32 p, %69, 0;\n"
    "wgmma.mma_async.sync.aligned.m64n128k16.f32.bf16.bf16 {%0, %1, %2, %3, %4, %5, %6, %7, %8, %9, %10, %11, %12, %13, %14, %15, %16, %17, %18, %19, %20, %21, %22, %23, %24, %25, %26, %27, %28, %29, %30, %31, %32, %33, %34, %35, %36, %37, %38, %39, %40, %41, %42, %43, %44, %45, %46, %47, %48, %49, %50, %51, %52, %53, %54, %55, %56, %57, %58, %59, %60, %61, %62, %63}, {%64, %65, %66, %67}, %68, p, 1, 1, %70;\n}\n"
    : "+f"(d[0]), "+f"(d[1]), "+f"(d[2]), "+f"(d[3]), "+f"(d[4]), "+f"(d[5]), "+f"(d[6]), "+f"(d[7]), "+f"(d[8]), "+f"(d[9]), "+f"(d[10]), "+f"(d[11]), "+f"(d[12]), "+f"(d[13]), "+f"(d[14]), "+f"(d[15]), "+f"(d[16]), "+f"(d[17]), "+f"(d[18]), "+f"(d[19]), "+f"(d[20]), "+f"(d[21]), "+f"(d[22]), "+f"(d[23]), "+f"(d[24]), "+f"(d[25]), "+f"(d[26]), "+f"(d[27]), "+f"(d[28]), "+f"(d[29]), "+f"(d[30]), "+f"(d[31]), "+f"(d[32]), "+f"(d[33]), "+f"(d[34]), "+f"(d[35]), "+f"(d[36]), "+f"(d[37]), "+f"(d[38]), "+f"(d[39]), "+f"(d[40]), "+f"(d[41]), "+f"(d[42]), "+f"(d[43]), "+f"(d[44]), "+f"(d[45]), "+f"(d[46]), "+f"(d[47]), "+f"(d[48]), "+f"(d[49]), "+f"(d[50]), "+f"(d[51]), "+f"(d[52]), "+f"(d[53]), "+f"(d[54]), "+f"(d[55]), "+f"(d[56]), "+f"(d[57]), "+f"(d[58]), "+f"(d[59]), "+f"(d[60]), "+f"(d[61]), "+f"(d[62]), "+f"(d[63])
    : "r"(a0), "r"(a1), "r"(a2), "r"(a3), "l"(db), "r"(sd), "n"(TB));
}


template <int N>
__device__ __forceinline__ void feature_shifted(const float (&p)[16], const float (&p2)[16], float sc0, float sc1, uint32_t (&o)[N]) {
  __align__(16) float t[N];
  __align__(16) uint32_t w[N];
#pragma unroll
  for (int i = 0; i < N; i++) t[i] = i < 16 ? p[i] : p2[i & 15];
#pragma unroll 1
  for (int it = 0; it < N / 4; it++) {
    const float* x = t + (it >> 2) * 16 + (it & 1) * 2;
    const int h = (it >> 1) & 1;
    const float sg = h ? -1.f : 1.f, sc = (it & 1) ? sc1 : sc0;
    float mx = sg * x[0], s = 0.f;
#pragma unroll 1
    for (int j = 0; j < 16; j += 4) mx = fmaxf(mx, fmaxf(sg * x[j], sg * x[j + 1]));
    mx = fmaxf(mx, __shfl_xor_sync(0xffffffffu, mx, 1));
    mx = fmaxf(mx, __shfl_xor_sync(0xffffffffu, mx, 2));
#pragma unroll 1
    for (int j = 0; j < 32; j += 4) {
      const float a = ex2((sg * x[(j & 15) + h] - mx) * sc), c = ex2((sg * x[(j & 15) + 1 - h] - mx) * sc);
      if (j < 16) s += a + c;
      else w[(it >> 1) * 8 + (j >> 1) - 8 + (it & 1)] = pack_bf16(a * s, c * s);
      if (j == 12) {
        s += __shfl_xor_sync(0xffffffffu, s, 1);
        s += __shfl_xor_sync(0xffffffffu, s, 2);
        s = rcp(s);
      }
    }
  }
#pragma unroll
  for (int i = 0; i < N; i++) o[i] = w[i];
}
constexpr float FAST_LIMIT = RCPG == 2 ? 0x1p60f : RCPG == 4 ? 0x1p30f : 0x1p15f;
__device__ __forceinline__ void feature_exp(const float* p, float sc0, float sc1, uint32_t* o, float (&d)[4], uint64_t sel) {
  float e[16], r[8];
#pragma unroll
  for (int i = 0; i < 16; i++) e[i] = ex2(p[i] * ((i & 2) ? sc1 : sc0));
#pragma unroll
  for (int i = 0; i < 8; i++) r[i] = e[2 * i] * e[2 * i + 1];
#pragma unroll
  for (int i = 0; i < 8; i++) o[i] = pack_bf16(e[2 * i], e[2 * i + 1]);
  uint32_t a[4];
#pragma unroll
  for (int i = 0; i < 2; i++) {
    if (RCPG == 2) {
      o[8 + i] = pack_bf16(rcp(r[i]), rcp(r[2 + i]));
      o[10 + i] = pack_bf16(rcp(r[4 + i]), rcp(r[6 + i]));
    } else {
      float u = r[i] * r[2 + i], w = r[4 + i] * r[6 + i];
      if (RCPG == 4) { u = rcp(u); w = rcp(w); }
      else { const float z = rcp(u * w), y = z * u; u = z * w; w = y; }
      o[8 + i] = pack_bf16(u * r[2 + i], u * r[i]);
      o[10 + i] = pack_bf16(w * r[6 + i], w * r[4 + i]);
    }
    a[i] = hadd2(hadd2(o[i], o[2 + i]), hadd2(o[4 + i], o[6 + i]));
    a[2 + i] = hfma2<1>(o[6 + i], o[10 + i], hfma2<0>(o[4 + i], o[10 + i], hfma2<1>(o[2 + i], o[8 + i], hmul2<0>(o[i], o[8 + i]))));
  }
  wg_fence();
  wg_n8_rs<0>(d, a[0], a[1], a[2], a[3], sel, 0);
  wg_commit();
}
template <bool FULL>
__device__ __forceinline__ float feature_norm(uint32_t* o, const float (&d)[4]) {
  uint32_t c[4];
  if (FULL) {
#pragma unroll
    for (int i = 0; i < 2; i++) {
      const float z = rcp(d[2 * i] * d[2 * i + 1]);
      const uint32_t n = pack_bf16(z * d[2 * i + 1], z * d[2 * i]);
      c[i] = hmul2<1>(o[8 + i], n); c[2 + i] = hmul2<1>(o[10 + i], n);
#pragma unroll
      for (int j = i; j < 8; j += 2) {
        o[8 + j] = (j & 2) ? hmul2<1>(o[j], c[(j >> 2) * 2 + i]) : hmul2<0>(o[j], c[(j >> 2) * 2 + i]);
        o[j] = hmul2<0>(o[j], n);
      }
    }
  } else {
    const uint32_t n = pack_bf16(d[0] * rcp(d[1]), d[2] * rcp(d[3]));
    c[0] = hmul2<0>(o[8], n); c[1] = hmul2<1>(o[9], n); c[2] = hmul2<0>(o[10], n); c[3] = hmul2<1>(o[11], n);
#pragma unroll
    for (int j = 0; j < 8; j++) o[8 + j] = (j & 2) ? hmul2<1>(o[j], c[(j >> 2) * 2 + (j & 1)]) : hmul2<0>(o[j], c[(j >> 2) * 2 + (j & 1)]);
  }
  return (d[0] + d[1]) + (d[2] + d[3]);
}
__device__ __forceinline__ float feature_norm32(const float (&e)[16], const float (&r)[8], const float (&d)[4], uint32_t* o) {
#pragma unroll
  for (int i = 0; i < 2; i++) {
    const float z = rcp(d[2 * i] * d[2 * i + 1]), np = z * d[2 * i + 1], nm = z * d[2 * i];
    if (KH2) {
      const float q = nm * d[2 * i];
      const uint32_t c0 = pack_bf16(r[i] * q, r[2 + i] * q), c1 = pack_bf16(r[4 + i] * q, r[6 + i] * q);
#pragma unroll
      for (int j = i; j < 8; j += 2) {
        o[j] = pack_bf16(e[2 * j] * np, e[2 * j + 1] * np);
        o[8 + j] = (j & 2) ? hmul2<1>(o[j], (j & 4) ? c1 : c0) : hmul2<0>(o[j], (j & 4) ? c1 : c0);
      }
    } else {
#pragma unroll
      for (int j = i; j < 8; j += 2) {
        const float c = r[j] * nm;
        o[j] = pack_bf16(e[2 * j] * np, e[2 * j + 1] * np);
        o[8 + j] = pack_bf16(e[2 * j] * c, e[2 * j + 1] * c);
      }
    }
  }
  return (d[0] + d[1]) + (d[2] + d[3]);
}
template <class H>
__device__ __forceinline__ float feature_fast(const float* p, float sc0, float sc1, uint32_t* o, H hook) {
  float e[16], r[8], sp[2] = {0.f, 0.f}, sm[2] = {0.f, 0.f};
#pragma unroll
  for (int i = 0; i < 16; i++) e[i] = ex2(p[i] * ((i & 2) ? sc1 : sc0));
#pragma unroll
  for (int i = 0; i < 8; i++) r[i] = e[2 * i] * e[2 * i + 1];
#pragma unroll
  for (int i = 0; i < 2; i++) {
    float u = r[i] * r[2 + i], w = r[4 + i] * r[6 + i];
    if (RCPG == 4) { u = rcp(u); w = rcp(w); }
    else { const float z = rcp(u * w), y = z * u; u = z * w; w = y; }
    const float c = u * r[i], d = w * r[4 + i];
    r[i] = u * r[2 + i]; r[2 + i] = c; r[4 + i] = w * r[6 + i]; r[6 + i] = d;
  }
#pragma unroll
  for (int i = 0; i < 8; i++) {
    const float t = e[2 * i] + e[2 * i + 1];
    sp[i & 1] += t; sm[i & 1] = fmaf(t, r[i], sm[i & 1]);
  }
  const float tot = (sp[0] + sp[1]) + (sm[0] + sm[1]);
  if (KSH == 1) {
#pragma unroll
    for (int i = 0; i < 2; i++) {
      uint32_t v = pack_bf16(sp[i], sm[i]);
      v = hadd2(v, __shfl_xor_sync(0xffffffffu, v, 1));
      const uint32_t w = __shfl_xor_sync(0xffffffffu, v, 2);
      sp[i] = bf_lo(v) + bf_lo(w); sm[i] = bf_hi(v) + bf_hi(w);
    }
  } else {
#pragma unroll
    for (int m = 1; m <= 2; m <<= 1)
#pragma unroll
      for (int i = 0; i < 2; i++) { sp[i] += __shfl_xor_sync(0xffffffffu, sp[i], m); sm[i] += __shfl_xor_sync(0xffffffffu, sm[i], m); }
  }
  hook();
  const float d[4] = {sp[0], sm[0], sp[1], sm[1]};
  feature_norm32(e, r, d, o);
  return tot;
}
__device__ __forceinline__ bool warp_fails(bool ok) { return __builtin_expect(!__all_sync(0xffffffffu, ok), 0); }
constexpr uint32_t OTAG = 0x00010001u;
__device__ __forceinline__ void attn_out(const float (&u)[20], uint32_t tg, uint32_t* r, uint4* dst, bool pub) {
  const float d0 = rcp(fmaf(u[17], 0.5e-6f, u[16])), d1 = rcp(fmaf(u[19], 0.5e-6f, u[18]));
#pragma unroll
  for (int j = 0; j < 8; j++) r[j] = pack_bf16(u[2 * j] * ((j & 1) ? d1 : d0), u[2 * j + 1] * ((j & 1) ? d1 : d0));
  r[0] = (r[0] & ~OTAG) | tg; r[4] = (r[4] & ~OTAG) | tg;
  if (pub) {
    st_rec16(dst, r[0], r[1], r[2], r[3]);
    st_rec16(dst + 32, r[4], r[5], r[6], r[7]);
  }
}

constexpr float L2E = 1.4426950408889634f;

__device__ __forceinline__ int pc_chunk(int j, int cb) {
  const int c = j > 8, e = j - 2 - 7 * c;
  return j < 2 ? 2 * cb + j : 2 * (e == cb ? 7 : e) + c;
}
constexpr unsigned long long Q_ASLOTS = 0x9763097630976309ull, Q_BSLOTS = 0x1854218542185421ull;
constexpr unsigned long long Q_CHUNKS = 0xBA9876543210EDCFull;
constexpr unsigned long long PC_ASLOTS = 0xBA20BA20BA20BA20ull, PC_BSLOTS = 0x3765437654376543ull;
constexpr unsigned long long FFN_SLOTS = 0xBA9854C11987ull;
constexpr unsigned long long FFN_ORDER = 0xBA7654983210ull;
constexpr unsigned long long FFN_WAIT0 = 0x7C4B4A493F3F3E3Eull, FFN_WAIT1 = 0x6E6D6C6Bull;
constexpr unsigned long long FFN_PACE0 = 0x6A69989392627F44ull, FFN_PACE1 = 0x97969594ull;
constexpr unsigned long long WO_WAIT0 = 0x626160483D3D3C3Cull, WO_WAIT1 = 0x6A69686766656463ull;
constexpr unsigned long long WO_PACE0 = 0x527F502Full, WO_PACE1 = 0x0ull;
constexpr int X_PACE = 81;
__device__ __forceinline__ uint32_t tab4(unsigned long long t, int i) { return (uint32_t)(t >> (4 * i)) & 15u; }
__device__ __forceinline__ uint32_t tab8(unsigned long long lo, unsigned long long hi, int i) { return (uint32_t)((i < 8 ? lo : hi) >> (8 * (i & 7))) & 255u; }

__device__ __forceinline__ float sum8(uint4 v) {
  return ((bf_lo(v.x) + bf_hi(v.x)) + (bf_lo(v.y) + bf_hi(v.y))) + ((bf_lo(v.z) + bf_hi(v.z)) + (bf_lo(v.w) + bf_hi(v.w)));
}
__device__ __forceinline__ float warp_sum(float s) {
#pragma unroll
  for (int m = 16; m >= 1; m >>= 1) s += __shfl_xor_sync(0xffffffffu, s, m);
  return s;
}
__device__ __forceinline__ uint32_t ln_res(uint32_t h, float a, float c, uint32_t& n) {
  const float l = bf_lo(h), u = bf_hi(h);
  n = pack_bf16(fmaf(l, a, c), fmaf(u, a, c));
  return pack_bf16(l + bf_lo(n), u + bf_hi(n));
}

__device__ __forceinline__ uint64_t ext_a(uint32_t sb, uint32_t row) { return mk_desc(sb + 12 * SLOT + 4096 + row * 16, 4096 - row * 16, 128, 0); }
__device__ __forceinline__ uint64_t ext_b(uint32_t sb, uint32_t part) { return mk_desc(sb + 12 * SLOT + part * 2048, 1024, 0, 1); }
__device__ __forceinline__ uint64_t sum_b(uint32_t sb) { return mk_desc(sb + OFF_SEL, 16, 128, 0); }
__device__ __forceinline__ uint32_t split_bf16(float v) { return pack_bf16(v, v - bf_round(v)); }

template <int N> __device__ __forceinline__ void padn() { if constexpr (N > 1) { padn<N / 2>(); padn<N - N / 2>(); } else if constexpr (N == 1) asm volatile("nanosleep.u32 1;"); }
__global__ void __launch_bounds__(NTHREADS, 1) fused_kernel(const __grid_constant__ Params P) {
  extern __shared__ __align__(1024) uint8_t smem_raw[];
  const uint32_t sb = smem_u32(smem_raw);
  const uint32_t bars = sb + OFF_BAR;
  const int tid = threadIdx.x;
  const int wg = __shfl_sync(0xffffffffu, tid >> 7, 0);
  const int warp = __shfl_sync(0xffffffffu, (tid >> 5) & 3, 0);
  const int lane = tid & 31;
  const int b = (blockIdx.x & 1) * 64 + (blockIdx.x >> 1);
  const bool ffn = (blockIdx.x & 7) != 7;
  const int fi = blockIdx.x - (blockIdx.x >> 3);
  const int rbk = b >> 4, hp = b & 15;
  const int rb = b >> 3, cb = b & 7;
#define BAR(i) (bars + 8u * (uint32_t)(i))
#define MMA_IDS \
    const int tid = fresh_tid(), lane = tid & 31; \
    const bool leader = (tid & 127) == 0; \
    const uint32_t srow = (uint32_t)(warp * 16 + (lane & 7) + ((lane >> 3) & 1) * 8); \
    const uint32_t sx = (uint32_t)(lane >> 4) ^ (srow & 7); \
    const int c2 = (lane & 3) * 2, lr = warp * 16 + (lane >> 2); \
    (void)leader; (void)sx; (void)c2; (void)lr;

  auto load_kv = [&](int it) {
    const uint32_t s = sb + (uint32_t)(it & 3) * 3 * SLOT, fb = BAR(B_FKV + it);
    mbar_expect_tx(fb, 3 * SLOT);
    tma_load_2d(s, &P.mX, fb, it * 64, rb * 128);
    tma_load_2d(s + SLOT, &P.mX, fb, it * 64, (rb ^ 1) * 128);
    tma_load_2d(s + 2 * SLOT, &P.mW, fb, 1024 + hp * 64, it * 64);
    tma_load_2d(s + 2 * SLOT + 8192, &P.mW, fb, 2048 + hp * 64, it * 64);
  };
  auto prefetch = [&](int c) {
    if (c < 2) { l2_prefetch(P.wo + b * 8192 + c * 4096, 8192); return; }
    if (!ffn) return;
    const int e = c - 2;
    if (e < 16) {
      asm volatile("cp.async.bulk.prefetch.tensor.2d.L2.global.tile [%0, {%1, %2}];"
                   :: "l"((e & 1) ? &P.mWuP : &P.mWgP), "r"((fi >> 1) * 64), "r"((e >> 1) * 128 + (fi & 1) * 64) : "memory");
    } else {
      l2_prefetch(P.wd + (size_t)fi * 32768 + (e - 16) * 4096, 8192);
    }
  };

  {
    const int w16 = wg * 4 + warp;
    const uint32_t cnt = w16 == 14 ? 128u : ((0x300Cu >> w16) & 1u) + 1u;
    if (elect()) {
      if (w16 == 11) {
#pragma unroll
        for (int i = 0; i < 4; i++) mbar_init(BAR(B_FKV + i), 1u);
        asm volatile("fence.mbarrier_init.release.cluster;" ::: "memory");
        load_kv(0);
      }
#pragma unroll
      for (int i = 0; i < 8; i++)
        if (w16 || i >= 4) mbar_init(BAR(w16 * 8 + i), w16 == 15 ? (uint32_t)(MISC_COUNTS >> (8 * i)) & 255u : cnt);
      mbar_init(BAR(B_FS + w16), w16 >= 14 ? 2u : 1u);
      mbar_init(BAR(B_FW + w16), 1u);
      asm volatile("fence.mbarrier_init.release.cluster;" ::: "memory");
    }
    __syncwarp();
    if (w16 == 11 && elect()) {
#pragma unroll 1
      for (int i = 1; i < 4; i++) load_kv(i);
    }
    __syncwarp();
  }

  if (wg >= 2) {
    if (wg == 3) {
      asm volatile("setmaxnreg.dec.sync.aligned.u32 64;");
      asm volatile("barrier.sync 0;" ::: "memory");
        if (warp) {
          const int q = 3 * b + warp - 1, cg = q % 96, kq = q / 96;
          const uint32_t buf = sb + (warp == 3 ? OFF_PHIQ : 12 * SLOT + (warp - 1) * 8192);
          const uint32_t fb = BAR(B_FS + (warp - 1) * 4);
          mbar_wait(BAR(B_FKV + ((CSW >> (4 * (kq + (cg < 32 ? 0 : 4)))) & 15)));
          if (elect()) {
#pragma unroll
            for (int p = 0; p < 2; p++) { mbar_expect_tx(fb + p * 8, 4096); tma_load_2d(buf + p * 4096, &P.mWs, fb + p * 8, cg * 32, kq * 256 + p * 64); }
          }
          float cs[8];
#pragma unroll
          for (int i = 0; i < 8; i++) cs[i] = 0.f;
          const unsigned ep = ld_relaxed(&g_epoch);
#pragma unroll 1
          for (int p = 0; p < 4; p++) {
            mbar_wait(fb + p * 8);
            uint4 v[8];
#pragma unroll
            for (int i = 0; i < 8; i++) v[i] = lds_u4(buf + (p & 1) * 4096 + i * 512 + lane * 16);
            if (p < 2) {
              uint32_t dep = 0;
#pragma unroll
              for (int i = 0; i < 8; i++) dep ^= v[i].x;
              const int n = p + 2 + (int)__shfl_sync(0xffffffffu, zero_after(dep), 0);
              if (elect()) {
                mbar_expect_tx(fb + n * 8, 4096);
                tma_load_2d(buf + (n & 1) * 4096, &P.mWs, fb + n * 8, cg * 32, kq * 256 + n * 64);
              }
            }
#pragma unroll
            for (int i = 0; i < 8; i += 2) {
              cs[0] += bf_lo(v[i].x) + bf_lo(v[i + 1].x); cs[1] += bf_hi(v[i].x) + bf_hi(v[i + 1].x);
              cs[2] += bf_lo(v[i].y) + bf_lo(v[i + 1].y); cs[3] += bf_hi(v[i].y) + bf_hi(v[i + 1].y);
              cs[4] += bf_lo(v[i].z) + bf_lo(v[i + 1].z); cs[5] += bf_hi(v[i].z) + bf_hi(v[i + 1].z);
              cs[6] += bf_lo(v[i].w) + bf_lo(v[i + 1].w); cs[7] += bf_hi(v[i].w) + bf_hi(v[i + 1].w);
            }
          }
          {
            const bool u4 = lane & 16, u2 = lane & 8, u1 = lane & 4;
#pragma unroll
            for (int i = 0; i < 4; i++) cs[i] = (u4 ? cs[4 + i] : cs[i]) + __shfl_xor_sync(0xffffffffu, u4 ? cs[i] : cs[4 + i], 16);
#pragma unroll
            for (int i = 0; i < 2; i++) cs[i] = (u2 ? cs[2 + i] : cs[i]) + __shfl_xor_sync(0xffffffffu, u2 ? cs[i] : cs[2 + i], 8);
            cs[0] = (u1 ? cs[1] : cs[0]) + __shfl_xor_sync(0xffffffffu, u1 ? cs[0] : cs[1], 4);
          }
          if (warp == 3 && elect()) {
            mbar_expect_tx(BAR(B_PHI), 12288);
            tma_load_2d(sb + OFF_PHIK, &P.mPhi, BAR(B_PHI), 0, hp * 64);
            tma_load_2d(sb + OFF_PHIQ, &P.mPhi, BAR(B_PHI), (int)zero_after(__float_as_uint(cs[0])), cb * 128);
            tma_load_2d(sb + OFF_PHIQ + 4096, &P.mPhi, BAR(B_PHI), (int)zero_after(__float_as_uint(cs[0])), cb * 128 + 64);
          }
          st_rec8(&g_colsum[kq][cg * 32 + (lane & 3) * 8 + (lane >> 2)], __float_as_uint(cs[0]), ep + 1);
          if (lane == 0) mbar_arrive(BAR(B_CSD));
        }
      asm volatile("setmaxnreg.dec.sync.aligned.u32 32;");
      if (warp == 0) {
#pragma unroll 1
        for (int it = 4; it < 16; it++) {
          mbar_wait(BAR(B_DKV + it - 4));
          if (elect()) load_kv(it);
        }
#pragma unroll 1
        for (int it = 0; it < 16; it++) {
          const uint32_t fb = BAR(B_FQ + it), s = sb + tab4(Q_BSLOTS, it) * SLOT;
          const int kc = (int)tab4(Q_CHUNKS, it) * 64;
          if (it == 5) mbar_wait(BAR(B_DKV + 15));
          mbar_wait(it >= 5 ? BAR(B_DQ + it - 5) : BAR(B_DKV + 12 + (it >> 1)));
          if (elect()) {
            mbar_expect_tx(fb, it < 4 ? SLOT : 2 * SLOT);
            if (it >= 4) tma_load_2d(sb + tab4(Q_ASLOTS, it) * SLOT, &P.mX, fb, kc, rb * 128);
            tma_load_2d(s, &P.mW, fb, cb * 128, kc);
            tma_load_2d(s + 8192, &P.mW, fb, cb * 128 + 64, kc);
          }
        }
        mbar_wait(BAR(B_DQ + 11));
        mbar_wait(BAR(X_PACE));
        if (elect()) {
          mbar_expect_tx(BAR(B_FX), 2 * SLOT);
          tma_load_2d(sb, &P.mX, BAR(B_FX), cb * 128, rb * 128);
          tma_load_2d(sb + 2 * SLOT, &P.mX, BAR(B_FX), cb * 128 + 64, rb * 128);
        }
        mbar_wait(BAR(B_KVRDY));
        const unsigned tag = lds_u(sb + OFF_RED + 4);
        uint32_t seen = 0;
#pragma unroll 1
        for (int j = 2; j < 16; j++) {
          const int kc = pc_chunk(j, cb);
          const uint32_t need = j > 8 ? 0u : GATE ? 0xFFFFu : 3u << kc;
#pragma unroll 1
          for (int it = 0; it < SPIN && (seen & need) != need; it++) {
            seen = __ballot_sync(0xffffffffu, ld_relaxed(&g_oflag[rb][cb][lane & 15].x) == tag);
          }
          mbar_wait(BAR(j < 4 ? (QRD ? B_QREAD : B_XDONE) : j < 6 ? B_XREAD : B_DC + j - 5));
          if (elect()) {
            mbar_expect_tx(BAR(B_FKV + j), SLOT);
            asm volatile("cp.async.bulk.shared::cluster.global.mbarrier::complete_tx::bytes [%0], [%1], %2, [%3];"
              :: "r"(sb + tab4(PC_ASLOTS, j) * SLOT), "l"(&g_o[rb][kc][0][0][0]), "n"(SLOT), "r"(BAR(B_FKV + j)) : "memory");
          }
        }
      } else {
        if (warp == 1) {
#pragma unroll 1
          for (int j = 0; j < 16; j++) {
            const uint32_t s = sb + tab4(PC_BSLOTS, j) * SLOT, fb = BAR(B_FB + j);
            const int kc = pc_chunk(j, cb);
            mbar_wait(BAR(tab8(WO_WAIT0, WO_WAIT1, j)));
            mbar_wait(BAR(tab8(WO_PACE0, WO_PACE1, j)));
            if (elect()) {
              mbar_expect_tx(fb, SLOT);
              tma_load_2d(s, &P.mWo, fb, cb * 128, kc * 64);
              tma_load_2d(s + 8192, &P.mWo, fb, cb * 128 + 64, kc * 64);
            }
          }
        } else if (warp == 3) {
#pragma unroll 1
          for (int c = 0; c < 26; c++) {
            mbar_wait(BAR(c < 8 ? B_DKV + 8 + c : B_DQ + ((c - 8) >> 1)));
            if (elect()) prefetch(c);
          }
          __syncwarp();
          if (lane == 0) mbar_arrive(BAR(B_KVRDY));
          mbar_wait(BAR(B_DC + 10));
#pragma unroll 1
          for (int i = 0; i < 4; i++) st_rec16(&g_hstat[rb][cb][i * 32 + lane], 0u, 0u, 0u, 0u);
          st_rec16(reinterpret_cast<uint4*>(&g_candx[rb][cb * 64]) + lane, 0u, 0u, 0u, 0u);
          if (KREP) { if (lane < 16) st_rec8(&g_key[cb][lane][rb], 0u, 0u); }
          else if (lane < 2) st_rec16(reinterpret_cast<uint4*>(&g_key[cb][rb >> 2][(rb & 3) * 4]) + lane, 0u, 0u, 0u, 0u);
          __syncwarp();
          if (lane == 0) mbar_arrive(BAR(B_RESET2));
        } else {
          mbar_wait(BAR(B_DQ + RSTQ));
#pragma unroll 1
          for (int i = 0; i < 12; i++) {
            st_rec16(&g_kvp[2 * hp][rbk][0][i * 32 + lane], 0u, 0u, 0u, 0u);
            st_rec16(&g_kvp[2 * hp + 1][rbk][0][i * 32 + lane], 0u, 0u, 0u, 0u);
          }
#pragma unroll 1
          for (int i = 0; i < 3; i++) st_rec16(&g_kvr[2 * hp + (lane >> 4)][i][rbk * 16 + (lane & 15)], 0u, 0u, 0u, 0u);
          if (lane < 16) st_rec16(&g_oflag[rb][lane >> 1][cb * 2 + (lane & 1)], 0u, 0u, 0u, 0u);
          __syncwarp();
          if (lane == 0) mbar_arrive(BAR(B_RESET));
          if (ffn) {
#pragma unroll 1
            for (int n = 0; n < 12; n++) {
              const int i = (int)tab4(FFN_ORDER, n);
              const uint32_t s = sb + tab4(FFN_SLOTS, i) * SLOT, fb = BAR(B_FW + i);
              mbar_wait(BAR(tab8(FFN_WAIT0, FFN_WAIT1, n)));
              mbar_wait(BAR(tab8(FFN_PACE0, FFN_PACE1, n)));
              if (elect()) {
                mbar_expect_tx(fb, SLOT);
              }
              const CUtensorMap* mp = i >= 8 ? &P.mWd : (i & 1) ? &P.mWu : &P.mWg;
#pragma unroll 1
              for (int e = 0; e < 4; e++) {
                const int c = (i < 8 ? i >> 1 : i - 8) * 256 + e * 64;
                if (elect()) tma_load_2d_ef(s + e * 4096, mp, fb, i < 8 ? fi * 32 : c, i < 8 ? c : fi * 32);
              }
            }
          }
        }
      }
    } else {
      asm volatile("barrier.sync 0;" ::: "memory");
      const int t = tid - 256;
      const unsigned tag = ld_relaxed(&g_epoch) + 1;
      if (warp == 0) {
        float s = 0.f;
#pragma unroll
        for (int i = 0; i < 4; i++) s += sum8(ldg_nc16(P.wr + i * 256 + lane * 8));
        const uint2 w = *reinterpret_cast<const uint2*>(P.wr + cb * 128 + lane * 4);
        s = warp_sum(s);
        if (lane == 0) { sts_f(sb + OFF_RED, s); sts_u(sb + OFF_RED + 4, tag); }
        sts_f2(sb + OFF_WR + lane * 16, bf_lo(w.x), bf_hi(w.x));
        sts_f2(sb + OFF_WR + lane * 16 + 8, bf_lo(w.y), bf_hi(w.y));
      }
      __syncwarp();
      {
        const __nv_bfloat16* xp = P.x + (size_t)(b * 16 + warp * 4 + (lane >> 3)) * DM + (lane & 7) * 8;
        float sh = 0.f, s0 = 0.f, q0 = 0.f, s1 = 0.f, q1 = 0.f;
        uint32_t ns = 0;
#pragma unroll 1
        for (int g = 0; g < 16 / SXN; g++) {
          uint4 xv[SXN];
          mbar_wait(BAR(B_FKV + SX0 + g * SXD));
#pragma unroll
          for (int i = 0; i < SXN; i++) xv[i] = ldg_nc16(xp + (g * SXN + i) * 64);
          if (g == 0) {
            sh = __shfl_sync(0xffffffffu, bf_lo(xv[0].x), lane & 24);
            ns = pack_bf16(-sh, -sh);
          }
#pragma unroll
          for (int i = 0; i < SXN; i++) {
              const uint32_t a = hadd2(xv[i].x, ns), c = hadd2(xv[i].y, ns), d = hadd2(xv[i].z, ns), e = hadd2(xv[i].w, ns);
              const uint32_t u = hadd2(hadd2(a, c), hadd2(d, e)), w = hsq2(a, hsq2(c, hsq2(d, hsq2(e, 0u))));
              s0 += bf_lo_p(u); s1 += bf_hi(u); q0 += bf_lo_p(w); q1 += bf_hi(w);
          }
        }
        s0 += s1; q0 += q1;
#pragma unroll
        for (int m = 4; m >= 1; m >>= 1) { s0 += __shfl_xor_sync(0xffffffffu, s0, m); q0 += __shfl_xor_sync(0xffffffffu, q0, m); }
        s0 *= (1.f / DM);
        const float var = fmaxf(q0 * (1.f / DM) - s0 * s0, 0.f);
        if ((lane & 7) == 0) st_rec16(&g_rowstat[b * 16 + warp * 4 + (lane >> 3)], __float_as_uint(rsq(var + 1e-5f)), __float_as_uint(-(s0 + sh)), 0u, tag);
      }
      {
        const uint4* rp = &g_rowstat[rb * 128 + t];
        const uint4* rq = &g_rowstat[(rb ^ 1) * 128 + t];
        const uint2* c0 = &g_colsum[0][1024 + (t >> 6) * 1024 + hp * 64 + (t & 63)];
        const uint2* c1 = &g_colsum[0][cb * 128 + t];
        uint4 v0, v1; uint2 u[8];
#pragma unroll 1
        for (int it = 0; it < SPIN; it++) {
          v0 = ld_rec16(rp); v1 = ld_rec16(rq);
          bool ok = true;
#pragma unroll
          for (int i = 0; i < 4; i++) { u[i] = ld_rec8(c0 + i * 3072); u[4 + i] = ld_rec8(c1 + i * 3072); }
#pragma unroll
          for (int i = 0; i < 8; i++) ok = ok && u[i].y == tag;
          if (__all_sync(0xffffffffu, ok && v0.w == tag && v1.w == tag)) break;
          __nanosleep(100);
        }
        sts_u(sb + OFF_RSTAT + t * 4, v0.x); sts_u(sb + OFF_RSTAT + (t + 128) * 4, v1.x);
        mbar_wait(BAR(B_CSD));
        {
          const uint32_t m0 = split_bf16(__uint_as_float(v0.y)), m1 = split_bf16(__uint_as_float(v1.y));
          sts_u4(sb + 12 * SLOT + 4096 + t * 16, m0, m0 & 0xFFFFu, 0u, 0u);
          sts_u4(sb + 12 * SLOT + 6144 + t * 16, m1, m1 & 0xFFFFu, 0u, 0u);
          sts_u2(sb + 12 * SLOT + 8192 + t * 8, 0u, 0u);
        }
#pragma unroll
        for (int e = 0; e < 2; e++) {
          const uint32_t hl = split_bf16((__uint_as_float(u[4 * e].x) + __uint_as_float(u[4 * e + 1].x)) + (__uint_as_float(u[4 * e + 2].x) + __uint_as_float(u[4 * e + 3].x)));
          const uint32_t a = sb + 12 * SLOT + e * 2048 + (t >> 6) * 1024 + (t & 7) * 2, ch = (uint32_t)(t >> 3) & 7u;
#pragma unroll
          for (uint32_t r = 0; r < 8; r++) sts_h(a + r * 128 + ((ch ^ r) << 4), r < 2 ? hl : r == 2 ? hl >> 16 : 0u);
        }
        sts_u(sb + OFF_ONES + t * 4, 0x3F803F80u);
        sts_u(sb + OFF_ONES + 512 + t * 4, 0x3F803F80u);
        if (t < 36) sts_u(sb + OFF_SEL + t * 4, (t & 4) ? 0u : 0x3F803F80u);
        {
          const uint32_t one = (t & 56) == 24 ? 0x3F80u << ((t & 1) * 16) : 0u, w = (t >> 1) & 3;
          sts_u4(sb + OFF_EYE + t * 16, w == 0 ? one : 0u, w == 1 ? one : 0u, w == 2 ? one : 0u, w == 3 ? one : 0u);
        }
        fence_async_smem();
        bar_sync(3, 128);
      }
      asm volatile("setmaxnreg.inc.sync.aligned.u32 160;");
      {
        float a0[64], a1[64];
        {
          wg_fence();
          wg_n128<0, 1>(a0, ext_a(sb, 0), ext_b(sb, 1), 0);
          wg_n128<0, 1>(a1, ext_a(sb, 64), ext_b(sb, 1), 0);
          wg_commit();
          wg_wait<0>();
          mbar_arrive(BAR(B_STAT));
        }
        {
          const bool leader = (tid & 127) == 0;
#pragma unroll 1
          for (int it = 12; it < 16; it++) mbar_wait(BAR(B_FKV + it));
          mbar_wait(BAR(B_QGO));
#pragma unroll 1
          for (int it = 0; it < 16; it++) {
            mbar_wait(BAR(B_FQ + it));
            const uint64_t da = mk_desc(sb + tab4(Q_ASLOTS, it) * SLOT, 16, 1024, 1);
            const uint64_t db = mk_desc(sb + tab4(Q_BSLOTS, it) * SLOT, 8192, 1024, 1);
#pragma unroll
            for (int hf = 0; hf < 2; hf++) {
              int yt = THR > hf ? fresh_tid() : tid;
              if (hf && THR > 1) asm volatile("mov.u32 %0, %%tid.y;" : "=r"(yt));
              wg_fence();
#pragma unroll
              for (int kk = 2 * hf; kk < 2 * hf + 2; kk++) {
                wg_n128<0, 1>(a0, da + kk * 2, db + kk * 128, 1);
                if (THR > 2 && kk == 2 * hf && yt == 8192) pin_order();
                wg_n128<0, 1>(a1, da + kk * 2 + 512, db + kk * 128, 1);
              }
              wg_commit();
              wg_wait<1>();
              if (hf == 0 && it > 0 && (yt & 127) == 0) mbar_arrive(BAR(B_DQ + it - 1));
            }
          }
          mbar_wait(BAR(B_KVFREE));
          wg_wait<0>();
          if (leader) mbar_arrive(BAR(B_DQ + 15));
        }
        MMA_IDS
#pragma unroll
        for (int c = 0; c < 2; c++) {
#pragma unroll
          for (int jj = 0; jj < 4; jj++)
#pragma unroll
            for (int mb = 0; mb < 2; mb++) {
              const float* a = mb ? &a1[32 * c + 8 * jj] : &a0[32 * c + 8 * jj];
              stsm_x4(sb + (10 + c) * SLOT + mb * 8192 + srow * 128 + ((sx ^ (2 * jj)) << 4),
                      pack_bf16(a[0], a[1]), pack_bf16(a[2], a[3]), pack_bf16(a[4], a[5]), pack_bf16(a[6], a[7]));
            }
          fence_async_smem();
          mbar_arrive(BAR(B_QD + c));
        }
        uint4 a[12];
#pragma unroll
        for (int i = 0; i < 12; i++) a[i] = make_uint4(0u, 0u, 0u, tag - 1);
#pragma unroll 1
        for (int it = 0; it < SPIN; it++) {
          bool ok = true;
#pragma unroll
          for (int i = 0; i < 12; i++) ld_rec16_stale(a[i], &g_kvr[4 * cb][i][tid & 127], tag);
#pragma unroll
          for (int i = 0; i < 12; i++) ok = ok && a[i].w == tag;
          if (__all_sync(0xffffffffu, ok)) break;
        }
        const uint32_t kx = (uint32_t)(lane >> 4) ^ ((srow >> 1) & 3);
#pragma unroll
        for (int h = 0; h < 4; h++) {
          const uint32_t base = sb + 12 * SLOT + h * 4096 + srow * 64;
          stsm_x4(base + (kx << 4), a[3 * h].x, a[3 * h].y, a[3 * h].z, a[3 * h + 1].x);
          stsm_x4(base + ((kx ^ 2) << 4), a[3 * h + 1].y, a[3 * h + 1].z, a[3 * h + 2].x, a[3 * h + 2].y);
          if (h & 1)
            stsm_x4(sb + 13 * SLOT + srow * 64 + ((kx ^ (h - 1)) << 4), (a[3 * h - 1].z & 0xFFFFu) | 0x3F800000u, (a[3 * h - 1].z >> 16) | 0x3F800000u,
                    (a[3 * h + 2].z & 0xFFFFu) | 0x3F800000u, (a[3 * h + 2].z >> 16) | 0x3F800000u);
        }
        fence_async_smem();
        __syncwarp();
        if (lane == 0) mbar_arrive(BAR(B_KVRDY));
      }
    }
    if (wg == 3) mbar_wait(BAR(B_DC + 15));
    asm volatile("setmaxnreg.inc.sync.aligned.u32 160;");
    const int w8 = (wg - 2) * 4 + warp;
    uint32_t wf[32][4], wd[16][4];
    if (ffn) {
      const int lane = fresh_tid() & 31;
      const uint32_t mrow = (uint32_t)((lane & 7) + (lane >> 4) * 8), mch = (uint32_t)(lane >> 3) & 1u;
      mbar_wait(BAR(B_FW + w8));
      const uint32_t wsm = sb + tab4(FFN_SLOTS, w8) * SLOT + mrow * 64;
      const uint32_t sw = (mrow >> 1) & 3;
#pragma unroll
      for (int i = 0; i < 16; i++) {
        ldsm_x4_t(wf[2 * i], wsm + i * 1024 + ((mch ^ sw) << 4));
        ldsm_x4_t(wf[2 * i + 1], wsm + i * 1024 + (((2 + mch) ^ sw) << 4));
      }
      uint32_t dep = 0;
#pragma unroll
      for (int i = 0; i < 32; i++) dep ^= wf[i][0];
      if (w8 < 4 && lane == 0) mbar_arrive(BAR(B_REL + w8) + zero_after(dep));
    } else if (w8 == 0 && elect()) {
      mbar_arrive(BAR(B_REL));
    }
    if (ffn) {
      const int lane = fresh_tid() & 31;
      if (wg == 2) mbar_wait(BAR(B_DC + 12));
      st_rec16(&g_ypart[w8 * 16 + (lane >> 1)][fi][lane & 1], 0u, 0u, 0u, 0u);
      __syncwarp();
    }
    mbar_wait(BAR(B_DC + 15));
    asm volatile("setmaxnreg.inc.sync.aligned.u32 224;");
    if (ffn) {
      const int lane = fresh_tid() & 31;
      const uint32_t mrow = (uint32_t)((lane & 7) + (lane >> 4) * 8), mch = (uint32_t)(lane >> 3) & 1u;
      mbar_wait(BAR(B_FW + 8 + (w8 >> 1)));
      const uint32_t dsm = sb + tab4(FFN_SLOTS, 8 + (w8 >> 1)) * SLOT + (w8 & 1) * 8192 + mrow * 128;
#pragma unroll
      for (int i = 0; i < 8; i++) {
        const uint32_t a = dsm + (i >> 2) * 4096 + ((((uint32_t)(i & 3) * 2 + mch) ^ (mrow & 7)) << 4);
        ldsm_x4_t(wd[2 * i], a);
        ldsm_x4_t(wd[2 * i + 1], a + 2048);
      }
    }
    {
      const int t = fresh_tid() - 256, lane = t & 31;
      const uint32_t xs = sb + OFF_PHIQ + w8 * 512;
      const unsigned tag = lds_u(sb + OFF_RED + 4);
      uint32_t wkey;
      {
        uint2 v;
        if (KGATE) mbar_wait(BAR(B_KEY));
#pragma unroll 1
        for (int it = 0; it < SPIN; it++) {
          v = ld_rec8(KREP ? &g_key[cb][rb][lane & 15] : &g_key[cb][0][(lane & 15) * 4]);
          if (__all_sync(0xffffffffu, v.y == tag)) break;
        }
        wkey = __reduce_max_sync(0xffffffffu, v.x);
      }
      const int wrow = (0xFFFF - (int)(wkey & 0xFFFFu)) & (SEQ - 1);
      {
        const uint4* src = reinterpret_cast<const uint4*>(&g_candx[wrow >> 7][(w8 >> 1) * 128]) + lane;
        uint4 v0, v1;
#pragma unroll 1
        for (int it = 0; it < SPIN; it++) {
          v0 = ld_rec16(src); v1 = ld_rec16(src + 32);
          if (__all_sync(0xffffffffu, v0.y == tag && v0.w == tag && v1.y == tag && v1.w == tag)) break;
        }
        const uint32_t a = xs + (lane >> 3) * 64 + (lane & 1) * 32 + ((lane >> 1) & 3) * 4;
        sts_u(a, v0.x); sts_u(a + 16, v0.z); sts_u(a + 256, v1.x); sts_u(a + 272, v1.z);
        __syncwarp();
      }
      if (t == 0) mbar_arrive(BAR(B_ROW));
      if (b == 0 && t == 0) g_epoch = tag;
      const uint32_t t3 = tag % 3u + 1u;
      if (ffn) {
        {
          uint4 xb[8];
#pragma unroll
          for (int i = 0; i < 8; i++) xb[i] = lds_u4(xs + i * 64 + (lane & 3) * 16);
          float d[16];
#pragma unroll
          for (int i = 0; i < 16; i++) d[i] = 0.f;
#pragma unroll
          for (int i = 0; i < 8; i++) {
            mma_bf16(&d[0], wf[4 * i], xb[i].x, xb[i].y); mma_bf16(&d[4], wf[4 * i + 1], xb[i].x, xb[i].y);
            mma_bf16(&d[8], wf[4 * i + 2], xb[i].z, xb[i].w); mma_bf16(&d[12], wf[4 * i + 3], xb[i].z, xb[i].w);
          }
          const int c = lane & 3;
          const float v = c == 0 ? d[0] + d[8] : c == 1 ? d[2] + d[10] : c == 2 ? d[4] + d[12] : d[6] + d[14];
          sts_f(sb + OFF_CS + (uint32_t)(w8 * 32 + c * 8 + (lane >> 2)) * 4, v);
        }
        bar_sync(2, 256);
        uint32_t ab[4];
        {
          const uint32_t pr = sb + OFF_CS + lane * 4;
          const float g = (lds_f(pr) + lds_f(pr + 256)) + (lds_f(pr + 512) + lds_f(pr + 768));
          const float u = (lds_f(pr + 128) + lds_f(pr + 384)) + (lds_f(pr + 640) + lds_f(pr + 896));
          const float act = g * rcp(1.f + ex2(-g * L2E)) * u;
          const uint32_t pair = pack_bf16(act, __shfl_down_sync(0xffffffffu, act, 1));
#pragma unroll
          for (int i = 0; i < 4; i++) ab[i] = __shfl_sync(0xffffffffu, pair, i * 8 + (lane & 3) * 2);
        }
        float d[32];
#pragma unroll
        for (int i = 0; i < 32; i++) d[i] = 0.f;
        {
#pragma unroll
          for (int i = 0; i < 8; i++) mma_bf16(&d[4 * i], wd[2 * i], ab[0], ab[1]);
#pragma unroll
          for (int i = 0; i < 8; i++) mma_bf16(&d[4 * i], wd[2 * i + 1], ab[2], ab[3]);
        }
        const int c = lane & 3;
#pragma unroll
        for (int i = 0; i < 4; i++) {
          const float v = c == 0 ? d[8 * i] : c == 1 ? d[8 * i + 2] : c == 2 ? d[8 * i + 4] : d[8 * i + 6];
          asm volatile("st.relaxed.gpu.global.u32 [%0], %1;" :: "l"(&g_ypart[w8 * 16 + i * 4 + c][fi][0].x + (lane >> 2)), "r"((__float_as_uint(v) & ~3u) | t3) : "memory");
        }
      }
      if (w8 == 0) {
        uint4 fin;
#pragma unroll 1
        for (int it = 0; it < SPIN; it++) {
          fin = ld_rec16(&g_cand[wrow >> 7][b * 4 + (lane & 1) * 2 + ((lane >> 1) & 1)]);
          if (__all_sync(0xffffffffu, fin.w == tag)) break;
        }
        uint32_t u = wkey >> 16;
        u = (u & 0x8000u) ? (u & 0x7FFFu) : (~u & 0xFFFFu);
        const float sig = rcp(1.f + ex2(-__uint_as_float(u << 16) * L2E));
        const uint4* yp = &g_ypart[b][0][0] + lane;
        uint4 v[7];
#pragma unroll 1
        for (int it = 0; it < SPIN; it++) {
          uint32_t bad = 0;
#pragma unroll
          for (int i = 0; i < 7; i++) v[i] = ld_rec16(yp + i * 32);
#pragma unroll
          for (int i = 0; i < 7; i++) {
            v[i].x ^= t3; v[i].y ^= t3; v[i].z ^= t3; v[i].w ^= t3;
            bad |= (v[i].x | v[i].y) | (v[i].z | v[i].w);
          }
          if (__all_sync(0xffffffffu, (bad & 3u) == 0)) break;
        }
        float y[4];
#pragma unroll
        for (int i = 0; i < 4; i++) {
          const float* q = reinterpret_cast<const float*>(v) + i;
          y[i] = ((q[0] + q[4]) + (q[8] + q[12])) + ((q[16] + q[20]) + q[24]);
        }
        const bool up = lane & 2;
        float y0 = (up ? y[2] : y[0]) + __shfl_xor_sync(0xffffffffu, up ? y[0] : y[2], 2);
        float y1 = (up ? y[3] : y[1]) + __shfl_xor_sync(0xffffffffu, up ? y[1] : y[3], 2);
#pragma unroll
        for (int m = 4; m <= 16; m <<= 1) { y0 += __shfl_xor_sync(0xffffffffu, y0, m); y1 += __shfl_xor_sync(0xffffffffu, y1, m); }
        if (lane < 4)
          *reinterpret_cast<uint32_t*>(P.out + (size_t)wrow * DM + b * 8 + (lane & 1) * 4 + (lane & 2)) =
              pack_bf16(bf_lo(fin.y) + fmaf(y0, sig, bf_lo(fin.x)), bf_hi(fin.y) + fmaf(y1, sig, bf_hi(fin.x)));
      }
    }
  } else {
    if (PAD && blockIdx.x == 5000) padn<PAD>();
    asm volatile("setmaxnreg.inc.sync.aligned.u32 160;");
    asm volatile("barrier.sync 0;" ::: "memory");
    {
      const bool leader = (tid & 127) == 0;
      {
        float a0[64], a1[64];
#pragma unroll 1
        for (int it = 0; it < 16; it++) {
          mbar_wait(BAR(B_FKV + it));
          const uint32_t s = sb + (uint32_t)(it & 3) * 3 * SLOT;
          const uint64_t da = mk_desc(s + wg * SLOT, 16, 1024, 1), db = mk_desc(s + 2 * SLOT, 8192, 1024, 1);
          wg_fence();
#pragma unroll
          for (int kk = 0; kk < 4; kk++) {
            wg_n128<0, 1>(a0, da + kk * 2, db + kk * 128, (it | kk) != 0);
            wg_n128<0, 1>(a1, da + kk * 2 + 512, db + kk * 128, (it | kk) != 0);
          }
          wg_commit();
          wg_wait<1>();
          if (it > 0 && leader) mbar_arrive(BAR(B_DKV + it - 1));
        }
        mbar_wait(BAR(B_STAT));
        wg_fence();
        wg_n128<0, 1>(a0, ext_a(sb, wg * 128), ext_b(sb, 0), 1);
        wg_n128<0, 1>(a1, ext_a(sb, wg * 128 + 64), ext_b(sb, 0), 1);
        wg_commit();
        if (leader) mbar_arrive(BAR(B_QGO));
        mbar_wait(BAR(B_PHI));
        wg_wait<0>();
        if (leader) mbar_arrive(BAR(B_DKV + 15));
        if (PIN & 2) pin_order();
        MMA_IDS
        const uint32_t rs = sb + OFF_RSTAT + (uint32_t)(wg * 128 + lr) * 4;
        const uint32_t vt = sb + 12 * SLOT + wg * 4096 + srow * 64 + (((uint32_t)(lane >> 4) ^ ((srow >> 1) & 3)) << 4);
        float pa[16], pb[16];
        uint32_t vp[16];
        const uint64_t dw = mk_desc(sb + OFF_PHIK, 16, 512, 2);
        auto pack_v = [&](const float* a, int mb) {
          const float r0 = lds_f(rs + mb * 256), r1 = lds_f(rs + mb * 256 + 32);
#pragma unroll
          for (int i = 0; i < 16; i++) vp[i] = pack_bf16(a[32 + 2 * i] * ((i & 1) ? r1 : r0), a[33 + 2 * i] * ((i & 1) ? r1 : r0));
        };
        auto put_v = [&]() {
#pragma unroll
          for (int jj = 0; jj < 4; jj++) stsm_x4((vt + (jj >> 1) * 8192) ^ (32 * (jj & 1)), vp[4 * jj], vp[4 * jj + 1], vp[4 * jj + 2], vp[4 * jj + 3]);
        };
        bar_sync(1, 256);
        pack_v(a0, 0);
        put_v();
        auto logits = [&](const uint32_t (&k)[16]) {
          wg_fence();
          wg_n32_rs<1>(pa, k[0], k[1], k[2], k[3], dw, 0);
          wg_n32_rs<1>(pb, k[8], k[9], k[10], k[11], dw + 128, 0);
          wg_n32_rs<1>(pa, k[4], k[5], k[6], k[7], dw + 64, 1);
          wg_n32_rs<1>(pb, k[12], k[13], k[14], k[15], dw + 192, 1);
          wg_commit();
        };
        uint32_t k0[16], k1[16];
        pin_order();
#pragma unroll
        for (int i = 0; i < 16; i++) k0[i] = pack_pin(a0[2 * i], a0[2 * i + 1]);
        logits(k0);
        if (leader) mbar_arrive(BAR(B_QGO2));
#pragma unroll
        for (int i = 0; i < 16; i++) k1[i] = pack_pin(a1[2 * i], a1[2 * i + 1]);
        pack_v(a1, 1);
        if (PIN & 1) pin_order();
        wg_wait<0>();
        float kv[20];
        auto half = [&](float (&p0)[16], float (&p1)[16], int mb) {
          const float sc0 = lds_f(rs + mb * 256) * L2E, sc1 = lds_f(rs + mb * 256 + 32) * L2E;
          const uint32_t ft = sb + 10 * SLOT + wg * 8192 + srow * 128 + (sx << 4);
          uint32_t fo[32];
          auto put = [&](int h) {
#pragma unroll
            for (int g = 4 * h; g < 4 * h + 4; g++) stsm_x4((ft + h * SLOT) ^ (32 * (g & 3)), fo[4 * g], fo[4 * g + 1], fo[4 * g + 2], fo[4 * g + 3]);
          };
          float tot;
          {
            tot = feature_fast(p0, sc0, sc1, &fo[0], [&]() {
              if (mb) {
                if (PIN & 128) pin_order();
                wg_wait<0>();
                bar_arrive(6 + wg, 256);
              }
            });
            if (mb) {
              bar_sync(7 - wg, 256);
              put_v();
            }
            put(0);
            tot += feature_fast(p1, sc0, sc1, &fo[16], []() {});
          }
          put(1);
          if (warp_fails(tot < FAST_LIMIT)) {
            feature_shifted(p0, p1, sc0, sc1, fo);
            put(0);
            put(1);
          }
          if (mb == 0) logits(k1);
          fence_async_smem();
          bar_sync(1, 256);
          if (PIN & 4) pin_order();
          const uint64_t d = mk_desc(sb + (10 + wg) * SLOT, 16, 1024, 1);
          const uint64_t e = mk_desc(sb + 12 * SLOT + wg * 8192, OFF_ONES - 12 * SLOT - wg * 8192, 512, 2);
          wg_fence();
#pragma unroll
          for (int kk = 0; kk < 8; kk++) wg_n40<1, 1>(kv, d + kk * 128, e + kk * (64 - (64 << 16)), (mb | kk) != 0);
          wg_commit();
        };
        half(pa, pb, 0);
        wg_wait<1>();
        half(pa, pb, 1);
        mbar_wait(BAR(B_RESET));
        const unsigned tag = lds_u(sb + OFF_RED + 4);
        uint4* dst = &g_kvp[2 * hp + wg][rbk][0][tid & 127];
        const uint4* src = &g_kvp[2 * hp + (lane >> 4)][0][warp][rbk * 16 + (lane & 15)];
        uint4 a[8];
        if (wg == 0 && warp < 3) {
#pragma unroll
          for (int p = 0; p < 8; p++) a[p] = ld_rec16(src + p * 384);
        }
        wg_wait<0>();
        if (PIN & 8) pin_order();
        kv[17] = kv[18];
#pragma unroll
        for (int i = 0; i < 3; i++)
          st_rec16(dst + i * 128, pack_bf16(kv[6 * i], kv[6 * i + 1]), pack_bf16(kv[6 * i + 2], kv[6 * i + 3]), pack_bf16(kv[6 * i + 4], kv[6 * i + 5]), tag);
        if (leader) mbar_arrive(BAR(B_KVFREE));
        if (wg == 0 && warp < 3) {
#pragma unroll 1
          for (int it = 0; it < SPIN; it++) {
            bool ok = true;
#pragma unroll
            for (int p = 0; p < 8; p++) ld_rec16_stale(a[p], src + p * 384, tag);
#pragma unroll
            for (int p = 0; p < 8; p++) ok = ok && a[p].w == tag;
            if (__all_sync(0xffffffffu, ok)) break;
          }
          float v[6] = {0.f, 0.f, 0.f, 0.f, 0.f, 0.f};
#pragma unroll
          for (int p = 0; p < 8; p++) {
            v[0] += bf_lo(a[p].x); v[1] += bf_hi(a[p].x); v[2] += bf_lo(a[p].y); v[3] += bf_hi(a[p].y); v[4] += bf_lo(a[p].z); v[5] += bf_hi(a[p].z);
          }
          st_rec16(&g_kvr[2 * hp + (lane >> 4)][warp][rbk * 16 + (lane & 15)], pack_bf16(v[0], v[1]), pack_bf16(v[2], v[3]), pack_bf16(v[4], v[5]), tag);
        }
      }
    }
    const uint32_t stg = sb + wg * 8192;
    float s0 = 0.f, q0 = 0.f, d0 = 0.f, s1 = 0.f, q1 = 0.f, d1 = 0.f;
    {
      MMA_IDS
      const unsigned tag = lds_u(sb + OFF_RED + 4);
      const uint32_t t3 = tag % 3u + 1u, tg = (t3 & 1u) | ((t3 & 2u) << 15);
      const int ln = __shfl_sync(0xffffffffu, lane, lane);
      uint4* const og = &g_o[rb][0][wg * 4 + warp][0][ln];
      const uint32_t af = sb + (uint32_t)(wg * 4 + warp) * 2048 + ln * 16;
      float acc[64];
      auto tile_addr = [&]() {
        uint32_t l = ln;
        asm volatile("" : "+r"(l));
        return stg + (uint32_t)warp * 2048 + (l & 15) * 128 + (((l >> 4) ^ (l & 7)) << 4);
      };
      auto add_x = [&]() {
        mbar_wait(BAR(B_FX));
        const uint64_t da = mk_desc(sb + OFF_EYE + 384, 512, 128, 0), db = mk_desc(stg, 2 * SLOT, 4096, 1);
        wg_fence();
#pragma unroll
        for (int s = 0; s < 4; s++) wg_n128<0, 1>(acc, da - s * 8, db + s * 64, s != 0);
        wg_commit();
      };
      auto announce = [&]() {
        if (warp == FLAGW && ln < 8) asm volatile("st.relaxed.gpu.global.u32 [%0], %1;" :: "l"(&g_oflag[rb][ln][cb * 2 + wg].x), "r"(tag) : "memory");
      };
      const bool early = !((LATE >> cb) & 1);
      uint32_t A[2][16];
      const bool lead = warp == 0 && ln == 0;
      {
        const float sc0 = lds_f(sb + OFF_RSTAT + (uint32_t)(wg * 64 + lr) * 4) * L2E, sc1 = lds_f(sb + OFF_RSTAT + (uint32_t)(wg * 64 + lr + 8) * 4) * L2E;
        auto logits = [&](float (&p0)[16], float (&p1)[16], int c) {
          const uint64_t dq = mk_desc(sb + (10 + c) * SLOT + wg * 8192, 16, 1024, 1), dw = mk_desc(sb + OFF_PHIQ + c * 4096, 16, 512, 2);
          mbar_wait(BAR(B_QD + c));
          wg_fence();
          wg_n32<0, 1>(p0, dq, dw, 0);
          wg_n32<0, 1>(p1, dq + 4, dw + 128, 0);
          wg_n32<0, 1>(p0, dq + 2, dw + 64, 1);
          wg_n32<0, 1>(p1, dq + 6, dw + 192, 1);
          wg_commit();
        };
        auto norm = [&](float (&p)[16], uint32_t (&f)[16], const float (&d)[4]) {
          if (warp_fails(feature_norm<false>(f, d) < FAST_LIMIT)) feature_shifted(p, p, sc0, sc1, f);
        };
        auto apply = [&](float (&u)[20], const uint32_t (&f)[16], int h) {
          const uint64_t d = mk_desc(sb + 12 * SLOT + h * 4096, SLOT - h * 4096 + h * 16, 512, 2);
          wg_fence();
#pragma unroll
          for (int s = 0; s < 4; s++) wg_n40_rs<1>(u, f[4 * s], f[4 * s + 1], f[4 * s + 2], f[4 * s + 3], d + s * 64, s != 0);
          wg_commit();
        };
        float pa[16], pb[16], pc[16], pd[16], u0[20], u1[20], u2[20], u3[20], da[4], db[4];
        uint32_t f0[16], f1[16], f2[16], f3[16];
        uint4* const od = og + cb * 2048;
        logits(pa, pb, 0);
        wg_wait<0>();
        feature_exp(pa, sc0, sc1, f0, da, sum_b(sb));
        if (PIN & 64) pin_order();
        logits(pc, pd, 1);
        feature_exp(pb, sc0, sc1, f1, db, sum_b(sb));
        wg_wait<1>();
        norm(pa, f0, da);
        feature_exp(pc, sc0, sc1, f2, da, sum_b(sb));
        wg_wait<1>();
        norm(pb, f1, db);
        wg_wait<0>();
        if (QRD && lead) mbar_arrive(BAR(B_QREAD));
        norm(pc, f2, da);
        if (QORD == 1) {
          feature_exp(pd, sc0, sc1, f3, db, sum_b(sb));
          wg_wait<0>();
          norm(pd, f3, db);
        }
        mbar_wait(BAR(B_KVRDY));
        if (FLAGP == 0 && early) announce();
        apply(u0, f0, 0);
        apply(u1, f1, 1);
        if (QORD == 0) {
          feature_exp(pd, sc0, sc1, f3, db, sum_b(sb));
          wg_wait<1>();
          apply(u2, f2, 2);
        } else {
          wg_wait<1>();
        }
        if (FLAGP == 1 && early) announce();
        attn_out(u0, tg, &A[0][0], od, early);
        if (FLAGP == 2 && early) announce();
        if (QORD) {
          wg_wait<0>();
          apply(u2, f2, 2);
        }
        attn_out(u1, tg, &A[0][8], od + 64, early);
        if (FLAGP == 3 && early) announce();
        if (PIN & 16) pin_order();
        if (QORD == 2) {
          feature_exp(pd, sc0, sc1, f3, db, sum_b(sb));
          wg_wait<1>();
          attn_out(u2, tg, &A[1][0], od + 1024, !LPUB);
          wg_wait<0>();
          norm(pd, f3, db);
          apply(u3, f3, 3);
          if (XMP < 2) { add_x(); wg_wait<1>(); } else wg_wait<0>();
        } else {
          if (QORD == 0) {
            wg_wait<1>();
            norm(pd, f3, db);
          }
          apply(u3, f3, 3);
          if (XMP == 0) { add_x(); wg_wait<2>(); } else wg_wait<1>();
          attn_out(u2, tg, &A[1][0], od + 1024, !LPUB);
          if (XMP == 1) add_x();
          if (XMP < 2) wg_wait<1>(); else wg_wait<0>();
        }
        if (lead) mbar_arrive(BAR(B_XDONE));
        attn_out(u3, tg, &A[1][8], od + 1088, !LPUB);
        if (!early) {
#pragma unroll
          for (int i = 0; i < 4; i++) st_rec16(od + i * 32, A[0][4 * i], A[0][4 * i + 1], A[0][4 * i + 2], A[0][4 * i + 3]);
          announce();
        }
      }
      auto take = [&](uint32_t (&a)[16], int j) {
        const uint32_t s = af + tab4(PC_ASLOTS, j) * SLOT;
#pragma unroll
        for (int i = 0; i < 4; i++) {
          const uint4 v = lds_u4(s + i * 512);
          a[4 * i] = v.x; a[4 * i + 1] = v.y; a[4 * i + 2] = v.z; a[4 * i + 3] = v.w;
        }
      };
      auto check = [&](uint32_t (&a)[16], int j) {
        if (PIN & 256) pin_order();
#pragma unroll
        for (int i = 0; i < 4; i++) a[4 * i] ^= tg;
        if (warp_fails((((a[0] | a[4]) | (a[8] | a[12])) & OTAG) == 0)) {
          const uint4* p = og + pc_chunk(j, cb) * 1024;
#pragma unroll 1
          for (int it = 0; it < SPIN; it++) {
#pragma unroll
            for (int i = 0; i < 4; i++) {
              const uint4 v = ld_rec16(p + i * 32);
              a[4 * i] = v.x ^ tg; a[4 * i + 1] = v.y; a[4 * i + 2] = v.z; a[4 * i + 3] = v.w;
            }
            if (__all_sync(0xffffffffu, (((a[0] | a[4]) | (a[8] | a[12])) & OTAG) == 0)) break;
          }
        }
      };
      if (XMP == 2) add_x();
#pragma unroll
      for (int i = 0; i < 4; i++) A[0][4 * i] ^= tg;
      {
        uint32_t bt = (uint32_t)mk_desc(sb + 3 * SLOT, 8192, 1024, 1);
        const uint32_t bl = bt + 4096;
#pragma unroll 1
        for (int m = 0; m < 16; m += 4) {
#pragma unroll
          for (int e = 0; e < 4; e++) {
            const int j = m + e;
            const uint32_t (&a)[16] = A[e & 1];
            mbar_wait(BAR(B_FB + j));
            const uint64_t db = (mk_desc(0, 0, 1024, 1)) | bt;
            wg_fence();
#pragma unroll
            for (int kk = 0; kk < 4; kk++) {
              wg_n128_rs<1>(acc, a[4 * kk], a[4 * kk + 1], a[4 * kk + 2], a[4 * kk + 3], db + kk * 128, 1);
              if (kk == PSPL) {
                wg_commit();
                wg_wait<1>();
                if (lead) mbar_arrive(BAR(j ? B_DC + j - 1 : B_XREAD));
                if (e || m) {
                  if (e < 3 || m < 12) mbar_wait<1>(BAR(B_FKV + j + 1));
                  take(A[(e & 1) ^ 1], (e + 1) & 3);
                }
                else if (LPUB == 1) {
#pragma unroll
                  for (int i = 0; i < 4; i++) st_rec16(og + cb * 2048 + 1024 + i * 32, A[1][4 * i], A[1][4 * i + 1], A[1][4 * i + 2], A[1][4 * i + 3]);
                }
                if (LPUB == 2 && e == 1 && m == 0) {
#pragma unroll
                  for (int i = 0; i < 4; i++) st_rec16(og + cb * 2048 + 1024 + i * 32, A[1][4 * i] ^ tg, A[1][4 * i + 1], A[1][4 * i + 2], A[1][4 * i + 3]);
                }
                wg_fence();
              }
            }
            wg_commit();
            asm volatile("{\n.reg .pred p;\nsetp.eq.u32 p, %0, %1;\nadd.u32 %0, %0, 1024;\n@p sub.u32 %0, %0, 5120;\n}\n" : "+r"(bt) : "r"(bl));
            if (e < 3 || m < 12) check(A[(e & 1) ^ 1], j + 1);
          }
        }
      }
      mbar_wait(BAR(B_RESET2));
      wg_wait<0>();
      if (leader) mbar_arrive(BAR(B_DC + 15));
#pragma unroll
      for (int j = 0; j < 16; j++) {
        const float2 w = lds_f2(sb + OFF_WR + (uint32_t)(j * 8 + c2) * 4);
        float a = acc[4 * j], c = acc[4 * j + 1];
        s0 += a + c; q0 = fmaf(a, a, fmaf(c, c, q0)); d0 = fmaf(a, w.x, fmaf(c, w.y, d0));
        a = acc[4 * j + 2]; c = acc[4 * j + 3];
        s1 += a + c; q1 = fmaf(a, a, fmaf(c, c, q1)); d1 = fmaf(a, w.x, fmaf(c, w.y, d1));
      }
#pragma unroll
      for (int m = 1; m <= 2; m <<= 1) {
        s0 += __shfl_xor_sync(0xffffffffu, s0, m); q0 += __shfl_xor_sync(0xffffffffu, q0, m); d0 += __shfl_xor_sync(0xffffffffu, d0, m);
        s1 += __shfl_xor_sync(0xffffffffu, s1, m); q1 += __shfl_xor_sync(0xffffffffu, q1, m); d1 += __shfl_xor_sync(0xffffffffu, d1, m);
      }
      if ((lane & 2) == 0) {
        const bool hi = lane & 1;
        st_rec16(&g_hstat[rb][cb][wg * 64 + lr + (hi ? 8 : 0)], __float_as_uint(hi ? s1 : s0), __float_as_uint(hi ? q1 : q0), __float_as_uint(hi ? d1 : d0), lds_u(sb + OFF_RED + 4));
      }
      const uint32_t ha = tile_addr();
#pragma unroll
      for (int jj = 0; jj < 8; jj++)
        stsm_x4((ha ^ (32 * (jj & 3))) + (jj >> 2) * 2 * SLOT,
                pack_bf16(acc[8 * jj], acc[8 * jj + 1]), pack_bf16(acc[8 * jj + 2], acc[8 * jj + 3]),
                pack_bf16(acc[8 * jj + 4], acc[8 * jj + 5]), pack_bf16(acc[8 * jj + 6], acc[8 * jj + 7]));
    }
    asm volatile("setmaxnreg.dec.sync.aligned.u32 32;");
    {
    MMA_IDS
    const int grow0 = rb * 128 + wg * 64 + lr;
    const unsigned tag = lds_u(sb + OFF_RED + 4);
    uint32_t key;
    {
      const int trow = wg * 64 + lr;
      uint4 r00, r01, r10, r11;
      r00 = r01 = r10 = r11 = make_uint4(0u, 0u, 0u, tag - 1);
#pragma unroll 1
      for (int it = 0; it < SPIN; it++) {
        if (HST) {
          ld_rec16_stale(r00, &g_hstat[rb][c2][trow], tag); ld_rec16_stale(r01, &g_hstat[rb][c2 + 1][trow], tag);
          ld_rec16_stale(r10, &g_hstat[rb][c2][trow + 8], tag); ld_rec16_stale(r11, &g_hstat[rb][c2 + 1][trow + 8], tag);
        } else {
        r00 = ld_rec16(&g_hstat[rb][c2][trow]); r01 = ld_rec16(&g_hstat[rb][c2 + 1][trow]);
        r10 = ld_rec16(&g_hstat[rb][c2][trow + 8]); r11 = ld_rec16(&g_hstat[rb][c2 + 1][trow + 8]);
        }
        if (__all_sync(0xffffffffu, r00.w == tag && r01.w == tag && r10.w == tag && r11.w == tag)) break;
      }
      s0 = __uint_as_float(r00.x) + __uint_as_float(r01.x); q0 = __uint_as_float(r00.y) + __uint_as_float(r01.y); d0 = __uint_as_float(r00.z) + __uint_as_float(r01.z);
      s1 = __uint_as_float(r10.x) + __uint_as_float(r11.x); q1 = __uint_as_float(r10.y) + __uint_as_float(r11.y); d1 = __uint_as_float(r10.z) + __uint_as_float(r11.z);
#pragma unroll
      for (int m = 1; m <= 2; m <<= 1) {
        s0 += __shfl_xor_sync(0xffffffffu, s0, m); q0 += __shfl_xor_sync(0xffffffffu, q0, m); d0 += __shfl_xor_sync(0xffffffffu, d0, m);
        s1 += __shfl_xor_sync(0xffffffffu, s1, m); q1 += __shfl_xor_sync(0xffffffffu, q1, m); d1 += __shfl_xor_sync(0xffffffffu, d1, m);
      }
      if (KGATE == 2 && tid == 0) mbar_arrive(BAR(B_KEY));
      const float sumw = lds_f(sb + OFF_RED);
      const float mean0 = s0 * (1.f / DM), mean1 = s1 * (1.f / DM);
      const float rstd0 = rsq(fmaxf(q0 * (1.f / DM) - mean0 * mean0, 0.f) + 1e-5f);
      const float rstd1 = rsq(fmaxf(q1 * (1.f / DM) - mean1 * mean1, 0.f) + 1e-5f);
      const uint32_t rr = pack_bf16(rstd0 * (d0 - mean0 * sumw), rstd1 * (d1 - mean1 * sumw));
      uint32_t u0 = rr & 0xFFFFu, u1 = rr >> 16;
      u0 = (u0 & 0x8000u) ? (~u0 & 0xFFFFu) : (u0 | 0x8000u);
      u1 = (u1 & 0x8000u) ? (~u1 & 0xFFFFu) : (u1 | 0x8000u);
      const uint32_t k0 = (u0 << 16) | (uint32_t)(0xFFFF - grow0), k1 = (u1 << 16) | (uint32_t)(0xFFFF - (grow0 + 8));
      key = __reduce_max_sync(0xffffffffu, max(k0, k1));
      if (lane == 0) sts_u(sb + OFF_RED + 16 + (uint32_t)(wg * 4 + warp) * 4, key);
      if ((lane & 3) == 0) {
        sts_f2(sb + OFF_RSTAT + trow * 8, rstd0, -mean0 * rstd0);
        sts_f2(sb + OFF_RSTAT + (trow + 8) * 8, rstd1, -mean1 * rstd1);
      }
      bar_sync(1, 256);
      const uint4 ka = lds_u4(sb + OFF_RED + 16), kb = lds_u4(sb + OFF_RED + 32);
      key = max(max(max(ka.x, ka.y), max(ka.z, ka.w)), max(max(kb.x, kb.y), max(kb.z, kb.w)));
    }
    if (KREP) { if (tid < 16) st_rec8(&g_key[cb][tid][rb], key, tag); }
    else if (tid == 0) st_rec8(&g_key[cb][0][rb * 4], key, tag);
    if (KGATE == 1 && tid == 0) mbar_arrive(BAR(B_KEY));
    const int crow = (0xFFFF - (int)(key & 0xFFFFu)) & 127;
    const bool own = (crow >> 4) == wg * 4 + warp;
    uint32_t co0 = 0, co1 = 0;
    if (own) {
      const uint32_t r = (uint32_t)(crow & 63);
      const float2 st = lds_f2(sb + OFF_RSTAT + crow * 8);
      const uint32_t a = stg + r * 128 + ((((uint32_t)lane >> 2) ^ (r & 7)) << 4) + (lane & 3) * 4;
      const uint32_t h0 = lds_u(a), h1 = lds_u(a + 2 * SLOT);
      uint32_t n0, n1;
      co0 = ln_res(h0, st.x, st.y, n0); co1 = ln_res(h1, st.x, st.y, n1);
      st_rec8(&g_candx[rb][cb * 64 + lane], n0, tag);
      st_rec8(&g_candx[rb][cb * 64 + 32 + lane], n1, tag);
      st_rec16(&g_cand[rb][cb * 64 + lane], n0, h0, key, tag);
      st_rec16(&g_cand[rb][cb * 64 + 32 + lane], n1, h1, key, tag);
    }
    __nv_bfloat16* ob = P.out + (size_t)(rb * 128 + wg * 64) * DM + cb * 128;
#pragma unroll 4
    for (int i = 0; i < 8; i++) {
      const uint32_t r = (uint32_t)(warp * 16 + (i & 3) * 4 + (lane >> 3));
      const uint32_t a = stg + (i >> 2) * 2 * SLOT + r * 128 + ((((uint32_t)lane & 7) ^ (r & 7)) << 4);
      const uint4 h = lds_u4(a);
      const float2 st = lds_f2(sb + OFF_RSTAT + (wg * 64 + r) * 8);
      uint32_t n;
      uint4 o;
      o.x = ln_res(h.x, st.x, st.y, n); o.y = ln_res(h.y, st.x, st.y, n); o.z = ln_res(h.z, st.x, st.y, n); o.w = ln_res(h.w, st.x, st.y, n);
      if (!own) sts_u4(a, o.x, o.y, o.z, o.w);
      else if ((int)(wg * 64 + r) != crow) stg16(ob + (size_t)r * DM + (i >> 2) * 64 + (lane & 7) * 8, o);
      if ((i & 3) == 3) {
        fence_async_smem();
        __syncwarp();
        if (i == 7) mbar_wait(BAR(B_ROW));
        if (elect()) {
          if (!own) tma_store_2d(&P.mOut, stg + (i >> 2) * 2 * SLOT + warp * 2048, cb * 128 + (i >> 2) * 64, rb * 128 + wg * 64 + warp * 16);
          asm volatile("cp.async.bulk.commit_group;" ::: "memory");
        }
        __syncwarp();
      }
    }
    if (elect()) {
      asm volatile("cp.async.bulk.wait_group.read 0;" ::: "memory");
    }
    __syncwarp();
    if (own) {
      uint2 v;
#pragma unroll 1
      for (int it = 0; it < SPIN; it++) {
        v = ld_rec8(KREP ? &g_key[cb][rb][lane & 15] : &g_key[cb][0][(lane & 15) * 4]);
        if (__all_sync(0xffffffffu, v.y == tag)) break;
      }
      if (__reduce_max_sync(0xffffffffu, v.x) != key) {
        uint32_t* op = reinterpret_cast<uint32_t*>(ob + (size_t)(crow & 63) * DM);
        op[lane] = co0; op[32 + lane] = co1;
      }
    }
    }
  }
#undef BAR
}

typedef CUresult (*EncodeFn)(CUtensorMap*, CUtensorMapDataType, cuuint32_t, void*, const cuuint64_t*, const cuuint64_t*,
                             const cuuint32_t*, const cuuint32_t*, CUtensorMapInterleave, CUtensorMapSwizzle,
                             CUtensorMapL2promotion, CUtensorMapFloatOOBfill);

void make_map(EncodeFn fn, CUtensorMap* m, const void* ptr, uint64_t cols, uint64_t rows, uint32_t bc, uint32_t br, CUtensorMapSwizzle swz) {
  cuuint64_t dims[2] = {cols, rows};
  cuuint64_t strides[1] = {cols * 2};
  cuuint32_t box[2] = {bc, br};
  cuuint32_t es[2] = {1, 1};
  fn(m, CU_TENSOR_MAP_DATA_TYPE_BFLOAT16, 2, const_cast<void*>(ptr), dims, strides, box, es, CU_TENSOR_MAP_INTERLEAVE_NONE, swz,
     CU_TENSOR_MAP_L2_PROMOTION_L2_128B, CU_TENSOR_MAP_FLOAT_OOB_FILL_NONE);
}

}

extern "C" void kernel_launch(void* const* d_in, const int* in_sizes, int n_in, void* d_out, int out_size) {
  static EncodeFn fn = nullptr;
  if (!fn) {
    cudaDriverEntryPointQueryResult q;
    cudaGetDriverEntryPoint("cuTensorMapEncodeTiled", (void**)&fn, cudaEnableDefault, &q);
    cudaFuncSetAttribute(fused_kernel, cudaFuncAttributeMaxDynamicSharedMemorySize, SMEM_BYTES);
  }
  Params P;
  P.x = (const __nv_bfloat16*)d_in[0];
  P.wqkv = (const __nv_bfloat16*)d_in[1];
  const __nv_bfloat16* wphi = (const __nv_bfloat16*)d_in[2];
  P.wo = (const __nv_bfloat16*)d_in[3];
  P.wr = (const __nv_bfloat16*)d_in[5];
  P.wg = (const __nv_bfloat16*)d_in[6];
  P.wu = (const __nv_bfloat16*)d_in[7];
  P.wd = (const __nv_bfloat16*)d_in[8];
  P.out = (__nv_bfloat16*)d_out;
  make_map(fn, &P.mX, P.x, DM, SEQ, 64, 128, CU_TENSOR_MAP_SWIZZLE_128B);
  make_map(fn, &P.mW, P.wqkv, 3 * DM, DM, 64, 64, CU_TENSOR_MAP_SWIZZLE_128B);
  make_map(fn, &P.mWo, P.wo, DM, DM, 64, 64, CU_TENSOR_MAP_SWIZZLE_128B);
  make_map(fn, &P.mPhi, wphi, 32, 1024, 32, 64, CU_TENSOR_MAP_SWIZZLE_64B);
  make_map(fn, &P.mWg, P.wg, FF, DM, 32, 64, CU_TENSOR_MAP_SWIZZLE_64B);
  make_map(fn, &P.mWu, P.wu, FF, DM, 32, 64, CU_TENSOR_MAP_SWIZZLE_64B);
  make_map(fn, &P.mWs, P.wqkv, 3 * DM, DM, 32, 64, CU_TENSOR_MAP_SWIZZLE_NONE);
  make_map(fn, &P.mWd, P.wd, DM, FF, 64, 32, CU_TENSOR_MAP_SWIZZLE_128B);
  make_map(fn, &P.mOut, P.out, DM, SEQ, 64, 16, CU_TENSOR_MAP_SWIZZLE_128B);
  make_map(fn, &P.mWgP, P.wg, FF, DM, 64, 64, CU_TENSOR_MAP_SWIZZLE_128B);
  make_map(fn, &P.mWuP, P.wu, FF, DM, 64, 64, CU_TENSOR_MAP_SWIZZLE_128B);
  fused_kernel<<<NCTA, NTHREADS, SMEM_BYTES, cudaStreamPerThread>>>(P);
}
```

```cpp
#include <cuda_runtime.h>
#include <cuda_bf16.h>
#include <cuda.h>
#include <stdint.h>

namespace {

constexpr int SEQ = 2048, DM = 1024, FF = 3584;
constexpr int NCTA = 128, NTHREADS = 512, NFFN = 112;
constexpr int SPIN = 1 << 17;
constexpr int RSTQ = 3;
constexpr int PSPL = 1;
constexpr int PIN = 145;
constexpr int RCPG = 4;
constexpr int THR = 1;
constexpr int QORD = 2;
constexpr int KH2 = 0;
constexpr int KSH = 0;
constexpr int LPUB = 5;
constexpr int PAD = 0;
constexpr int GATE = 6;
constexpr int FLAGW = 3;
constexpr int LATE = 0x78;
constexpr int SXN = 4;
constexpr int SX0 = 2;
constexpr int SXD = 2;
constexpr int CSW = 0x65431234;
constexpr int HST = 0;
constexpr int KREP = 0;
constexpr int KGATE = 1;
constexpr int SKIP = 0;
constexpr int WEF = 0;
constexpr int TROWS = 16;
constexpr int DYN = 1;
constexpr int MAP = 1;
constexpr int OUTG = 1;
constexpr int EB = 0;
constexpr int FLAGP = 2;
constexpr int FLAGB = 0;
constexpr int QD = 5;

constexpr uint32_t SLOT = 16384;
constexpr uint32_t OFF_MISC = 13 * SLOT;
constexpr uint32_t OFF_PHIK = OFF_MISC;
constexpr uint32_t OFF_PHIQ = OFF_MISC + 4096;
constexpr uint32_t OFF_ONES = OFF_MISC + 12288;
constexpr uint32_t OFF_RSTAT = OFF_MISC + 13312;
constexpr uint32_t OFF_EYE = OFF_MISC + 14336;
constexpr uint32_t OFF_CS = OFF_MISC + 15360;
constexpr uint32_t OFF_WR = OFF_MISC + 16384;
constexpr uint32_t OFF_BAR = OFF_MISC + 16896;
constexpr uint32_t OFF_RED = OFF_MISC + 18304;
constexpr uint32_t OFF_SEL = OFF_RED + 320;
constexpr uint32_t OFF_TCH = OFF_MISC + 19072;
constexpr uint32_t SMEM_BYTES = OFF_MISC + 19456;

enum {
  B_FKV = 0, B_DKV = 16, B_FQ = 32, B_DQ = 48,
  B_PHI = 64, B_RESET = 65, B_RESET2 = 66, B_ROW = 67, B_FX = 68, B_KEY = 69, B_TCH = 70, B_REL = 72,
  B_FB = 80, B_DC = 96, B_QD = 112, B_STAT = 114,
  B_KVFREE = 120, B_QGO = 121, B_QGO2 = 122, B_CSD = 123, B_XDONE = 124, B_QREAD = 125, B_XREAD = 126, B_KVRDY = 127,
  B_FS = 128, B_FW = 144
};
constexpr unsigned long long MISC_COUNTS = 0x0502020203020202ull;

struct Params {
  CUtensorMap mX, mW, mWo, mPhi, mWg, mWu, mWs, mWd, mOut, mWgT, mWuT, mWdT;
  const __nv_bfloat16 *x, *wqkv, *wo, *wr, *wg, *wu, *wd;
  __nv_bfloat16* out;
};

__device__ unsigned g_epoch;
__device__ __align__(128) uint4 g_rowstat[SEQ];
__device__ __align__(128) uint2 g_colsum[4][3 * DM];
__device__ __align__(128) uint4 g_kvp[32][8][3][128];
__device__ __align__(128) uint4 g_kvr[32][3][128];
__device__ __align__(128) uint4 g_o[16][16][8][4][32];
__device__ __align__(128) uint4 g_oflag[16][8][16];
__device__ __align__(128) uint4 g_hstat[16][8][128];
__device__ __align__(128) uint4 g_cand[16][512];
__device__ __align__(128) uint2 g_candx[16][512];
__device__ __align__(128) uint2 g_key[8][16][16];
__device__ __align__(128) uint4 g_ypart[128][NFFN][2];

__device__ __forceinline__ uint32_t smem_u32(const void* p) { return (uint32_t)__cvta_generic_to_shared(p); }
__device__ __forceinline__ bool elect() {
  uint32_t p;
  asm volatile("{\n.reg .pred P;\nelect.sync _|P, 0xffffffff;\nselp.u32 %0, 1, 0, P;\n}\n" : "=r"(p));
  return p != 0;
}
__device__ __forceinline__ void mbar_init(uint32_t bar, uint32_t cnt) { asm volatile("mbarrier.init.shared::cta.b64 [%0], %1;" :: "r"(bar), "r"(cnt)); }
__device__ __forceinline__ void mbar_expect_tx(uint32_t bar, uint32_t bytes) { asm volatile("mbarrier.arrive.expect_tx.shared::cta.b64 _, [%0], %1;" :: "r"(bar), "r"(bytes) : "memory"); }
__device__ __forceinline__ void mbar_arrive(uint32_t bar) { asm volatile("mbarrier.arrive.shared::cta.b64 _, [%0];" :: "r"(bar) : "memory"); }
template <int PARITY = 0>
__device__ __forceinline__ void mbar_wait(uint32_t bar) {
#pragma unroll 1
  for (int it = 0; it < SPIN; it++) {
    uint32_t ok;
    asm volatile("{\n.reg .pred p;\nmbarrier.try_wait.parity.shared::cta.b64 p, [%1], %2;\nselp.u32 %0, 1, 0, p;\n}\n" : "=r"(ok) : "r"(bar), "n"(PARITY) : "memory");
    if (ok) break;
  }
}
__device__ __forceinline__ void tma_load_2d(uint32_t dst, const CUtensorMap* m, uint32_t bar, int c0, int c1) {
  asm volatile("cp.async.bulk.tensor.2d.shared::cluster.global.mbarrier::complete_tx::bytes [%0], [%1, {%3, %4}], [%2];"
    :: "r"(dst), "l"(m), "r"(bar), "r"(c0), "r"(c1) : "memory");
}
__device__ __forceinline__ void tma_load_2d_ef(uint32_t dst, const CUtensorMap* m, uint32_t bar, int c0, int c1) {
  uint64_t pol;
  asm("createpolicy.fractional.L2::evict_first.b64 %0, 1.0;" : "=l"(pol));
  asm volatile("cp.async.bulk.tensor.2d.shared::cluster.global.mbarrier::complete_tx::bytes.L2::cache_hint [%0], [%1, {%3, %4}], [%2], %5;"
    :: "r"(dst), "l"(m), "r"(bar), "r"(c0), "r"(c1), "l"(pol) : "memory");
}
__device__ __forceinline__ void tma_load_3d_ef(uint32_t dst, const CUtensorMap* m, uint32_t bar, int c0, int c1, int c2) {
  uint64_t pol;
  asm("createpolicy.fractional.L2::evict_first.b64 %0, 1.0;" : "=l"(pol));
  asm volatile("cp.async.bulk.tensor.3d.shared::cluster.global.mbarrier::complete_tx::bytes.L2::cache_hint [%0], [%1, {%3, %4, %5}], [%2], %6;"
    :: "r"(dst), "l"(m), "r"(bar), "r"(c0), "r"(c1), "r"(c2), "l"(pol) : "memory");
}
template <int EF> __device__ __forceinline__ void tma_load_w(uint32_t dst, const CUtensorMap* m, uint32_t bar, int c0, int c1) {
  if (EF) tma_load_2d_ef(dst, m, bar, c0, c1); else tma_load_2d(dst, m, bar, c0, c1);
}
__device__ __forceinline__ void tma_store_2d(const CUtensorMap* m, uint32_t src, int c0, int c1) {
  asm volatile("cp.async.bulk.tensor.2d.global.shared::cta.bulk_group [%0, {%2, %3}], [%1];"
    :: "l"(m), "r"(src), "r"(c0), "r"(c1) : "memory");
}
__device__ __forceinline__ void cp_async16(uint32_t dst, const void* src) { asm volatile("cp.async.cg.shared.global [%0], [%1], 16;" :: "r"(dst), "l"(src) : "memory"); }
__device__ __forceinline__ void cp_commit() { asm volatile("cp.async.commit_group;" ::: "memory"); }
template <int N> __device__ __forceinline__ void cp_wait() { asm volatile("cp.async.wait_group %0;" :: "n"(N) : "memory"); }
__device__ __forceinline__ void l2_prefetch(const void* src, uint32_t bytes) {
  asm volatile("cp.async.bulk.prefetch.L2.global [%0], %1;" :: "l"(src), "r"(bytes) : "memory");
}
__device__ __forceinline__ void wg_fence() { asm volatile("wgmma.fence.sync.aligned;" ::: "memory"); }
__device__ __forceinline__ void wg_commit() { asm volatile("wgmma.commit_group.sync.aligned;" ::: "memory"); }
template <int N> __device__ __forceinline__ void wg_wait() { asm volatile("wgmma.wait_group.sync.aligned %0;" :: "n"(N) : "memory"); }
__device__ __forceinline__ void fence_async_smem() { asm volatile("fence.proxy.async.shared::cta;" ::: "memory"); }
__device__ __forceinline__ void bar_sync(int id, int n) { asm volatile("bar.sync %0, %1;" :: "r"(id), "r"(n) : "memory"); }
__device__ __forceinline__ void bar_arrive(int id, int n) { asm volatile("bar.arrive %0, %1;" :: "r"(id), "r"(n) : "memory"); }
__device__ __forceinline__ uint64_t mk_desc(uint32_t addr, uint32_t lbo, uint32_t sbo, uint32_t swz) {
  return (uint64_t)((addr & 0x3FFFF) >> 4) | ((uint64_t)((lbo & 0x3FFFF) >> 4) << 16) | ((uint64_t)(sbo >> 4) << 32) | ((uint64_t)swz << 62);
}
__device__ __forceinline__ void stsm_x4(uint32_t addr, uint32_t r0, uint32_t r1, uint32_t r2, uint32_t r3) {
  asm volatile("stmatrix.sync.aligned.m8n8.x4.shared.b16 [%0], {%1, %2, %3, %4};" :: "r"(addr), "r"(r0), "r"(r1), "r"(r2), "r"(r3) : "memory");
}
__device__ __forceinline__ void ldsm_x4(uint32_t& r0, uint32_t& r1, uint32_t& r2, uint32_t& r3, uint32_t addr) {
  asm volatile("ldmatrix.sync.aligned.m8n8.x4.shared.b16 {%0, %1, %2, %3}, [%4];" : "=r"(r0), "=r"(r1), "=r"(r2), "=r"(r3) : "r"(addr) : "memory");
}
__device__ __forceinline__ void ldsm_x4_t(uint32_t (&r)[4], uint32_t addr) {
  asm volatile("ldmatrix.sync.aligned.m8n8.x4.trans.shared.b16 {%0, %1, %2, %3}, [%4];" : "=r"(r[0]), "=r"(r[1]), "=r"(r[2]), "=r"(r[3]) : "r"(addr) : "memory");
}
__device__ __forceinline__ void mma_bf16(float* d, const uint32_t (&a)[4], uint32_t b0, uint32_t b1) {
  asm volatile("mma.sync.aligned.m16n8k16.row.col.f32.bf16.bf16.f32 {%0, %1, %2, %3}, {%4, %5, %6, %7}, {%8, %9}, {%0, %1, %2, %3};"
    : "+f"(d[0]), "+f"(d[1]), "+f"(d[2]), "+f"(d[3]) : "r"(a[0]), "r"(a[1]), "r"(a[2]), "r"(a[3]), "r"(b0), "r"(b1));
}
__device__ __forceinline__ uint32_t zero_after(uint32_t v) { uint32_t r; asm volatile("prmt.b32 %0, %1, 0, 0x4444;" : "=r"(r) : "r"(v)); return r; }
__device__ __forceinline__ uint32_t now() { uint32_t t; asm volatile("mov.u32 %0, %%globaltimer_lo;" : "=r"(t)); return t; }
__device__ __forceinline__ int fresh_tid() { int v; asm volatile("mov.u32 %0, %%tid.x;" : "=r"(v)); return v; }
template <int ID> __device__ __forceinline__ void pin_at() {
  asm volatile("{\n.reg .pred p;\nsetp.eq.u32 p, %0, %1;\nPIN:\n@p nanosleep.u32 0;\n@p bra.uni PIN;\n}\n" :: "r"(blockIdx.x), "n"(4096 + ID) : "memory");
}
#define pin_order() pin_at<__LINE__>()
__device__ __forceinline__ uint32_t pack_bf16(float lo, float hi) {
  uint32_t r; asm("cvt.rn.bf16x2.f32 %0, %1, %2;" : "=r"(r) : "f"(hi), "f"(lo)); return r;
}
__device__ __forceinline__ uint32_t pack_pin(float lo, float hi) {
  uint32_t r; asm volatile("cvt.rn.bf16x2.f32 %0, %1, %2;" : "=r"(r) : "f"(hi), "f"(lo)); return r;
}
__device__ __forceinline__ uint32_t hadd2(uint32_t a, uint32_t b) { uint32_t r; asm("add.rn.bf16x2 %0, %1, %2;" : "=r"(r) : "r"(a), "r"(b)); return r; }
template <int H> __device__ __forceinline__ uint32_t hmul2(uint32_t a, uint32_t b) {
  uint32_t r;
  if (H) asm("{\n.reg .b16 l, h;\n.reg .b32 t;\nmov.b32 {l, h}, %2;\nmov.b32 t, {h, h};\nmul.rn.bf16x2 %0, %1, t;\n}\n" : "=r"(r) : "r"(a), "r"(b));
  else asm("{\n.reg .b16 l, h;\n.reg .b32 t;\nmov.b32 {l, h}, %2;\nmov.b32 t, {l, l};\nmul.rn.bf16x2 %0, %1, t;\n}\n" : "=r"(r) : "r"(a), "r"(b));
  return r;
}
template <int H> __device__ __forceinline__ uint32_t hfma2(uint32_t a, uint32_t b, uint32_t c) {
  uint32_t r;
  if (H) asm("{\n.reg .b16 l, h;\n.reg .b32 t;\nmov.b32 {l, h}, %2;\nmov.b32 t, {h, h};\nfma.rn.bf16x2 %0, %1, t, %3;\n}\n" : "=r"(r) : "r"(a), "r"(b), "r"(c));
  else asm("{\n.reg .b16 l, h;\n.reg .b32 t;\nmov.b32 {l, h}, %2;\nmov.b32 t, {l, l};\nfma.rn.bf16x2 %0, %1, t, %3;\n}\n" : "=r"(r) : "r"(a), "r"(b), "r"(c));
  return r;
}
__device__ __forceinline__ uint32_t hsq2(uint32_t a, uint32_t c) { uint32_t r; asm("fma.rn.bf16x2 %0, %1, %1, %2;" : "=r"(r) : "r"(a), "r"(c)); return r; }
__device__ __forceinline__ float bf_lo_p(uint32_t v) { float r; asm("prmt.b32 %0, %1, 0, 0x1044;" : "=f"(r) : "r"(v)); return r; }
__device__ __forceinline__ float bf_lo(uint32_t v) { return __uint_as_float(v << 16); }
__device__ __forceinline__ float bf_hi(uint32_t v) { return __uint_as_float(v & 0xFFFF0000u); }
__device__ __forceinline__ float bf_round(float v) { return bf_lo(pack_bf16(v, 0.f)); }
__device__ __forceinline__ float ex2(float v) { float r; asm("ex2.approx.ftz.f32 %0, %1;" : "=f"(r) : "f"(v)); return r; }
__device__ __forceinline__ float rsq(float v) { float r; asm("rsqrt.approx.ftz.f32 %0, %1;" : "=f"(r) : "f"(v)); return r; }
__device__ __forceinline__ float rcp(float v) { float r; asm("rcp.approx.ftz.f32 %0, %1;" : "=f"(r) : "f"(v)); return r; }
__device__ __forceinline__ void st_rec16(uint4* p, uint32_t a, uint32_t b, uint32_t c, uint32_t d) {
  asm volatile("{\n.reg .b128 r;\n.reg .b64 lo, hi;\nmov.b64 lo, {%1, %2};\nmov.b64 hi, {%3, %4};\nmov.b128 r, {lo, hi};\nst.relaxed.gpu.global.b128 [%0], r;\n}\n"
    :: "l"(p), "r"(a), "r"(b), "r"(c), "r"(d) : "memory");
}
__device__ __forceinline__ uint4 ld_rec16(const uint4* p) {
  uint4 v;
  asm volatile("{\n.reg .b128 r;\n.reg .b64 lo, hi;\nld.relaxed.gpu.global.b128 r, [%4];\nmov.b128 {lo, hi}, r;\nmov.b64 {%0, %1}, lo;\nmov.b64 {%2, %3}, hi;\n}\n"
    : "=r"(v.x), "=r"(v.y), "=r"(v.z), "=r"(v.w) : "l"(p) : "memory");
  return v;
}
__device__ __forceinline__ void ld_rec16_stale(uint4& v, const uint4* p, uint32_t tag) {
  asm volatile("{\n.reg .pred p;\n.reg .b128 r;\n.reg .b64 lo, hi;\nmov.b64 lo, {%0, %1};\nmov.b64 hi, {%2, %3};\nmov.b128 r, {lo, hi};\nsetp.ne.u32 p, %3, %5;\n"
    "@p ld.relaxed.gpu.global.b128 r, [%4];\nmov.b128 {lo, hi}, r;\nmov.b64 {%0, %1}, lo;\nmov.b64 {%2, %3}, hi;\n}\n"
    : "+r"(v.x), "+r"(v.y), "+r"(v.z), "+r"(v.w) : "l"(p), "r"(tag) : "memory");
}
__device__ __forceinline__ void st_rec8(uint2* p, uint32_t a, uint32_t b) {
  asm volatile("{\n.reg .b64 r;\nmov.b64 r, {%1, %2};\nst.relaxed.gpu.global.b64 [%0], r;\n}\n" :: "l"(p), "r"(a), "r"(b) : "memory");
}
__device__ __forceinline__ uint2 ld_rec8(const uint2* p) {
  uint2 v;
  asm volatile("{\n.reg .b64 r;\nld.relaxed.gpu.global.b64 r, [%2];\nmov.b64 {%0, %1}, r;\n}\n" : "=r"(v.x), "=r"(v.y) : "l"(p) : "memory");
  return v;
}
__device__ __forceinline__ unsigned ld_relaxed(const unsigned* p) { unsigned v; asm volatile("ld.relaxed.gpu.global.u32 %0, [%1];" : "=r"(v) : "l"(p) : "memory"); return v; }
__device__ __forceinline__ uint4 ldg_nc16(const void* p) {
  uint4 v; asm volatile("ld.global.nc.L1::no_allocate.v4.u32 {%0, %1, %2, %3}, [%4];" : "=r"(v.x), "=r"(v.y), "=r"(v.z), "=r"(v.w) : "l"(p)); return v;
}
__device__ __forceinline__ void stg16(void* p, uint4 v) { asm volatile("st.global.v4.u32 [%0], {%1, %2, %3, %4};" :: "l"(p), "r"(v.x), "r"(v.y), "r"(v.z), "r"(v.w) : "memory"); }
__device__ __forceinline__ float2 lds_f2(uint32_t a) { float2 v; asm volatile("ld.shared.v2.f32 {%0, %1}, [%2];" : "=f"(v.x), "=f"(v.y) : "r"(a)); return v; }
__device__ __forceinline__ float lds_f(uint32_t a) { float v; asm volatile("ld.shared.f32 %0, [%1];" : "=f"(v) : "r"(a)); return v; }
__device__ __forceinline__ uint32_t lds_u(uint32_t a) { uint32_t v; asm volatile("ld.shared.u32 %0, [%1];" : "=r"(v) : "r"(a)); return v; }
__device__ __forceinline__ uint2 lds_u2(uint32_t a) { uint2 v; asm volatile("ld.shared.v2.u32 {%0, %1}, [%2];" : "=r"(v.x), "=r"(v.y) : "r"(a)); return v; }
__device__ __forceinline__ uint4 lds_u4(uint32_t a) { uint4 v; asm volatile("ld.shared.v4.u32 {%0, %1, %2, %3}, [%4];" : "=r"(v.x), "=r"(v.y), "=r"(v.z), "=r"(v.w) : "r"(a)); return v; }
__device__ __forceinline__ void sts_f(uint32_t a, float v) { asm volatile("st.shared.f32 [%0], %1;" :: "r"(a), "f"(v) : "memory"); }
__device__ __forceinline__ void sts_f2(uint32_t a, float x, float y) { asm volatile("st.shared.v2.f32 [%0], {%1, %2};" :: "r"(a), "f"(x), "f"(y) : "memory"); }
__device__ __forceinline__ void sts_u2(uint32_t a, uint32_t x, uint32_t y) { asm volatile("st.shared.v2.u32 [%0], {%1, %2};" :: "r"(a), "r"(x), "r"(y) : "memory"); }
__device__ __forceinline__ void sts_u4(uint32_t a, uint32_t x, uint32_t y, uint32_t z, uint32_t w) { asm volatile("st.shared.v4.u32 [%0], {%1, %2, %3, %4};" :: "r"(a), "r"(x), "r"(y), "r"(z), "r"(w) : "memory"); }
__device__ __forceinline__ void sts_h(uint32_t a, uint32_t v) { asm volatile("st.shared.u16 [%0], %1;" :: "r"(a), "h"((uint16_t)v) : "memory"); }
__device__ __forceinline__ void sts_u(uint32_t a, uint32_t v) { asm volatile("st.shared.u32 [%0], %1;" :: "r"(a), "r"(v) : "memory"); }

template <int TA, int TB>
__device__ __forceinline__ void wg_n128(float (&d)[64], uint64_t da, uint64_t db, int sd) {
  asm volatile("{\n.reg .pred p;\nsetp.ne.b32 p, %66, 0;\n"
    "wgmma.mma_async.sync.aligned.m64n128k16.f32.bf16.bf16 {%0, %1, %2, %3, %4, %5, %6, %7, %8, %9, %10, %11, %12, %13, %14, %15, %16, %17, %18, %19, %20, %21, %22, %23, %24, %25, %26, %27, %28, %29, %30, %31, %32, %33, %34, %35, %36, %37, %38, %39, %40, %41, %42, %43, %44, %45, %46, %47, %48, %49, %50, %51, %52, %53, %54, %55, %56, %57, %58, %59, %60, %61, %62, %63}, %64, %65, p, 1, 1, %67, %68;\n}\n"
    : "+f"(d[0]), "+f"(d[1]), "+f"(d[2]), "+f"(d[3]), "+f"(d[4]), "+f"(d[5]), "+f"(d[6]), "+f"(d[7]), "+f"(d[8]), "+f"(d[9]), "+f"(d[10]), "+f"(d[11]), "+f"(d[12]), "+f"(d[13]), "+f"(d[14]), "+f"(d[15]), "+f"(d[16]), "+f"(d[17]), "+f"(d[18]), "+f"(d[19]), "+f"(d[20]), "+f"(d[21]), "+f"(d[22]), "+f"(d[23]), "+f"(d[24]), "+f"(d[25]), "+f"(d[26]), "+f"(d[27]), "+f"(d[28]), "+f"(d[29]), "+f"(d[30]), "+f"(d[31]), "+f"(d[32]), "+f"(d[33]), "+f"(d[34]), "+f"(d[35]), "+f"(d[36]), "+f"(d[37]), "+f"(d[38]), "+f"(d[39]), "+f"(d[40]), "+f"(d[41]), "+f"(d[42]), "+f"(d[43]), "+f"(d[44]), "+f"(d[45]), "+f"(d[46]), "+f"(d[47]), "+f"(d[48]), "+f"(d[49]), "+f"(d[50]), "+f"(d[51]), "+f"(d[52]), "+f"(d[53]), "+f"(d[54]), "+f"(d[55]), "+f"(d[56]), "+f"(d[57]), "+f"(d[58]), "+f"(d[59]), "+f"(d[60]), "+f"(d[61]), "+f"(d[62]), "+f"(d[63])
    : "l"(da), "l"(db), "r"(sd), "n"(TA), "n"(TB));
}

template <int TA, int TB, int O>
__device__ __forceinline__ void wg_n64(float (&d)[64], uint64_t da, uint64_t db, int sd) {
  asm volatile("{\n.reg .pred p;\nsetp.ne.b32 p, %34, 0;\n"
    "wgmma.mma_async.sync.aligned.m64n64k16.f32.bf16.bf16 {%0, %1, %2, %3, %4, %5, %6, %7, %8, %9, %10, %11, %12, %13, %14, %15, %16, %17, %18, %19, %20, %21, %22, %23, %24, %25, %26, %27, %28, %29, %30, %31}, %32, %33, p, 1, 1, %35, %36;\n}\n"
    : "+f"(d[O + 0]), "+f"(d[O + 1]), "+f"(d[O + 2]), "+f"(d[O + 3]), "+f"(d[O + 4]), "+f"(d[O + 5]), "+f"(d[O + 6]), "+f"(d[O + 7]), "+f"(d[O + 8]), "+f"(d[O + 9]), "+f"(d[O + 10]), "+f"(d[O + 11]), "+f"(d[O + 12]), "+f"(d[O + 13]), "+f"(d[O + 14]), "+f"(d[O + 15]), "+f"(d[O + 16]), "+f"(d[O + 17]), "+f"(d[O + 18]), "+f"(d[O + 19]), "+f"(d[O + 20]), "+f"(d[O + 21]), "+f"(d[O + 22]), "+f"(d[O + 23]), "+f"(d[O + 24]), "+f"(d[O + 25]), "+f"(d[O + 26]), "+f"(d[O + 27]), "+f"(d[O + 28]), "+f"(d[O + 29]), "+f"(d[O + 30]), "+f"(d[O + 31])
    : "l"(da), "l"(db), "r"(sd), "n"(TA), "n"(TB));
}

template <int TA, int TB>
__device__ __forceinline__ void wg_n40(float (&d)[20], uint64_t da, uint64_t db, int sd) {
  asm volatile("{\n.reg .pred p;\nsetp.ne.b32 p, %22, 0;\n"
    "wgmma.mma_async.sync.aligned.m64n40k16.f32.bf16.bf16 {%0, %1, %2, %3, %4, %5, %6, %7, %8, %9, %10, %11, %12, %13, %14, %15, %16, %17, %18, %19}, %20, %21, p, 1, 1, %23, %24;\n}\n"
    : "+f"(d[0]), "+f"(d[1]), "+f"(d[2]), "+f"(d[3]), "+f"(d[4]), "+f"(d[5]), "+f"(d[6]), "+f"(d[7]), "+f"(d[8]), "+f"(d[9]), "+f"(d[10]), "+f"(d[11]), "+f"(d[12]), "+f"(d[13]), "+f"(d[14]), "+f"(d[15]), "+f"(d[16]), "+f"(d[17]), "+f"(d[18]), "+f"(d[19])
    : "l"(da), "l"(db), "r"(sd), "n"(TA), "n"(TB));
}

template <int TA, int TB>
__device__ __forceinline__ void wg_n32(float (&d)[16], uint64_t da, uint64_t db, int sd) {
  asm volatile("{\n.reg .pred p;\nsetp.ne.b32 p, %18, 0;\n"
    "wgmma.mma_async.sync.aligned.m64n32k16.f32.bf16.bf16 {%0, %1, %2, %3, %4, %5, %6, %7, %8, %9, %10, %11, %12, %13, %14, %15}, %16, %17, p, 1, 1, %19, %20;\n}\n"
    : "+f"(d[0]), "+f"(d[1]), "+f"(d[2]), "+f"(d[3]), "+f"(d[4]), "+f"(d[5]), "+f"(d[6]), "+f"(d[7]), "+f"(d[8]), "+f"(d[9]), "+f"(d[10]), "+f"(d[11]), "+f"(d[12]), "+f"(d[13]), "+f"(d[14]), "+f"(d[15])
    : "l"(da), "l"(db), "r"(sd), "n"(TA), "n"(TB));
}

template <int TB>
__device__ __forceinline__ void wg_n40_rs(float (&d)[20], uint32_t a0, uint32_t a1, uint32_t a2, uint32_t a3, uint64_t db, int sd) {
  asm volatile("{\n.reg .pred p;\nsetp.ne.b32 p, %25, 0;\n"
    "wgmma.mma_async.sync.aligned.m64n40k16.f32.bf16.bf16 {%0, %1, %2, %3, %4, %5, %6, %7, %8, %9, %10, %11, %12, %13, %14, %15, %16, %17, %18, %19}, {%20, %21, %22, %23}, %24, p, 1, 1, %26;\n}\n"
    : "+f"(d[0]), "+f"(d[1]), "+f"(d[2]), "+f"(d[3]), "+f"(d[4]), "+f"(d[5]), "+f"(d[6]), "+f"(d[7]), "+f"(d[8]), "+f"(d[9]), "+f"(d[10]), "+f"(d[11]), "+f"(d[12]), "+f"(d[13]), "+f"(d[14]), "+f"(d[15]), "+f"(d[16]), "+f"(d[17]), "+f"(d[18]), "+f"(d[19])
    : "r"(a0), "r"(a1), "r"(a2), "r"(a3), "l"(db), "r"(sd), "n"(TB));
}

template <int TB>
__device__ __forceinline__ void wg_n32_rs(float (&d)[16], uint32_t a0, uint32_t a1, uint32_t a2, uint32_t a3, uint64_t db, int sd) {
  asm volatile("{\n.reg .pred p;\nsetp.ne.b32 p, %21, 0;\n"
    "wgmma.mma_async.sync.aligned.m64n32k16.f32.bf16.bf16 {%0, %1, %2, %3, %4, %5, %6, %7, %8, %9, %10, %11, %12, %13, %14, %15}, {%16, %17, %18, %19}, %20, p, 1, 1, %22;\n}\n"
    : "+f"(d[0]), "+f"(d[1]), "+f"(d[2]), "+f"(d[3]), "+f"(d[4]), "+f"(d[5]), "+f"(d[6]), "+f"(d[7]), "+f"(d[8]), "+f"(d[9]), "+f"(d[10]), "+f"(d[11]), "+f"(d[12]), "+f"(d[13]), "+f"(d[14]), "+f"(d[15])
    : "r"(a0), "r"(a1), "r"(a2), "r"(a3), "l"(db), "r"(sd), "n"(TB));
}

template <int TB>
__device__ __forceinline__ void wg_n8_rs(float (&d)[4], uint32_t a0, uint32_t a1, uint32_t a2, uint32_t a3, uint64_t db, int sd) {
  asm volatile("{\n.reg .pred p;\nsetp.ne.b32 p, %9, 0;\n"
    "wgmma.mma_async.sync.aligned.m64n8k16.f32.bf16.bf16 {%0, %1, %2, %3}, {%4, %5, %6, %7}, %8, p, 1, 1, %10;\n}\n"
    : "+f"(d[0]), "+f"(d[1]), "+f"(d[2]), "+f"(d[3])
    : "r"(a0), "r"(a1), "r"(a2), "r"(a3), "l"(db), "r"(sd), "n"(TB));
}

template <int TB>
__device__ __forceinline__ void wg_n128_rs(float (&d)[64], uint32_t a0, uint32_t a1, uint32_t a2, uint32_t a3, uint64_t db, int sd) {
  asm volatile("{\n.reg .pred p;\nsetp.ne.b32 p, %69, 0;\n"
    "wgmma.mma_async.sync.aligned.m64n128k16.f32.bf16.bf16 {%0, %1, %2, %3, %4, %5, %6, %7, %8, %9, %10, %11, %12, %13, %14, %15, %16, %17, %18, %19, %20, %21, %22, %23, %24, %25, %26, %27, %28, %29, %30, %31, %32, %33, %34, %35, %36, %37, %38, %39, %40, %41, %42, %43, %44, %45, %46, %47, %48, %49, %50, %51, %52, %53, %54, %55, %56, %57, %58, %59, %60, %61, %62, %63}, {%64, %65, %66, %67}, %68, p, 1, 1, %70;\n}\n"
    : "+f"(d[0]), "+f"(d[1]), "+f"(d[2]), "+f"(d[3]), "+f"(d[4]), "+f"(d[5]), "+f"(d[6]), "+f"(d[7]), "+f"(d[8]), "+f"(d[9]), "+f"(d[10]), "+f"(d[11]), "+f"(d[12]), "+f"(d[13]), "+f"(d[14]), "+f"(d[15]), "+f"(d[16]), "+f"(d[17]), "+f"(d[18]), "+f"(d[19]), "+f"(d[20]), "+f"(d[21]), "+f"(d[22]), "+f"(d[23]), "+f"(d[24]), "+f"(d[25]), "+f"(d[26]), "+f"(d[27]), "+f"(d[28]), "+f"(d[29]), "+f"(d[30]), "+f"(d[31]), "+f"(d[32]), "+f"(d[33]), "+f"(d[34]), "+f"(d[35]), "+f"(d[36]), "+f"(d[37]), "+f"(d[38]), "+f"(d[39]), "+f"(d[40]), "+f"(d[41]), "+f"(d[42]), "+f"(d[43]), "+f"(d[44]), "+f"(d[45]), "+f"(d[46]), "+f"(d[47]), "+f"(d[48]), "+f"(d[49]), "+f"(d[50]), "+f"(d[51]), "+f"(d[52]), "+f"(d[53]), "+f"(d[54]), "+f"(d[55]), "+f"(d[56]), "+f"(d[57]), "+f"(d[58]), "+f"(d[59]), "+f"(d[60]), "+f"(d[61]), "+f"(d[62]), "+f"(d[63])
    : "r"(a0), "r"(a1), "r"(a2), "r"(a3), "l"(db), "r"(sd), "n"(TB));
}


template <int N>
__device__ __forceinline__ void feature_shifted(const float (&p)[16], const float (&p2)[16], float sc0, float sc1, uint32_t (&o)[N]) {
  __align__(16) float t[N];
  __align__(16) uint32_t w[N];
#pragma unroll
  for (int i = 0; i < N; i++) t[i] = i < 16 ? p[i] : p2[i & 15];
#pragma unroll 1
  for (int it = 0; it < N / 4; it++) {
    const float* x = t + (it >> 2) * 16 + (it & 1) * 2;
    const int h = (it >> 1) & 1;
    const float sg = h ? -1.f : 1.f, sc = (it & 1) ? sc1 : sc0;
    float mx = sg * x[0], s = 0.f;
#pragma unroll 1
    for (int j = 0; j < 16; j += 4) mx = fmaxf(mx, fmaxf(sg * x[j], sg * x[j + 1]));
    mx = fmaxf(mx, __shfl_xor_sync(0xffffffffu, mx, 1));
    mx = fmaxf(mx, __shfl_xor_sync(0xffffffffu, mx, 2));
#pragma unroll 1
    for (int j = 0; j < 32; j += 4) {
      const float a = ex2((sg * x[(j & 15) + h] - mx) * sc), c = ex2((sg * x[(j & 15) + 1 - h] - mx) * sc);
      if (j < 16) s += a + c;
      else w[(it >> 1) * 8 + (j >> 1) - 8 + (it & 1)] = pack_bf16(a * s, c * s);
      if (j == 12) {
        s += __shfl_xor_sync(0xffffffffu, s, 1);
        s += __shfl_xor_sync(0xffffffffu, s, 2);
        s = rcp(s);
      }
    }
  }
#pragma unroll
  for (int i = 0; i < N; i++) o[i] = w[i];
}
constexpr float FAST_LIMIT = RCPG == 2 ? 0x1p60f : RCPG == 4 ? 0x1p30f : 0x1p15f;
__device__ __forceinline__ void feature_exp(const float* p, float sc0, float sc1, uint32_t* o, float (&d)[4], uint64_t sel) {
  float e[16], r[8];
#pragma unroll
  for (int i = 0; i < 16; i++) e[i] = ex2(p[i] * ((i & 2) ? sc1 : sc0));
#pragma unroll
  for (int i = 0; i < 8; i++) r[i] = e[2 * i] * e[2 * i + 1];
#pragma unroll
  for (int i = 0; i < 8; i++) o[i] = pack_bf16(e[2 * i], e[2 * i + 1]);
  uint32_t a[4];
#pragma unroll
  for (int i = 0; i < 2; i++) {
    if (RCPG == 2) {
      o[8 + i] = pack_bf16(rcp(r[i]), rcp(r[2 + i]));
      o[10 + i] = pack_bf16(rcp(r[4 + i]), rcp(r[6 + i]));
    } else {
      float u = r[i] * r[2 + i], w = r[4 + i] * r[6 + i];
      if (RCPG == 4) { u = rcp(u); w = rcp(w); }
      else { const float z = rcp(u * w), y = z * u; u = z * w; w = y; }
      o[8 + i] = pack_bf16(u * r[2 + i], u * r[i]);
      o[10 + i] = pack_bf16(w * r[6 + i], w * r[4 + i]);
    }
    a[i] = hadd2(hadd2(o[i], o[2 + i]), hadd2(o[4 + i], o[6 + i]));
    a[2 + i] = hfma2<1>(o[6 + i], o[10 + i], hfma2<0>(o[4 + i], o[10 + i], hfma2<1>(o[2 + i], o[8 + i], hmul2<0>(o[i], o[8 + i]))));
  }
  wg_fence();
  wg_n8_rs<0>(d, a[0], a[1], a[2], a[3], sel, 0);
  wg_commit();
}
template <bool FULL>
__device__ __forceinline__ float feature_norm(uint32_t* o, const float (&d)[4]) {
  uint32_t c[4];
  if (FULL) {
#pragma unroll
    for (int i = 0; i < 2; i++) {
      const float z = rcp(d[2 * i] * d[2 * i + 1]);
      const uint32_t n = pack_bf16(z * d[2 * i + 1], z * d[2 * i]);
      c[i] = hmul2<1>(o[8 + i], n); c[2 + i] = hmul2<1>(o[10 + i], n);
#pragma unroll
      for (int j = i; j < 8; j += 2) {
        o[8 + j] = (j & 2) ? hmul2<1>(o[j], c[(j >> 2) * 2 + i]) : hmul2<0>(o[j], c[(j >> 2) * 2 + i]);
        o[j] = hmul2<0>(o[j], n);
      }
    }
  } else {
    const uint32_t n = pack_bf16(d[0] * rcp(d[1]), d[2] * rcp(d[3]));
    c[0] = hmul2<0>(o[8], n); c[1] = hmul2<1>(o[9], n); c[2] = hmul2<0>(o[10], n); c[3] = hmul2<1>(o[11], n);
#pragma unroll
    for (int j = 0; j < 8; j++) o[8 + j] = (j & 2) ? hmul2<1>(o[j], c[(j >> 2) * 2 + (j & 1)]) : hmul2<0>(o[j], c[(j >> 2) * 2 + (j & 1)]);
  }
  return (d[0] + d[1]) + (d[2] + d[3]);
}
__device__ __forceinline__ float feature_norm32(const float (&e)[16], const float (&r)[8], const float (&d)[4], uint32_t* o) {
#pragma unroll
  for (int i = 0; i < 2; i++) {
    const float z = rcp(d[2 * i] * d[2 * i + 1]), np = z * d[2 * i + 1], nm = z * d[2 * i];
    if (KH2) {
      const float q = nm * d[2 * i];
      const uint32_t c0 = pack_bf16(r[i] * q, r[2 + i] * q), c1 = pack_bf16(r[4 + i] * q, r[6 + i] * q);
#pragma unroll
      for (int j = i; j < 8; j += 2) {
        o[j] = pack_bf16(e[2 * j] * np, e[2 * j + 1] * np);
        o[8 + j] = (j & 2) ? hmul2<1>(o[j], (j & 4) ? c1 : c0) : hmul2<0>(o[j], (j & 4) ? c1 : c0);
      }
    } else {
#pragma unroll
      for (int j = i; j < 8; j += 2) {
        const float c = r[j] * nm;
        o[j] = pack_bf16(e[2 * j] * np, e[2 * j + 1] * np);
        o[8 + j] = pack_bf16(e[2 * j] * c, e[2 * j + 1] * c);
      }
    }
  }
  return (d[0] + d[1]) + (d[2] + d[3]);
}
template <class H>
__device__ __forceinline__ float feature_fast(const float* p, float sc0, float sc1, uint32_t* o, H hook) {
  float e[16], r[8], sp[2] = {0.f, 0.f}, sm[2] = {0.f, 0.f};
#pragma unroll
  for (int i = 0; i < 16; i++) e[i] = ex2(p[i] * ((i & 2) ? sc1 : sc0));
#pragma unroll
  for (int i = 0; i < 8; i++) r[i] = e[2 * i] * e[2 * i + 1];
#pragma unroll
  for (int i = 0; i < 2; i++) {
    float u = r[i] * r[2 + i], w = r[4 + i] * r[6 + i];
    if (RCPG == 4) { u = rcp(u); w = rcp(w); }
    else { const float z = rcp(u * w), y = z * u; u = z * w; w = y; }
    const float c = u * r[i], d = w * r[4 + i];
    r[i] = u * r[2 + i]; r[2 + i] = c; r[4 + i] = w * r[6 + i]; r[6 + i] = d;
  }
#pragma unroll
  for (int i = 0; i < 8; i++) {
    const float t = e[2 * i] + e[2 * i + 1];
    sp[i & 1] += t; sm[i & 1] = fmaf(t, r[i], sm[i & 1]);
  }
  const float tot = (sp[0] + sp[1]) + (sm[0] + sm[1]);
  if (KSH == 1) {
#pragma unroll
    for (int i = 0; i < 2; i++) {
      uint32_t v = pack_bf16(sp[i], sm[i]);
      v = hadd2(v, __shfl_xor_sync(0xffffffffu, v, 1));
      const uint32_t w = __shfl_xor_sync(0xffffffffu, v, 2);
      sp[i] = bf_lo(v) + bf_lo(w); sm[i] = bf_hi(v) + bf_hi(w);
    }
  } else {
#pragma unroll
    for (int m = 1; m <= 2; m <<= 1)
#pragma unroll
      for (int i = 0; i < 2; i++) { sp[i] += __shfl_xor_sync(0xffffffffu, sp[i], m); sm[i] += __shfl_xor_sync(0xffffffffu, sm[i], m); }
  }
  hook();
  const float d[4] = {sp[0], sm[0], sp[1], sm[1]};
  feature_norm32(e, r, d, o);
  return tot;
}
__device__ __forceinline__ bool warp_fails(bool ok) { return __builtin_expect(!__all_sync(0xffffffffu, ok), 0); }
constexpr uint32_t OTAG = 0x00010001u;
__device__ __forceinline__ void attn_out(const float (&u)[20], uint32_t tg, uint32_t* r, uint4* dst, bool pub) {
  const float d0 = rcp(fmaf(u[17], 0.5e-6f, u[16])), d1 = rcp(fmaf(u[19], 0.5e-6f, u[18]));
#pragma unroll
  for (int j = 0; j < 8; j++) r[j] = pack_bf16(u[2 * j] * ((j & 1) ? d1 : d0), u[2 * j + 1] * ((j & 1) ? d1 : d0));
  r[0] = (r[0] & ~OTAG) | tg; r[4] = (r[4] & ~OTAG) | tg;
  if (pub) {
    st_rec16(dst, r[0], r[1], r[2], r[3]);
    st_rec16(dst + 32, r[4], r[5], r[6], r[7]);
  }
}

constexpr float L2E = 1.4426950408889634f;

__device__ __forceinline__ int pc_chunk(int j, int cb) {
  const int c = j > 8, e = j - 2 - 7 * c;
  return j < 2 ? 2 * cb + j : 2 * (e == cb ? 7 : e) + c;
}
constexpr unsigned long long Q_ASLOTS = 0x1896308963089630ull, Q_BSLOTS = 0x754217542175421ull;
constexpr unsigned long long Q_CHUNKS = 0xAB9876543210FEDCull;
constexpr unsigned long long PC_ASLOTS = 0x2BA02BA02BA02BAull, PC_BSLOTS = 0x3765437654376543ull;
constexpr unsigned long long FFN_SLOTS = 0xBA8954C11897ull;
constexpr unsigned long long FFN_ORDER = 0xB74A69583210ull;
constexpr unsigned long long FFN_WAIT0 = 0x6B4A65497E7E3D3Eull, FFN_WAIT1 = 0x6C6C4B6Bull;
constexpr unsigned long long FFN_PACE0 = 0x6A67647F51ull, FFN_PACE1 = 0x0ull;
constexpr unsigned long long WO_WAIT0 = 0x626160483C3D3C3Bull, WO_WAIT1 = 0x6A69686766656463ull;
constexpr unsigned long long WO_PACE0 = 0x527F502Full, WO_PACE1 = 0x0ull;
constexpr unsigned long long PF_PACE0 = 0x0ull, PF_PACE1 = 0x1D1D1C1C00000000ull, PF_PACE2 = 0x313130301F1F1E1Eull, PF_PACE3 = 0x3232ull;
constexpr unsigned long long PF_EARLY = 0x111111111111ull;
constexpr int PF_FIRST = 12;
__device__ __forceinline__ uint32_t tab4(unsigned long long t, int i) { return (uint32_t)(t >> (4 * i)) & 15u; }
__device__ __forceinline__ uint32_t tab8(unsigned long long lo, unsigned long long hi, int i) { return (uint32_t)((i < 8 ? lo : hi) >> (8 * (i & 7))) & 255u; }

__device__ __forceinline__ float sum8(uint4 v) {
  return ((bf_lo(v.x) + bf_hi(v.x)) + (bf_lo(v.y) + bf_hi(v.y))) + ((bf_lo(v.z) + bf_hi(v.z)) + (bf_lo(v.w) + bf_hi(v.w)));
}
__device__ __forceinline__ float warp_sum(float s) {
#pragma unroll
  for (int m = 16; m >= 1; m >>= 1) s += __shfl_xor_sync(0xffffffffu, s, m);
  return s;
}
__device__ __forceinline__ uint32_t ln_res(uint32_t h, float a, float c, uint32_t& n) {
  const float l = bf_lo(h), u = bf_hi(h);
  n = pack_bf16(fmaf(l, a, c), fmaf(u, a, c));
  return pack_bf16(l + bf_lo(n), u + bf_hi(n));
}

__device__ __forceinline__ uint64_t ext_a(uint32_t sb, uint32_t row) { return mk_desc(sb + 12 * SLOT + 4096 + row * 16, 4096 - row * 16, 128, 0); }
__device__ __forceinline__ uint64_t ext_b(uint32_t sb, uint32_t part) { return mk_desc(sb + 12 * SLOT + part * 2048, 1024, 0, 1); }
__device__ __forceinline__ uint64_t sum_b(uint32_t sb) { return mk_desc(sb + OFF_SEL, 16, 128, 0); }
__device__ __forceinline__ uint32_t split_bf16(float v) { return pack_bf16(v, v - bf_round(v)); }

template <int N> __device__ __forceinline__ void padn() { if constexpr (N > 1) { padn<N / 2>(); padn<N - N / 2>(); } else if constexpr (N == 1) asm volatile("nanosleep.u32 1;"); }
__global__ void __launch_bounds__(NTHREADS, 1) fused_kernel(const __grid_constant__ Params P) {
  extern __shared__ __align__(1024) uint8_t smem_raw[];
  const uint32_t sb = smem_u32(smem_raw);
  const uint32_t bars = sb + OFF_BAR;
  const int tid = threadIdx.x;
  const int wg = __shfl_sync(0xffffffffu, tid >> 7, 0);
  const int warp = __shfl_sync(0xffffffffu, (tid >> 5) & 3, 0);
  const int lane = tid & 31;
  const int b = MAP == 0 ? (blockIdx.x & 1) * 64 + (blockIdx.x >> 1)
              : MAP == 1 ? (blockIdx.x >> 5) * 32 + (blockIdx.x & 3) * 8 + ((blockIdx.x >> 2) & 7)
              : MAP == 2 ? (blockIdx.x >> 5) * 32 + ((blockIdx.x >> 2) & 3) * 8 + ((blockIdx.x >> 4) & 1) * 4 + (blockIdx.x & 3)
              : MAP == 3 ? (blockIdx.x & 3) * 32 + (blockIdx.x >> 5) * 8 + ((blockIdx.x >> 2) & 7)
              : (blockIdx.x & 1) * 64 + ((blockIdx.x >> 1) & 1) * 8 + (blockIdx.x >> 5) * 16 + ((blockIdx.x >> 2) & 7);
  const bool ffn = (blockIdx.x & 7) != 7;
  const int fi = blockIdx.x - (blockIdx.x >> 3);
  const int rbk = b >> 4, hp = b & 15;
  const int rb = b >> 3, cb = b & 7;
#define BAR(i) (bars + 8u * (uint32_t)(i))
#define MMA_IDS \
    const int tid = fresh_tid(), lane = tid & 31; \
    const bool leader = (tid & 127) == 0; \
    const uint32_t srow = (uint32_t)(warp * 16 + (lane & 7) + ((lane >> 3) & 1) * 8); \
    const uint32_t sx = (uint32_t)(lane >> 4) ^ (srow & 7); \
    const int c2 = (lane & 3) * 2, lr = warp * 16 + (lane >> 2); \
    (void)leader; (void)sx; (void)c2; (void)lr;

  auto load_kv = [&](int it) {
    const uint32_t s = sb + (uint32_t)(it & 3) * 3 * SLOT, fb = BAR(B_FKV + it);
    mbar_expect_tx(fb, ((SKIP & 8) ? 0 : 2 * SLOT) + ((SKIP & 16) ? 0 : SLOT));
    if (!(SKIP & 8)) {
    tma_load_2d(s, &P.mX, fb, it * 64, rb * 128);
    tma_load_2d(s + SLOT, &P.mX, fb, it * 64, (rb ^ 1) * 128);
    }
    if (!(SKIP & 16)) {
    tma_load_w<WEF & 1>(s + 2 * SLOT, &P.mW, fb, 1024 + hp * 64, it * 64);
    tma_load_w<WEF & 1>(s + 2 * SLOT + 8192, &P.mW, fb, 2048 + hp * 64, it * 64);
    }
  };
  auto prefetch = [&](int c) {
    if (c < 2) { l2_prefetch(P.wo + b * 8192 + c * 4096, 8192); return; }
    if (!ffn) return;
    const int e = c - 2;
    if (e == 0) mbar_expect_tx(BAR(B_TCH), 24 * 1024);
    const CUtensorMap* mp = e >= 16 ? &P.mWdT : (e & 1) ? &P.mWuT : &P.mWgT;
    const int r = e >= 16 ? fi * 512 + (e - 16) * 64 : (e >> 1) * 128 + (fi & 1) * 64;
#pragma unroll 1
    for (int q = 0; q < 64; q += TROWS) tma_load_2d(sb + OFF_TCH, mp, BAR(B_TCH), e >= 16 ? 0 : (fi >> 1) * 64, r + q);
  };

  {
    const int w16 = wg * 4 + warp;
    const uint32_t cnt = w16 == 14 ? 128u : ((0x300Cu >> w16) & 1u) + 1u;
    if (elect()) {
      if (w16 == 11) {
#pragma unroll
        for (int i = 0; i < 4; i++) mbar_init(BAR(B_FKV + i), 1u);
        asm volatile("fence.mbarrier_init.release.cluster;" ::: "memory");
        load_kv(0);
      }
#pragma unroll
      for (int i = 0; i < 8; i++)
        if (w16 || i >= 4) mbar_init(BAR(w16 * 8 + i), w16 == 15 ? (uint32_t)(MISC_COUNTS >> (8 * i)) & 255u : cnt);
      mbar_init(BAR(B_FS + w16), w16 >= 14 ? 2u : 1u);
      mbar_init(BAR(B_FW + w16), 1u);
      asm volatile("fence.mbarrier_init.release.cluster;" ::: "memory");
    }
    __syncwarp();
    if (w16 == 11 && elect()) {
#pragma unroll 1
      for (int i = 1; i < 4; i++) load_kv(i);
    }
    __syncwarp();
  }

  if (wg >= 2) {
    if (wg == 3) {
      asm volatile("setmaxnreg.dec.sync.aligned.u32 64;");
      asm volatile("barrier.sync 0;" ::: "memory");
        if (warp) {
          const int q = 3 * b + warp - 1, cg = q % 96, kq = q / 96;
          const uint32_t buf = sb + (warp == 3 ? OFF_PHIQ : 12 * SLOT + (warp - 1) * 8192);
          const uint32_t fb = BAR(B_FS + (warp - 1) * 4);
          mbar_wait(BAR(B_FKV + ((CSW >> (4 * (kq + (cg < 32 ? 0 : 4)))) & 15)));
          if (elect()) {
#pragma unroll
            for (int p = 0; p < 2; p++) { mbar_expect_tx(fb + p * 8, 4096); tma_load_w<WEF & 4>(buf + p * 4096, &P.mWs, fb + p * 8, cg * 32, kq * 256 + p * 64); }
          }
          float cs[8];
#pragma unroll
          for (int i = 0; i < 8; i++) cs[i] = 0.f;
          const unsigned ep = ld_relaxed(&g_epoch);
#pragma unroll 1
          for (int p = 0; p < 4; p++) {
            mbar_wait(fb + p * 8);
            uint4 v[8];
#pragma unroll
            for (int i = 0; i < 8; i++) v[i] = lds_u4(buf + (p & 1) * 4096 + i * 512 + lane * 16);
            if (p < 2) {
              uint32_t dep = 0;
#pragma unroll
              for (int i = 0; i < 8; i++) dep ^= v[i].x;
              const int n = p + 2 + (int)__shfl_sync(0xffffffffu, zero_after(dep), 0);
              if (elect()) {
                mbar_expect_tx(fb + n * 8, 4096);
                tma_load_w<WEF & 4>(buf + (n & 1) * 4096, &P.mWs, fb + n * 8, cg * 32, kq * 256 + n * 64);
              }
            }
#pragma unroll
            for (int i = 0; i < 8; i += 2) {
              cs[0] += bf_lo(v[i].x) + bf_lo(v[i + 1].x); cs[1] += bf_hi(v[i].x) + bf_hi(v[i + 1].x);
              cs[2] += bf_lo(v[i].y) + bf_lo(v[i + 1].y); cs[3] += bf_hi(v[i].y) + bf_hi(v[i + 1].y);
              cs[4] += bf_lo(v[i].z) + bf_lo(v[i + 1].z); cs[5] += bf_hi(v[i].z) + bf_hi(v[i + 1].z);
              cs[6] += bf_lo(v[i].w) + bf_lo(v[i + 1].w); cs[7] += bf_hi(v[i].w) + bf_hi(v[i + 1].w);
            }
          }
          {
            const bool u4 = lane & 16, u2 = lane & 8, u1 = lane & 4;
#pragma unroll
            for (int i = 0; i < 4; i++) cs[i] = (u4 ? cs[4 + i] : cs[i]) + __shfl_xor_sync(0xffffffffu, u4 ? cs[i] : cs[4 + i], 16);
#pragma unroll
            for (int i = 0; i < 2; i++) cs[i] = (u2 ? cs[2 + i] : cs[i]) + __shfl_xor_sync(0xffffffffu, u2 ? cs[i] : cs[2 + i], 8);
            cs[0] = (u1 ? cs[1] : cs[0]) + __shfl_xor_sync(0xffffffffu, u1 ? cs[0] : cs[1], 4);
          }
          if (warp == 3 && elect()) {
            mbar_expect_tx(BAR(B_PHI), 12288);
            tma_load_2d(sb + OFF_PHIK, &P.mPhi, BAR(B_PHI), 0, hp * 64);
            tma_load_2d(sb + OFF_PHIQ, &P.mPhi, BAR(B_PHI), (int)zero_after(__float_as_uint(cs[0])), cb * 128);
            tma_load_2d(sb + OFF_PHIQ + 4096, &P.mPhi, BAR(B_PHI), (int)zero_after(__float_as_uint(cs[0])), cb * 128 + 64);
          }
          st_rec8(&g_colsum[kq][cg * 32 + (lane & 3) * 8 + (lane >> 2)], __float_as_uint(cs[0]), ep + 1);
          if (lane == 0) mbar_arrive(BAR(B_CSD));
        }
      asm volatile("setmaxnreg.dec.sync.aligned.u32 32;");
      if (warp == 0) {
        int pc = 0;
#pragma unroll 1
        for (int it = 4; it < 16; it++) {
          mbar_wait(BAR(B_DKV + it - 4));
          if (elect()) {
            load_kv(it);
#pragma unroll 1
            for (int n = tab4(PF_EARLY, it - 4); n > 0; n--) prefetch(pc++);
          }
        }
#pragma unroll 1
        for (int it = 0; it < 16; it++) {
          const uint32_t fb = BAR(B_FQ + it), s = sb + tab4(Q_BSLOTS, it) * SLOT;
          int kc = (int)tab4(Q_CHUNKS, it);
          const bool own = (kc >> 1) == cb;
          kc = (own ? 10 + (kc & 1) : it >= 14 ? 2 * cb + (kc & 1) : kc) * 64;
          if (it == 5) mbar_wait(BAR(B_DKV + 15));
          mbar_wait(it >= QD ? BAR(B_DQ + it - QD) : BAR(B_DKV + 12 + (own && it < 4 ? it : it >> 1)));
          if (elect()) {
            mbar_expect_tx(fb, it < 4 && !own ? SLOT : 2 * SLOT);
            if (it >= 4 || own) tma_load_2d(sb + tab4(Q_ASLOTS, it) * SLOT, &P.mX, fb, kc, rb * 128);
            tma_load_2d(s, &P.mW, fb, cb * 128, kc);
            tma_load_2d(s + 8192, &P.mW, fb, cb * 128 + 64, kc);
          }
        }
        mbar_wait(BAR(B_KVRDY));
        const unsigned tag = lds_u(sb + OFF_RED + 4);
        const unsigned* fp = &g_oflag[rb][cb][lane & 15].x;
        uint32_t seen = 0, all = 0, perm = 0, pv = ld_relaxed(fp), left = cb < 3 ? (0x4015u ^ (1u << (2 * cb))) : 0x15u;
#pragma unroll 1
        for (int j = 2; j < 16; j++) {
          if (!DYN || j >= 5) left = 1u << pc_chunk(j, cb);
          if (j == GATE) all = 0xFFFFu;
#pragma unroll 1
          for (int it = 0; it < SPIN && j <= 8 && !((seen & (seen >> 1) & left) && (seen & all) == all); it++) {
            seen |= __ballot_sync(0xffffffffu, pv == tag);
            pv = ld_relaxed(fp);
          }
          const int kc = (__ffs(j <= 8 ? seen & (seen >> 1) & left : left) - 1) & 15;
          left ^= 1u << kc;
          const int dj = j < 5 ? (kc == 14 ? cb : kc >> 1) + 2 - j : 0;
          const int ds = j < 5 ? dj : (int)(perm << 12) >> 28;
          perm = (perm << 4) | (ds & 15);
          mbar_wait(BAR(j < 4 ? B_KVRDY : j < (EB ? 5 : 6) ? B_QREAD : B_DC + j - 5));
          if (elect()) {
            if (DYN) sts_u2(sb + OFF_RED + 64 + j * 8, dj * 8, ds * 1024);
            mbar_expect_tx(BAR(B_FKV + j), (SKIP & 2) ? 0 : SLOT);
            if (!(SKIP & 2)) asm volatile("cp.async.bulk.shared::cluster.global.mbarrier::complete_tx::bytes [%0], [%1], %2, [%3];"
              :: "r"(sb + tab4(PC_ASLOTS, j) * SLOT), "l"(&g_o[rb][kc][0][0][0]), "n"(SLOT), "r"(BAR(B_FKV + j)) : "memory");
          }
        }
      } else {
        if (warp == 1) {
#pragma unroll 1
          for (int j = 0; j < 16; j++) {
            uint32_t s = sb + tab4(PC_BSLOTS, j) * SLOT;
            const uint32_t fb = BAR(B_FB + j);
            const int kc = pc_chunk(j, cb);
            mbar_wait(BAR(tab8(WO_WAIT0, WO_WAIT1, j)));
            mbar_wait(BAR(tab8(WO_PACE0, WO_PACE1, j)));
            if (DYN && j >= 7) s += lds_u(sb + OFF_RED + 28 + j * 8) * 16;
            if (elect()) {
              mbar_expect_tx(fb, (SKIP & 1) ? 0 : SLOT);
              if (!(SKIP & 1)) {
              tma_load_2d(s, &P.mWo, fb, cb * 128, kc * 64);
              tma_load_2d(s + 8192, &P.mWo, fb, cb * 128 + 64, kc * 64);
              }
            }
          }
        } else if (warp == 3) {
#pragma unroll 1
          for (int c = PF_FIRST; c < 26; c++) {
            mbar_wait(BAR(c < 16 ? tab8(PF_PACE0, PF_PACE1, c) : tab8(PF_PACE2, PF_PACE3, c - 16)));
            if (elect()) prefetch(c);
          }
          __syncwarp();
          if (lane == 0) mbar_arrive(BAR(B_KVRDY));
          if (ffn) mbar_wait(BAR(B_TCH));
          mbar_wait(BAR(B_DC + 10));
#pragma unroll 1
          for (int i = 0; i < 4; i++) st_rec16(&g_hstat[rb][cb][i * 32 + lane], 0u, 0u, 0u, 0u);
          st_rec16(reinterpret_cast<uint4*>(&g_candx[rb][cb * 64]) + lane, 0u, 0u, 0u, 0u);
          if (KREP) { if (lane < 16) st_rec8(&g_key[cb][lane][rb], 0u, 0u); }
          else if (lane < 2) st_rec16(reinterpret_cast<uint4*>(&g_key[cb][rb >> 2][(rb & 3) * 4]) + lane, 0u, 0u, 0u, 0u);
          __syncwarp();
          if (lane == 0) mbar_arrive(BAR(B_RESET2));
        } else {
          mbar_wait(BAR(B_DQ + RSTQ));
#pragma unroll 1
          for (int i = 0; i < 12; i++) {
            st_rec16(&g_kvp[2 * hp][rbk][0][i * 32 + lane], 0u, 0u, 0u, 0u);
            st_rec16(&g_kvp[2 * hp + 1][rbk][0][i * 32 + lane], 0u, 0u, 0u, 0u);
          }
#pragma unroll 1
          for (int i = 0; i < 3; i++) st_rec16(&g_kvr[2 * hp + (lane >> 4)][i][rbk * 16 + (lane & 15)], 0u, 0u, 0u, 0u);
          if (lane < 16) st_rec16(&g_oflag[rb][lane >> 1][cb * 2 + (lane & 1)], 0u, 0u, 0u, 0u);
          __syncwarp();
          if (lane == 0) mbar_arrive(BAR(B_RESET));
          if (ffn) {
#pragma unroll 1
            for (int n = 0; n < 12; n++) {
              const int i = (int)tab4(FFN_ORDER, n);
              uint32_t s = sb + tab4(FFN_SLOTS, i) * SLOT;
              const uint32_t fb = BAR(B_FW + i);
              mbar_wait(BAR(tab8(FFN_WAIT0, FFN_WAIT1, n)));
              mbar_wait(BAR(tab8(FFN_PACE0, FFN_PACE1, n)));
              if (DYN && i == 7) s += lds_u(sb + OFF_RED + 84) * 16;
              if (elect()) {
                mbar_expect_tx(fb, SLOT);
                tma_load_3d_ef(s, i >= 8 ? &P.mWd : (i & 1) ? &P.mWu : &P.mWg, fb, i < 8 ? fi * 32 : 0, i < 8 ? (i >> 1) * 256 : fi * 32, i < 8 ? 0 : (i - 8) * 4);
              }
            }
          }
        }
      }
    } else {
      asm volatile("barrier.sync 0;" ::: "memory");
      const int t = tid - 256;
      const unsigned tag = ld_relaxed(&g_epoch) + 1;
      if (warp == 0) {
        float s = 0.f;
#pragma unroll
        for (int i = 0; i < 4; i++) s += sum8(ldg_nc16(P.wr + i * 256 + lane * 8));
        const uint2 w = *reinterpret_cast<const uint2*>(P.wr + cb * 128 + lane * 4);
        s = warp_sum(s);
        if (lane == 0) { sts_f(sb + OFF_RED, s); sts_u(sb + OFF_RED + 4, tag); }
        sts_f2(sb + OFF_WR + lane * 16, bf_lo(w.x), bf_hi(w.x));
        sts_f2(sb + OFF_WR + lane * 16 + 8, bf_lo(w.y), bf_hi(w.y));
      }
      __syncwarp();
      {
        const __nv_bfloat16* xp = P.x + (size_t)(b * 16 + warp * 4 + (lane >> 3)) * DM + (lane & 7) * 8;
        float sh = 0.f, s0 = 0.f, q0 = 0.f, s1 = 0.f, q1 = 0.f;
        uint32_t ns = 0;
#pragma unroll 1
        for (int g = 0; g < 16 / SXN; g++) {
          uint4 xv[SXN];
          mbar_wait(BAR(B_FKV + SX0 + g * SXD));
#pragma unroll
          for (int i = 0; i < SXN; i++) xv[i] = ldg_nc16(xp + (g * SXN + i) * 64);
          if (g == 0) {
            sh = __shfl_sync(0xffffffffu, bf_lo(xv[0].x), lane & 24);
            ns = pack_bf16(-sh, -sh);
          }
#pragma unroll
          for (int i = 0; i < SXN; i++) {
              const uint32_t a = hadd2(xv[i].x, ns), c = hadd2(xv[i].y, ns), d = hadd2(xv[i].z, ns), e = hadd2(xv[i].w, ns);
              const uint32_t u = hadd2(hadd2(a, c), hadd2(d, e)), w = hsq2(a, hsq2(c, hsq2(d, hsq2(e, 0u))));
              s0 += bf_lo_p(u); s1 += bf_hi(u); q0 += bf_lo_p(w); q1 += bf_hi(w);
          }
        }
        s0 += s1; q0 += q1;
#pragma unroll
        for (int m = 4; m >= 1; m >>= 1) { s0 += __shfl_xor_sync(0xffffffffu, s0, m); q0 += __shfl_xor_sync(0xffffffffu, q0, m); }
        s0 *= (1.f / DM);
        const float var = fmaxf(q0 * (1.f / DM) - s0 * s0, 0.f);
        if ((lane & 7) == 0) st_rec16(&g_rowstat[b * 16 + warp * 4 + (lane >> 3)], __float_as_uint(rsq(var + 1e-5f)), __float_as_uint(-(s0 + sh)), 0u, tag);
      }
      {
        const uint4* rp = &g_rowstat[rb * 128 + t];
        const uint4* rq = &g_rowstat[(rb ^ 1) * 128 + t];
        const uint2* c0 = &g_colsum[0][1024 + (t >> 6) * 1024 + hp * 64 + (t & 63)];
        const uint2* c1 = &g_colsum[0][cb * 128 + t];
        uint4 v0, v1; uint2 u[8];
#pragma unroll 1
        for (int it = 0; it < SPIN; it++) {
          v0 = ld_rec16(rp); v1 = ld_rec16(rq);
          bool ok = true;
#pragma unroll
          for (int i = 0; i < 4; i++) { u[i] = ld_rec8(c0 + i * 3072); u[4 + i] = ld_rec8(c1 + i * 3072); }
#pragma unroll
          for (int i = 0; i < 8; i++) ok = ok && u[i].y == tag;
          if (__all_sync(0xffffffffu, ok && v0.w == tag && v1.w == tag)) break;
          __nanosleep(100);
        }
        sts_u(sb + OFF_RSTAT + t * 4, v0.x); sts_u(sb + OFF_RSTAT + (t + 128) * 4, v1.x);
        mbar_wait(BAR(B_CSD));
        {
          const uint32_t m0 = split_bf16(__uint_as_float(v0.y)), m1 = split_bf16(__uint_as_float(v1.y));
          sts_u4(sb + 12 * SLOT + 4096 + t * 16, m0, m0 & 0xFFFFu, 0u, 0u);
          sts_u4(sb + 12 * SLOT + 6144 + t * 16, m1, m1 & 0xFFFFu, 0u, 0u);
          sts_u2(sb + 12 * SLOT + 8192 + t * 8, 0u, 0u);
        }
#pragma unroll
        for (int e = 0; e < 2; e++) {
          const uint32_t hl = split_bf16((__uint_as_float(u[4 * e].x) + __uint_as_float(u[4 * e + 1].x)) + (__uint_as_float(u[4 * e + 2].x) + __uint_as_float(u[4 * e + 3].x)));
          const uint32_t a = sb + 12 * SLOT + e * 2048 + (t >> 6) * 1024 + (t & 7) * 2, ch = (uint32_t)(t >> 3) & 7u;
#pragma unroll
          for (uint32_t r = 0; r < 8; r++) sts_h(a + r * 128 + ((ch ^ r) << 4), r < 2 ? hl : r == 2 ? hl >> 16 : 0u);
        }
        sts_u(sb + OFF_ONES + t * 4, 0x3F803F80u);
        sts_u(sb + OFF_ONES + 512 + t * 4, 0x3F803F80u);
        if (t < 36) sts_u(sb + OFF_SEL + t * 4, (t & 4) ? 0u : 0x3F803F80u);
        {
          const uint32_t one = (t & 56) == 24 ? 0x3F80u << ((t & 1) * 16) : 0u, w = (t >> 1) & 3;
          sts_u4(sb + OFF_EYE + t * 16, w == 0 ? one : 0u, w == 1 ? one : 0u, w == 2 ? one : 0u, w == 3 ? one : 0u);
        }
        fence_async_smem();
        bar_sync(3, 128);
      }
      asm volatile("setmaxnreg.inc.sync.aligned.u32 160;");
      {
        float a0[64], a1[64];
        {
          wg_fence();
          wg_n128<0, 1>(a0, ext_a(sb, 0), ext_b(sb, 1), 0);
          wg_n128<0, 1>(a1, ext_a(sb, 64), ext_b(sb, 1), 0);
          wg_commit();
          wg_wait<0>();
          mbar_arrive(BAR(B_STAT));
        }
        {
          const bool leader = (tid & 127) == 0;
#pragma unroll 1
          for (int it = 12; it < 16; it++) mbar_wait(BAR(B_FKV + it));
          mbar_wait(BAR(B_QGO));
#pragma unroll 1
          for (int it = 0; it < 16; it++) {
            mbar_wait(BAR(B_FQ + it));
            const uint64_t da = mk_desc(sb + tab4(Q_ASLOTS, it) * SLOT, 16, 1024, 1);
            const uint64_t db = mk_desc(sb + tab4(Q_BSLOTS, it) * SLOT, 8192, 1024, 1);
#pragma unroll
            for (int hf = 0; hf < 2; hf++) {
              int yt = THR > hf ? fresh_tid() : tid;
              if (hf && THR > 1) asm volatile("mov.u32 %0, %%tid.y;" : "=r"(yt));
              wg_fence();
#pragma unroll
              for (int kk = 2 * hf; kk < 2 * hf + 2; kk++) {
                wg_n128<0, 1>(a0, da + kk * 2, db + kk * 128, 1);
                if (THR > 2 && kk == 2 * hf && yt == 8192) pin_order();
                wg_n128<0, 1>(a1, da + kk * 2 + 512, db + kk * 128, 1);
              }
              wg_commit();
              wg_wait<1>();
              if (hf == 0 && it > 0 && (yt & 127) == 0) mbar_arrive(BAR(B_DQ + it - 1));
            }
          }
          mbar_wait(BAR(B_KVFREE));
          wg_wait<0>();
          if (leader) mbar_arrive(BAR(B_DQ + 15));
        }
        MMA_IDS
#pragma unroll
        for (int c = 0; c < 2; c++) {
#pragma unroll
          for (int jj = 0; jj < 4; jj++)
#pragma unroll
            for (int mb = 0; mb < 2; mb++) {
              const float* a = mb ? &a1[32 * c + 8 * jj] : &a0[32 * c + 8 * jj];
              stsm_x4(sb + (10 + c) * SLOT + mb * 8192 + srow * 128 + ((sx ^ (2 * jj)) << 4),
                      pack_bf16(a[0], a[1]), pack_bf16(a[2], a[3]), pack_bf16(a[4], a[5]), pack_bf16(a[6], a[7]));
            }
          fence_async_smem();
          mbar_arrive(BAR(B_QD + c));
        }
        uint4 a[12];
#pragma unroll
        for (int i = 0; i < 12; i++) a[i] = make_uint4(0u, 0u, 0u, tag - 1);
#pragma unroll 1
        for (int it = 0; it < SPIN; it++) {
          bool ok = true;
#pragma unroll
          for (int i = 0; i < 12; i++) ld_rec16_stale(a[i], &g_kvr[4 * cb][i][tid & 127], tag);
#pragma unroll
          for (int i = 0; i < 12; i++) ok = ok && a[i].w == tag;
          if (__all_sync(0xffffffffu, ok)) break;
        }
        const uint32_t kx = (uint32_t)(lane >> 4) ^ ((srow >> 1) & 3);
#pragma unroll
        for (int h = 0; h < 4; h++) {
          const uint32_t base = sb + 12 * SLOT + h * 4096 + srow * 64;
          stsm_x4(base + (kx << 4), a[3 * h].x, a[3 * h].y, a[3 * h].z, a[3 * h + 1].x);
          stsm_x4(base + ((kx ^ 2) << 4), a[3 * h + 1].y, a[3 * h + 1].z, a[3 * h + 2].x, a[3 * h + 2].y);
          if (h & 1)
            stsm_x4(sb + 13 * SLOT + srow * 64 + ((kx ^ (h - 1)) << 4), (a[3 * h - 1].z & 0xFFFFu) | 0x3F800000u, (a[3 * h - 1].z >> 16) | 0x3F800000u,
                    (a[3 * h + 2].z & 0xFFFFu) | 0x3F800000u, (a[3 * h + 2].z >> 16) | 0x3F800000u);
        }
        fence_async_smem();
        __syncwarp();
        if (lane == 0) mbar_arrive(BAR(B_KVRDY));
      }
    }
    if (wg == 3) mbar_wait(BAR(B_DC + 15));
    asm volatile("setmaxnreg.inc.sync.aligned.u32 160;");
    const int w8 = (wg - 2) * 4 + warp;
    uint32_t wf[32][4], wd[16][4];
    if (ffn) {
      const int lane = fresh_tid() & 31;
      const uint32_t mrow = (uint32_t)((lane & 7) + (lane >> 4) * 8), mch = (uint32_t)(lane >> 3) & 1u;
      mbar_wait(BAR(B_FW + w8));
      uint32_t wsm = sb + tab4(FFN_SLOTS, w8) * SLOT + mrow * 64;
      if (DYN && w8 == 7) wsm += lds_u(sb + OFF_RED + 84) * 16;
      const uint32_t sw = (mrow >> 1) & 3;
#pragma unroll
      for (int i = 0; i < 16; i++) {
        ldsm_x4_t(wf[2 * i], wsm + i * 1024 + ((mch ^ sw) << 4));
        ldsm_x4_t(wf[2 * i + 1], wsm + i * 1024 + (((2 + mch) ^ sw) << 4));
      }
      uint32_t dep = 0;
#pragma unroll
      for (int i = 0; i < 32; i++) dep ^= wf[i][0];
      if (w8 < 4 && lane == 0) mbar_arrive(BAR(B_REL + w8) + zero_after(dep));
    } else if (w8 == 0 && elect()) {
      mbar_arrive(BAR(B_REL));
    }
    if (ffn) {
      const int lane = fresh_tid() & 31;
      if (wg == 2) mbar_wait(BAR(B_DC + 12));
      st_rec16(&g_ypart[w8 * 16 + (lane >> 1)][fi][lane & 1], 0u, 0u, 0u, 0u);
      __syncwarp();
    }
    mbar_wait(BAR(B_DC + 15));
    asm volatile("setmaxnreg.inc.sync.aligned.u32 224;");
    if (ffn) {
      const int lane = fresh_tid() & 31;
      const uint32_t mrow = (uint32_t)((lane & 7) + (lane >> 4) * 8), mch = (uint32_t)(lane >> 3) & 1u;
      mbar_wait(BAR(B_FW + 8 + (w8 >> 1)));
      const uint32_t dsm = sb + tab4(FFN_SLOTS, 8 + (w8 >> 1)) * SLOT + (w8 & 1) * 8192 + mrow * 128;
#pragma unroll
      for (int i = 0; i < 8; i++) {
        const uint32_t a = dsm + (i >> 2) * 4096 + ((((uint32_t)(i & 3) * 2 + mch) ^ (mrow & 7)) << 4);
        ldsm_x4_t(wd[2 * i], a);
        ldsm_x4_t(wd[2 * i + 1], a + 2048);
      }
    }
    {
      const int t = fresh_tid() - 256, lane = t & 31;
      const uint32_t xs = sb + OFF_PHIQ + w8 * 512;
      const unsigned tag = lds_u(sb + OFF_RED + 4);
      uint32_t wkey;
      {
        uint2 v;
        if (KGATE) mbar_wait(BAR(B_KEY));
#pragma unroll 1
        for (int it = 0; it < SPIN; it++) {
          v = ld_rec8(KREP ? &g_key[cb][rb][lane & 15] : &g_key[cb][0][(lane & 15) * 4]);
          if (__all_sync(0xffffffffu, v.y == tag)) break;
        }
        wkey = __reduce_max_sync(0xffffffffu, v.x);
      }
      const int wrow = (0xFFFF - (int)(wkey & 0xFFFFu)) & (SEQ - 1);
      {
        const uint4* src = reinterpret_cast<const uint4*>(&g_candx[wrow >> 7][(w8 >> 1) * 128]) + lane;
        uint4 v0, v1;
#pragma unroll 1
        for (int it = 0; it < SPIN; it++) {
          v0 = ld_rec16(src); v1 = ld_rec16(src + 32);
          if (__all_sync(0xffffffffu, v0.y == tag && v0.w == tag && v1.y == tag && v1.w == tag)) break;
        }
        const uint32_t a = xs + (lane >> 3) * 64 + (lane & 1) * 32 + ((lane >> 1) & 3) * 4;
        sts_u(a, v0.x); sts_u(a + 16, v0.z); sts_u(a + 256, v1.x); sts_u(a + 272, v1.z);
        __syncwarp();
      }
      if (t == 0) mbar_arrive(BAR(B_ROW));
      if (b == 0 && t == 0) g_epoch = tag;
      const uint32_t t3 = tag % 3u + 1u;
      if (ffn) {
        {
          uint4 xb[8];
#pragma unroll
          for (int i = 0; i < 8; i++) xb[i] = lds_u4(xs + i * 64 + (lane & 3) * 16);
          float d[16];
#pragma unroll
          for (int i = 0; i < 16; i++) d[i] = 0.f;
#pragma unroll
          for (int i = 0; i < 8; i++) {
            mma_bf16(&d[0], wf[4 * i], xb[i].x, xb[i].y); mma_bf16(&d[4], wf[4 * i + 1], xb[i].x, xb[i].y);
            mma_bf16(&d[8], wf[4 * i + 2], xb[i].z, xb[i].w); mma_bf16(&d[12], wf[4 * i + 3], xb[i].z, xb[i].w);
          }
          const int c = lane & 3;
          const float v = c == 0 ? d[0] + d[8] : c == 1 ? d[2] + d[10] : c == 2 ? d[4] + d[12] : d[6] + d[14];
          sts_f(sb + OFF_CS + (uint32_t)(w8 * 32 + c * 8 + (lane >> 2)) * 4, v);
        }
        bar_sync(2, 256);
        uint32_t ab[4];
        {
          const uint32_t pr = sb + OFF_CS + lane * 4;
          const float g = (lds_f(pr) + lds_f(pr + 256)) + (lds_f(pr + 512) + lds_f(pr + 768));
          const float u = (lds_f(pr + 128) + lds_f(pr + 384)) + (lds_f(pr + 640) + lds_f(pr + 896));
          const float act = g * rcp(1.f + ex2(-g * L2E)) * u;
          const uint32_t pair = pack_bf16(act, __shfl_down_sync(0xffffffffu, act, 1));
#pragma unroll
          for (int i = 0; i < 4; i++) ab[i] = __shfl_sync(0xffffffffu, pair, i * 8 + (lane & 3) * 2);
        }
        float d[32];
#pragma unroll
        for (int i = 0; i < 32; i++) d[i] = 0.f;
        {
#pragma unroll
          for (int i = 0; i < 8; i++) mma_bf16(&d[4 * i], wd[2 * i], ab[0], ab[1]);
#pragma unroll
          for (int i = 0; i < 8; i++) mma_bf16(&d[4 * i], wd[2 * i + 1], ab[2], ab[3]);
        }
        const int c = lane & 3;
#pragma unroll
        for (int i = 0; i < 4; i++) {
          const float v = c == 0 ? d[8 * i] : c == 1 ? d[8 * i + 2] : c == 2 ? d[8 * i + 4] : d[8 * i + 6];
          asm volatile("st.relaxed.gpu.global.u32 [%0], %1;" :: "l"(&g_ypart[w8 * 16 + i * 4 + c][fi][0].x + (lane >> 2)), "r"((__float_as_uint(v) & ~3u) | t3) : "memory");
        }
      }
      if (w8 == 0) {
        uint4 fin;
#pragma unroll 1
        for (int it = 0; it < SPIN; it++) {
          fin = ld_rec16(&g_cand[wrow >> 7][b * 4 + (lane & 1) * 2 + ((lane >> 1) & 1)]);
          if (__all_sync(0xffffffffu, fin.w == tag)) break;
        }
        uint32_t u = wkey >> 16;
        u = (u & 0x8000u) ? (u & 0x7FFFu) : (~u & 0xFFFFu);
        const float sig = rcp(1.f + ex2(-__uint_as_float(u << 16) * L2E));
        const uint4* yp = &g_ypart[b][0][0] + lane;
        uint4 v[7];
#pragma unroll 1
        for (int it = 0; it < SPIN; it++) {
          uint32_t bad = 0;
#pragma unroll
          for (int i = 0; i < 7; i++) v[i] = ld_rec16(yp + i * 32);
#pragma unroll
          for (int i = 0; i < 7; i++) {
            v[i].x ^= t3; v[i].y ^= t3; v[i].z ^= t3; v[i].w ^= t3;
            bad |= (v[i].x | v[i].y) | (v[i].z | v[i].w);
          }
          if (__all_sync(0xffffffffu, (bad & 3u) == 0)) break;
        }
        float y[4];
#pragma unroll
        for (int i = 0; i < 4; i++) {
          const float* q = reinterpret_cast<const float*>(v) + i;
          y[i] = ((q[0] + q[4]) + (q[8] + q[12])) + ((q[16] + q[20]) + q[24]);
        }
        const bool up = lane & 2;
        float y0 = (up ? y[2] : y[0]) + __shfl_xor_sync(0xffffffffu, up ? y[0] : y[2], 2);
        float y1 = (up ? y[3] : y[1]) + __shfl_xor_sync(0xffffffffu, up ? y[1] : y[3], 2);
#pragma unroll
        for (int m = 4; m <= 16; m <<= 1) { y0 += __shfl_xor_sync(0xffffffffu, y0, m); y1 += __shfl_xor_sync(0xffffffffu, y1, m); }
        if (lane < 4)
          *reinterpret_cast<uint32_t*>(P.out + (size_t)wrow * DM + b * 8 + (lane & 1) * 4 + (lane & 2)) =
              pack_bf16(bf_lo(fin.y) + fmaf(y0, sig, bf_lo(fin.x)), bf_hi(fin.y) + fmaf(y1, sig, bf_hi(fin.x)));
      }
    }
  } else {
    if (PAD && blockIdx.x == 5000) padn<PAD>();
    asm volatile("setmaxnreg.inc.sync.aligned.u32 160;");
    asm volatile("barrier.sync 0;" ::: "memory");
    {
      const bool leader = (tid & 127) == 0;
      {
        float a0[64], a1[64];
#pragma unroll 1
        for (int it = 0; it < 16; it++) {
          mbar_wait(BAR(B_FKV + it));
          const uint32_t s = sb + (uint32_t)(it & 3) * 3 * SLOT;
          const uint64_t da = mk_desc(s + wg * SLOT, 16, 1024, 1), db = mk_desc(s + 2 * SLOT, 8192, 1024, 1);
          wg_fence();
#pragma unroll
          for (int kk = 0; kk < 4; kk++) {
            wg_n128<0, 1>(a0, da + kk * 2, db + kk * 128, (it | kk) != 0);
            wg_n128<0, 1>(a1, da + kk * 2 + 512, db + kk * 128, (it | kk) != 0);
          }
          wg_commit();
          wg_wait<1>();
          if (it > 0 && leader) mbar_arrive(BAR(B_DKV + it - 1));
        }
        mbar_wait(BAR(B_STAT));
        wg_fence();
        wg_n128<0, 1>(a0, ext_a(sb, wg * 128), ext_b(sb, 0), 1);
        wg_n128<0, 1>(a1, ext_a(sb, wg * 128 + 64), ext_b(sb, 0), 1);
        wg_commit();
        if (leader) mbar_arrive(BAR(B_QGO));
        mbar_wait(BAR(B_PHI));
        wg_wait<0>();
        if (leader) mbar_arrive(BAR(B_DKV + 15));
        if (PIN & 2) pin_order();
        MMA_IDS
        const uint32_t rs = sb + OFF_RSTAT + (uint32_t)(wg * 128 + lr) * 4;
        const uint32_t vt = sb + 12 * SLOT + wg * 4096 + srow * 64 + (((uint32_t)(lane >> 4) ^ ((srow >> 1) & 3)) << 4);
        float pa[16], pb[16];
        uint32_t vp[16];
        const uint64_t dw = mk_desc(sb + OFF_PHIK, 16, 512, 2);
        auto pack_v = [&](const float* a, int mb) {
          const float r0 = lds_f(rs + mb * 256), r1 = lds_f(rs + mb * 256 + 32);
#pragma unroll
          for (int i = 0; i < 16; i++) vp[i] = pack_bf16(a[32 + 2 * i] * ((i & 1) ? r1 : r0), a[33 + 2 * i] * ((i & 1) ? r1 : r0));
        };
        auto put_v = [&]() {
#pragma unroll
          for (int jj = 0; jj < 4; jj++) stsm_x4((vt + (jj >> 1) * 8192) ^ (32 * (jj & 1)), vp[4 * jj], vp[4 * jj + 1], vp[4 * jj + 2], vp[4 * jj + 3]);
        };
        bar_sync(1, 256);
        pack_v(a0, 0);
        put_v();
        auto logits = [&](const uint32_t (&k)[16]) {
          wg_fence();
          wg_n32_rs<1>(pa, k[0], k[1], k[2], k[3], dw, 0);
          wg_n32_rs<1>(pb, k[8], k[9], k[10], k[11], dw + 128, 0);
          wg_n32_rs<1>(pa, k[4], k[5], k[6], k[7], dw + 64, 1);
          wg_n32_rs<1>(pb, k[12], k[13], k[14], k[15], dw + 192, 1);
          wg_commit();
        };
        uint32_t k0[16], k1[16];
        pin_order();
#pragma unroll
        for (int i = 0; i < 16; i++) k0[i] = pack_pin(a0[2 * i], a0[2 * i + 1]);
        logits(k0);
#pragma unroll
        for (int i = 0; i < 16; i++) k1[i] = pack_pin(a1[2 * i], a1[2 * i + 1]);
        pack_v(a1, 1);
        if (PIN & 1) pin_order();
        wg_wait<0>();
        float kv[20];
        auto half = [&](float (&p0)[16], float (&p1)[16], int mb) {
          const float sc0 = lds_f(rs + mb * 256) * L2E, sc1 = lds_f(rs + mb * 256 + 32) * L2E;
          const uint32_t ft = sb + 10 * SLOT + wg * 8192 + srow * 128 + (sx << 4);
          uint32_t fo[32];
          auto put = [&](int h) {
#pragma unroll
            for (int g = 4 * h; g < 4 * h + 4; g++) stsm_x4((ft + h * SLOT) ^ (32 * (g & 3)), fo[4 * g], fo[4 * g + 1], fo[4 * g + 2], fo[4 * g + 3]);
          };
          float tot;
          {
            tot = feature_fast(p0, sc0, sc1, &fo[0], [&]() {
              if (mb) {
                if (PIN & 128) pin_order();
                wg_wait<0>();
                bar_arrive(6 + wg, 256);
              }
            });
            if (mb) {
              bar_sync(7 - wg, 256);
              put_v();
            }
            put(0);
            tot += feature_fast(p1, sc0, sc1, &fo[16], []() {});
          }
          put(1);
          if (warp_fails(tot < FAST_LIMIT)) {
            feature_shifted(p0, p1, sc0, sc1, fo);
            put(0);
            put(1);
          }
          if (mb == 0) logits(k1);
          fence_async_smem();
          bar_sync(1, 256);
          if (PIN & 4) pin_order();
          const uint64_t d = mk_desc(sb + (10 + wg) * SLOT, 16, 1024, 1);
          const uint64_t e = mk_desc(sb + 12 * SLOT + wg * 8192, OFF_ONES - 12 * SLOT - wg * 8192, 512, 2);
          wg_fence();
#pragma unroll
          for (int kk = 0; kk < 8; kk++) wg_n40<1, 1>(kv, d + kk * 128, e + kk * (64 - (64 << 16)), (mb | kk) != 0);
          wg_commit();
        };
        half(pa, pb, 0);
        wg_wait<1>();
        half(pa, pb, 1);
        mbar_wait(BAR(B_RESET));
        const unsigned tag = lds_u(sb + OFF_RED + 4);
        uint4* dst = &g_kvp[2 * hp + wg][rbk][0][tid & 127];
        const uint4* src = &g_kvp[2 * hp + (lane >> 4)][0][warp][rbk * 16 + (lane & 15)];
        uint4 a[8];
        if (wg == 0 && warp < 3) {
#pragma unroll
          for (int p = 0; p < 8; p++) a[p] = ld_rec16(src + p * 384);
        }
        wg_wait<0>();
        if (PIN & 8) pin_order();
        kv[17] = kv[18];
#pragma unroll
        for (int i = 0; i < 3; i++)
          st_rec16(dst + i * 128, pack_bf16(kv[6 * i], kv[6 * i + 1]), pack_bf16(kv[6 * i + 2], kv[6 * i + 3]), pack_bf16(kv[6 * i + 4], kv[6 * i + 5]), tag);
        if (leader) mbar_arrive(BAR(B_KVFREE));
        if (wg == 0 && warp < 3) {
#pragma unroll 1
          for (int it = 0; it < SPIN; it++) {
            bool ok = true;
#pragma unroll
            for (int p = 0; p < 8; p++) ld_rec16_stale(a[p], src + p * 384, tag);
#pragma unroll
            for (int p = 0; p < 8; p++) ok = ok && a[p].w == tag;
            if (__all_sync(0xffffffffu, ok)) break;
          }
          float v[6] = {0.f, 0.f, 0.f, 0.f, 0.f, 0.f};
#pragma unroll
          for (int p = 0; p < 8; p++) {
            v[0] += bf_lo(a[p].x); v[1] += bf_hi(a[p].x); v[2] += bf_lo(a[p].y); v[3] += bf_hi(a[p].y); v[4] += bf_lo(a[p].z); v[5] += bf_hi(a[p].z);
          }
          st_rec16(&g_kvr[2 * hp + (lane >> 4)][warp][rbk * 16 + (lane & 15)], pack_bf16(v[0], v[1]), pack_bf16(v[2], v[3]), pack_bf16(v[4], v[5]), tag);
        }
      }
    }
    const uint32_t stg = sb + wg * 8192;
    float s0 = 0.f, q0 = 0.f, d0 = 0.f, s1 = 0.f, q1 = 0.f, d1 = 0.f;
    {
      MMA_IDS
      const unsigned tag = lds_u(sb + OFF_RED + 4);
      const uint32_t t3 = tag % 3u + 1u, tg = (t3 & 1u) | ((t3 & 2u) << 15);
      const int ln = __shfl_sync(0xffffffffu, lane, lane);
      uint4* const og = &g_o[rb][0][wg * 4 + warp][0][ln];
      const uint32_t af = sb + (uint32_t)(wg * 4 + warp) * 2048 + ln * 16;
      float acc[64];
      auto tile_addr = [&]() {
        uint32_t l = ln;
        asm volatile("" : "+r"(l));
        return stg + (uint32_t)warp * 2048 + (l & 15) * 128 + (((l >> 4) ^ (l & 7)) << 4);
      };
      auto add_x = [&]() {
        mbar_wait(BAR(B_FQ + 14));
        mbar_wait(BAR(B_FQ + 15));
        const uint64_t da = mk_desc(sb + OFF_EYE + 384, 512, 128, 0), db = mk_desc(stg + SLOT, 7 * SLOT, 4096, 1);
        wg_fence();
#pragma unroll
        for (int s = 0; s < 4; s++) wg_n128<0, 1>(acc, da - s * 8, db + s * 64, s != 0);
        wg_commit();
      };
      auto announce = [&]() {
        if (FLAGB) { if (warp == FLAGW) bar_sync(4 + wg, 128); else bar_arrive(4 + wg, 128); }
        if (warp == FLAGW && ln < 8) asm volatile("st.relaxed.gpu.global.u32 [%0], %1;" :: "l"(&g_oflag[rb][ln][cb * 2 + wg].x), "r"(tag) : "memory");
      };
      auto send = [&](const uint32_t (&a)[16], uint32_t flip, uint32_t slot, int c) {
#pragma unroll
        for (int i = 0; i < 4; i++) sts_u4(af + slot * SLOT + i * 512, a[4 * i] ^ flip, a[4 * i + 1], a[4 * i + 2], a[4 * i + 3]);
        fence_async_smem();
        __syncwarp();
        if (ln == 0) {
          asm volatile("cp.async.bulk.global.shared::cta.bulk_group [%0], [%1], 2048;" :: "l"(og + cb * 2048 + c * 1024), "r"(af + slot * SLOT) : "memory");
          asm volatile("cp.async.bulk.commit_group;" ::: "memory");
        }
        __syncwarp();
      };
      const bool early = !((LATE >> cb) & 1);
      uint32_t A[2][16];
      const bool lead = warp == 0 && ln == 0;
      {
        const float sc0 = lds_f(sb + OFF_RSTAT + (uint32_t)(wg * 64 + lr) * 4) * L2E, sc1 = lds_f(sb + OFF_RSTAT + (uint32_t)(wg * 64 + lr + 8) * 4) * L2E;
        auto logits = [&](float (&p0)[16], float (&p1)[16], int c) {
          const uint64_t dq = mk_desc(sb + (10 + c) * SLOT + wg * 8192, 16, 1024, 1), dw = mk_desc(sb + OFF_PHIQ + c * 4096, 16, 512, 2);
          mbar_wait(BAR(B_QD + c));
          wg_fence();
          wg_n32<0, 1>(p0, dq, dw, 0);
          wg_n32<0, 1>(p1, dq + 4, dw + 128, 0);
          wg_n32<0, 1>(p0, dq + 2, dw + 64, 1);
          wg_n32<0, 1>(p1, dq + 6, dw + 192, 1);
          wg_commit();
        };
        auto norm = [&](float (&p)[16], uint32_t (&f)[16], const float (&d)[4]) {
          if (warp_fails(feature_norm<false>(f, d) < FAST_LIMIT)) feature_shifted(p, p, sc0, sc1, f);
        };
        auto apply = [&](float (&u)[20], const uint32_t (&f)[16], int h) {
          const uint64_t d = mk_desc(sb + 12 * SLOT + h * 4096, SLOT - h * 4096 + h * 16, 512, 2);
          wg_fence();
#pragma unroll
          for (int s = 0; s < 4; s++) wg_n40_rs<1>(u, f[4 * s], f[4 * s + 1], f[4 * s + 2], f[4 * s + 3], d + s * 64, s != 0);
          wg_commit();
        };
        float pa[16], pb[16], pc[16], pd[16], u0[20], u1[20], u2[20], u3[20], da[4], db[4];
        uint32_t f0[16], f1[16], f2[16], f3[16];
        uint4* const od = og + cb * 2048;
        logits(pa, pb, 0);
        wg_wait<0>();
        feature_exp(pa, sc0, sc1, f0, da, sum_b(sb));
        if (PIN & 64) pin_order();
        logits(pc, pd, 1);
        feature_exp(pb, sc0, sc1, f1, db, sum_b(sb));
        wg_wait<1>();
        norm(pa, f0, da);
        if (QORD == 2) {
          feature_exp(pc, sc0, sc1, f2, da, sum_b(sb));
          wg_wait<1>();
          norm(pb, f1, db);
          wg_wait<0>();
          if (lead) mbar_arrive(BAR(B_QREAD));
          norm(pc, f2, da);
          mbar_wait(BAR(B_KVRDY));
          apply(u0, f0, 0);
          apply(u1, f1, 1);
          wg_wait<1>();
          attn_out(u0, tg, &A[0][0], od, early && !(EB & 2));
          if (FLAGP == 2 && early && (EB & 6) != 2) announce();
          wg_wait<0>();
          apply(u2, f2, 2);
          attn_out(u1, tg, &A[0][8], od + 64, early && !(EB & 2));
          if (FLAGP == 3 && early) announce();
          if (early && (EB & 2)) {
            send(A[0], 0u, 11, 0);
            if (!(EB & 4)) announce();
          }
          if (PIN & 16) pin_order();
          feature_exp(pd, sc0, sc1, f3, db, sum_b(sb));
          wg_wait<1>();
          attn_out(u2, tg, &A[1][0], od + 1024, !LPUB);
          wg_wait<0>();
          norm(pd, f3, db);
          apply(u3, f3, 3);
          add_x();
          wg_wait<1>();
        } else {
          wg_wait<0>();
          if (lead) mbar_arrive(BAR(B_QREAD));
          norm(pb, f1, db);
          mbar_wait(BAR(B_KVRDY));
          apply(u0, f0, 0);
          apply(u1, f1, 1);
          if (QORD == 3) {
            feature_exp(pc, sc0, sc1, f2, da, sum_b(sb));
            wg_wait<1>();
            attn_out(u0, tg, &A[0][0], od, early);
            if (early) announce();
            attn_out(u1, tg, &A[0][8], od + 64, early);
          } else {
            wg_wait<1>();
            attn_out(u0, tg, &A[0][0], od, early);
            if (early) announce();
            wg_wait<0>();
            attn_out(u1, tg, &A[0][8], od + 64, early);
            if (PIN & 16) pin_order();
            feature_exp(pc, sc0, sc1, f2, da, sum_b(sb));
          }
          if (PIN & 16) pin_order();
          feature_exp(pd, sc0, sc1, f3, db, sum_b(sb));
          wg_wait<1>();
          norm(pc, f2, da);
          apply(u2, f2, 2);
          wg_wait<1>();
          norm(pd, f3, db);
          apply(u3, f3, 3);
          wg_wait<1>();
          attn_out(u2, tg, &A[1][0], od + 1024, !LPUB);
          add_x();
          wg_wait<1>();
        }
        if (lead) mbar_arrive(BAR(B_XDONE));
        attn_out(u3, tg, &A[1][8], od + 1088, !LPUB);
        if (!early) {
          if (EB & 1) send(A[0], 0u, 11, 0);
          else
#pragma unroll
          for (int i = 0; i < 4; i++) st_rec16(od + i * 32, A[0][4 * i], A[0][4 * i + 1], A[0][4 * i + 2], A[0][4 * i + 3]);
          announce();
        }
      }
      auto take = [&](uint32_t (&a)[16], int j) {
        const uint32_t s = af + tab4(PC_ASLOTS, j) * SLOT;
#pragma unroll
        for (int i = 0; i < 4; i++) {
          const uint4 v = lds_u4(s + i * 512);
          a[4 * i] = v.x; a[4 * i + 1] = v.y; a[4 * i + 2] = v.z; a[4 * i + 3] = v.w;
        }
      };
      auto check = [&](uint32_t (&a)[16], int j) {
        if (PIN & 256) pin_order();
#pragma unroll
        for (int i = 0; i < 4; i++) a[4 * i] ^= tg;
        if (!(SKIP & 2) && warp_fails((((a[0] | a[4]) | (a[8] | a[12])) & OTAG) == 0)) {
          const uint4* p = og + pc_chunk(j, cb) * 1024;
#pragma unroll 1
          for (int it = 0; it < SPIN; it++) {
#pragma unroll
            for (int i = 0; i < 4; i++) {
              const uint4 v = ld_rec16(p + i * 32);
              a[4 * i] = v.x ^ tg; a[4 * i + 1] = v.y; a[4 * i + 2] = v.z; a[4 * i + 3] = v.w;
            }
            if (__all_sync(0xffffffffu, (((a[0] | a[4]) | (a[8] | a[12])) & OTAG) == 0)) break;
          }
        }
      };
#pragma unroll
      for (int i = 0; i < 4; i++) A[0][4 * i] ^= tg;
      {
        uint32_t bt = (uint32_t)mk_desc(sb + 3 * SLOT, 8192, 1024, 1);
        const uint32_t bl = bt + 4096;
        uint2 dl = make_uint2(0u, 0u), dn = dl;
#pragma unroll 1
        for (int m = 0; m < 16; m += 4) {
#pragma unroll
          for (int e = 0; e < 4; e++) {
            const int j = m + e;
            const uint32_t (&a)[16] = A[e & 1];
            mbar_wait(BAR(B_FB + j) + dl.x);
            const uint64_t db = (mk_desc(0, 0, 1024, 1)) | (bt + dl.y);
            wg_fence();
#pragma unroll
            for (int kk = 0; kk < 4; kk++) {
              wg_n128_rs<1>(acc, a[4 * kk], a[4 * kk + 1], a[4 * kk + 2], a[4 * kk + 3], db + kk * 128, 1);
              if (kk == PSPL) {
                wg_commit();
                wg_wait<1>();
                if (lead) mbar_arrive(BAR(j ? B_DC + j - 1 : B_XREAD));
                if (LPUB == 3 && e == 2 && m == 0) {
#pragma unroll
                  for (int i = 0; i < 4; i++) st_rec16(og + cb * 2048 + 1024 + i * 32, A[1][4 * i] ^ tg, A[1][4 * i + 1], A[1][4 * i + 2], A[1][4 * i + 3]);
                }
                if (e || m) {
                  if (e < 3 || m < 12) mbar_wait<1>(BAR(B_FKV + j + 1));
                  take(A[(e & 1) ^ 1], (e + 1) & 3);
                  if (DYN) dn = lds_u2(sb + OFF_RED + 72 + j * 8);
                }
                else if (LPUB == 1) {
#pragma unroll
                  for (int i = 0; i < 4; i++) st_rec16(og + cb * 2048 + 1024 + i * 32, A[1][4 * i], A[1][4 * i + 1], A[1][4 * i + 2], A[1][4 * i + 3]);
                }
                if (LPUB >= 4 && LPUB < 6 && e == LPUB - 4 && m == 0) {
                  mbar_wait(BAR(B_XDONE));
                  send(A[1], e ? tg : 0u, 12, 1);
                }
                if (e == (EB ? 0 : 3)) asm volatile("cp.async.bulk.wait_group.read 0;" ::: "memory");
                if (LPUB == 2 && e == 1 && m == 0) {
#pragma unroll
                  for (int i = 0; i < 4; i++) st_rec16(og + cb * 2048 + 1024 + i * 32, A[1][4 * i] ^ tg, A[1][4 * i + 1], A[1][4 * i + 2], A[1][4 * i + 3]);
                }
                wg_fence();
              }
            }
            wg_commit();
            if (LPUB >= 6 && e == LPUB - 6 && m == 0) {
              mbar_wait(BAR(B_XDONE));
              send(A[1], e ? tg : 0u, 12, 1);
            }
            asm volatile("{\n.reg .pred p;\nsetp.eq.u32 p, %0, %1;\nadd.u32 %0, %0, 1024;\n@p sub.u32 %0, %0, 5120;\n}\n" : "+r"(bt) : "r"(bl));
            dl = dn;
            if (e < 3 || m < 12) check(A[(e & 1) ^ 1], j + 1 + ((int)dl.x >> 3));
          }
        }
      }
      mbar_wait(BAR(B_RESET2));
      wg_wait<0>();
      if (leader) mbar_arrive(BAR(B_DC + 15));
#pragma unroll
      for (int j = 0; j < 16; j++) {
        const float2 w = lds_f2(sb + OFF_WR + (uint32_t)(j * 8 + c2) * 4);
        float a = acc[4 * j], c = acc[4 * j + 1];
        s0 += a + c; q0 = fmaf(a, a, fmaf(c, c, q0)); d0 = fmaf(a, w.x, fmaf(c, w.y, d0));
        a = acc[4 * j + 2]; c = acc[4 * j + 3];
        s1 += a + c; q1 = fmaf(a, a, fmaf(c, c, q1)); d1 = fmaf(a, w.x, fmaf(c, w.y, d1));
      }
#pragma unroll
      for (int m = 1; m <= 2; m <<= 1) {
        s0 += __shfl_xor_sync(0xffffffffu, s0, m); q0 += __shfl_xor_sync(0xffffffffu, q0, m); d0 += __shfl_xor_sync(0xffffffffu, d0, m);
        s1 += __shfl_xor_sync(0xffffffffu, s1, m); q1 += __shfl_xor_sync(0xffffffffu, q1, m); d1 += __shfl_xor_sync(0xffffffffu, d1, m);
      }
      if ((lane & 2) == 0) {
        const bool hi = lane & 1;
        st_rec16(&g_hstat[rb][cb][wg * 64 + lr + (hi ? 8 : 0)], __float_as_uint(hi ? s1 : s0), __float_as_uint(hi ? q1 : q0), __float_as_uint(hi ? d1 : d0), lds_u(sb + OFF_RED + 4));
      }
      const uint32_t ha = tile_addr();
#pragma unroll
      for (int jj = 0; jj < 8; jj++)
        stsm_x4((ha ^ (32 * (jj & 3))) + (jj >> 2) * 2 * SLOT,
                pack_bf16(acc[8 * jj], acc[8 * jj + 1]), pack_bf16(acc[8 * jj + 2], acc[8 * jj + 3]),
                pack_bf16(acc[8 * jj + 4], acc[8 * jj + 5]), pack_bf16(acc[8 * jj + 6], acc[8 * jj + 7]));
    }
    asm volatile("setmaxnreg.dec.sync.aligned.u32 32;");
    {
    MMA_IDS
    const int grow0 = rb * 128 + wg * 64 + lr;
    const unsigned tag = lds_u(sb + OFF_RED + 4);
    uint32_t key;
    {
      const int trow = wg * 64 + lr;
      uint4 r00, r01, r10, r11;
      r00 = r01 = r10 = r11 = make_uint4(0u, 0u, 0u, tag - 1);
#pragma unroll 1
      for (int it = 0; it < SPIN; it++) {
        if (HST) {
          ld_rec16_stale(r00, &g_hstat[rb][c2][trow], tag); ld_rec16_stale(r01, &g_hstat[rb][c2 + 1][trow], tag);
          ld_rec16_stale(r10, &g_hstat[rb][c2][trow + 8], tag); ld_rec16_stale(r11, &g_hstat[rb][c2 + 1][trow + 8], tag);
        } else {
        r00 = ld_rec16(&g_hstat[rb][c2][trow]); r01 = ld_rec16(&g_hstat[rb][c2 + 1][trow]);
        r10 = ld_rec16(&g_hstat[rb][c2][trow + 8]); r11 = ld_rec16(&g_hstat[rb][c2 + 1][trow + 8]);
        }
        if (__all_sync(0xffffffffu, r00.w == tag && r01.w == tag && r10.w == tag && r11.w == tag)) break;
      }
      s0 = __uint_as_float(r00.x) + __uint_as_float(r01.x); q0 = __uint_as_float(r00.y) + __uint_as_float(r01.y); d0 = __uint_as_float(r00.z) + __uint_as_float(r01.z);
      s1 = __uint_as_float(r10.x) + __uint_as_float(r11.x); q1 = __uint_as_float(r10.y) + __uint_as_float(r11.y); d1 = __uint_as_float(r10.z) + __uint_as_float(r11.z);
#pragma unroll
      for (int m = 1; m <= 2; m <<= 1) {
        s0 += __shfl_xor_sync(0xffffffffu, s0, m); q0 += __shfl_xor_sync(0xffffffffu, q0, m); d0 += __shfl_xor_sync(0xffffffffu, d0, m);
        s1 += __shfl_xor_sync(0xffffffffu, s1, m); q1 += __shfl_xor_sync(0xffffffffu, q1, m); d1 += __shfl_xor_sync(0xffffffffu, d1, m);
      }
      if (KGATE == 2 && tid == 0) mbar_arrive(BAR(B_KEY));
      const float sumw = lds_f(sb + OFF_RED);
      const float mean0 = s0 * (1.f / DM), mean1 = s1 * (1.f / DM);
      const float rstd0 = rsq(fmaxf(q0 * (1.f / DM) - mean0 * mean0, 0.f) + 1e-5f);
      const float rstd1 = rsq(fmaxf(q1 * (1.f / DM) - mean1 * mean1, 0.f) + 1e-5f);
      const uint32_t rr = pack_bf16(rstd0 * (d0 - mean0 * sumw), rstd1 * (d1 - mean1 * sumw));
      uint32_t u0 = rr & 0xFFFFu, u1 = rr >> 16;
      u0 = (u0 & 0x8000u) ? (~u0 & 0xFFFFu) : (u0 | 0x8000u);
      u1 = (u1 & 0x8000u) ? (~u1 & 0xFFFFu) : (u1 | 0x8000u);
      const uint32_t k0 = (u0 << 16) | (uint32_t)(0xFFFF - grow0), k1 = (u1 << 16) | (uint32_t)(0xFFFF - (grow0 + 8));
      key = __reduce_max_sync(0xffffffffu, max(k0, k1));
      if (lane == 0) sts_u(sb + OFF_RED + 16 + (uint32_t)(wg * 4 + warp) * 4, key);
      if ((lane & 3) == 0) {
        sts_f2(sb + OFF_RSTAT + trow * 8, rstd0, -mean0 * rstd0);
        sts_f2(sb + OFF_RSTAT + (trow + 8) * 8, rstd1, -mean1 * rstd1);
      }
      bar_sync(1, 256);
      const uint4 ka = lds_u4(sb + OFF_RED + 16), kb = lds_u4(sb + OFF_RED + 32);
      key = max(max(max(ka.x, ka.y), max(ka.z, ka.w)), max(max(kb.x, kb.y), max(kb.z, kb.w)));
    }
    if (KREP) { if (tid < 16) st_rec8(&g_key[cb][tid][rb], key, tag); }
    else if (tid == 0) st_rec8(&g_key[cb][0][rb * 4], key, tag);
    if (KGATE == 1 && tid == 0) mbar_arrive(BAR(B_KEY));
    const int crow = (0xFFFF - (int)(key & 0xFFFFu)) & 127;
    const bool own = (crow >> 4) == wg * 4 + warp;
    uint32_t co0 = 0, co1 = 0;
    if (own) {
      const uint32_t r = (uint32_t)(crow & 63);
      const float2 st = lds_f2(sb + OFF_RSTAT + crow * 8);
      const uint32_t a = stg + r * 128 + ((((uint32_t)lane >> 2) ^ (r & 7)) << 4) + (lane & 3) * 4;
      const uint32_t h0 = lds_u(a), h1 = lds_u(a + 2 * SLOT);
      uint32_t n0, n1;
      co0 = ln_res(h0, st.x, st.y, n0); co1 = ln_res(h1, st.x, st.y, n1);
      st_rec8(&g_candx[rb][cb * 64 + lane], n0, tag);
      st_rec8(&g_candx[rb][cb * 64 + 32 + lane], n1, tag);
      st_rec16(&g_cand[rb][cb * 64 + lane], n0, h0, key, tag);
      st_rec16(&g_cand[rb][cb * 64 + 32 + lane], n1, h1, key, tag);
    }
    __nv_bfloat16* ob = P.out + (size_t)(rb * 128 + wg * 64) * DM + cb * 128;
#pragma unroll 4
    for (int i = 0; i < 8; i++) {
      const uint32_t r = (uint32_t)(warp * 16 + (i & 3) * 4 + (lane >> 3));
      const uint32_t a = stg + (i >> 2) * 2 * SLOT + r * 128 + ((((uint32_t)lane & 7) ^ (r & 7)) << 4);
      const uint4 h = lds_u4(a);
      const float2 st = lds_f2(sb + OFF_RSTAT + (wg * 64 + r) * 8);
      uint32_t n;
      uint4 o;
      o.x = ln_res(h.x, st.x, st.y, n); o.y = ln_res(h.y, st.x, st.y, n); o.z = ln_res(h.z, st.x, st.y, n); o.w = ln_res(h.w, st.x, st.y, n);
      if (!own) sts_u4(a, o.x, o.y, o.z, o.w);
      else if ((int)(wg * 64 + r) != crow) stg16(ob + (size_t)r * DM + (i >> 2) * 64 + (lane & 7) * 8, o);
      if ((i & 3) == 3) {
        fence_async_smem();
        __syncwarp();
        if (OUTG == 1 ? i == 7 : OUTG == 2 ? i == 3 : OUTG == 3 ? i == 7 || wg : OUTG == 4 ? i == 7 && wg : false) mbar_wait(BAR(B_ROW));
        if (elect()) {
          if (!own) tma_store_2d(&P.mOut, stg + (i >> 2) * 2 * SLOT + warp * 2048, cb * 128 + (i >> 2) * 64, rb * 128 + wg * 64 + warp * 16);
          asm volatile("cp.async.bulk.commit_group;" ::: "memory");
        }
        __syncwarp();
      }
    }
    if (elect()) {
      asm volatile("cp.async.bulk.wait_group.read 0;" ::: "memory");
    }
    __syncwarp();
    if (own) {
      uint2 v;
#pragma unroll 1
      for (int it = 0; it < SPIN; it++) {
        v = ld_rec8(KREP ? &g_key[cb][rb][lane & 15] : &g_key[cb][0][(lane & 15) * 4]);
        if (__all_sync(0xffffffffu, v.y == tag)) break;
      }
      if (__reduce_max_sync(0xffffffffu, v.x) != key) {
        uint32_t* op = reinterpret_cast<uint32_t*>(ob + (size_t)(crow & 63) * DM);
        op[lane] = co0; op[32 + lane] = co1;
      }
    }
    }
  }
#undef BAR
}

typedef CUresult (*EncodeFn)(CUtensorMap*, CUtensorMapDataType, cuuint32_t, void*, const cuuint64_t*, const cuuint64_t*,
                             const cuuint32_t*, const cuuint32_t*, CUtensorMapInterleave, CUtensorMapSwizzle,
                             CUtensorMapL2promotion, CUtensorMapFloatOOBfill);

void make_map(EncodeFn fn, CUtensorMap* m, const void* ptr, uint64_t cols, uint64_t rows, uint32_t bc, uint32_t br, CUtensorMapSwizzle swz,
              uint32_t parts = 0, uint32_t bp = 1) {
  cuuint64_t dims[3] = {parts ? cols / parts : cols, rows, parts};
  cuuint64_t strides[2] = {cols * 2, dims[0] * 2};
  cuuint32_t box[3] = {bc, br, bp};
  cuuint32_t es[3] = {1, 1, 1};
  fn(m, CU_TENSOR_MAP_DATA_TYPE_BFLOAT16, parts ? 3 : 2, const_cast<void*>(ptr), dims, strides, box, es, CU_TENSOR_MAP_INTERLEAVE_NONE, swz,
     CU_TENSOR_MAP_L2_PROMOTION_L2_128B, CU_TENSOR_MAP_FLOAT_OOB_FILL_NONE);
}

}

extern "C" void kernel_launch(void* const* d_in, const int* in_sizes, int n_in, void* d_out, int out_size) {
  static EncodeFn fn = nullptr;
  if (!fn) {
    cudaDriverEntryPointQueryResult q;
    cudaGetDriverEntryPoint("cuTensorMapEncodeTiled", (void**)&fn, cudaEnableDefault, &q);
    cudaFuncSetAttribute(fused_kernel, cudaFuncAttributeMaxDynamicSharedMemorySize, SMEM_BYTES);
  }
  Params P;
  P.x = (const __nv_bfloat16*)d_in[0];
  P.wqkv = (const __nv_bfloat16*)d_in[1];
  const __nv_bfloat16* wphi = (const __nv_bfloat16*)d_in[2];
  P.wo = (const __nv_bfloat16*)d_in[3];
  P.wr = (const __nv_bfloat16*)d_in[5];
  P.wg = (const __nv_bfloat16*)d_in[6];
  P.wu = (const __nv_bfloat16*)d_in[7];
  P.wd = (const __nv_bfloat16*)d_in[8];
  P.out = (__nv_bfloat16*)d_out;
  make_map(fn, &P.mX, P.x, DM, SEQ, 64, 128, CU_TENSOR_MAP_SWIZZLE_128B);
  make_map(fn, &P.mW, P.wqkv, 3 * DM, DM, 64, 64, CU_TENSOR_MAP_SWIZZLE_128B);
  make_map(fn, &P.mWo, P.wo, DM, DM, 64, 64, CU_TENSOR_MAP_SWIZZLE_128B);
  make_map(fn, &P.mPhi, wphi, 32, 1024, 32, 64, CU_TENSOR_MAP_SWIZZLE_64B);
  make_map(fn, &P.mWg, P.wg, FF, DM, 32, 256, CU_TENSOR_MAP_SWIZZLE_64B, 1);
  make_map(fn, &P.mWu, P.wu, FF, DM, 32, 256, CU_TENSOR_MAP_SWIZZLE_64B, 1);
  make_map(fn, &P.mWs, P.wqkv, 3 * DM, DM, 32, 64, CU_TENSOR_MAP_SWIZZLE_NONE);
  make_map(fn, &P.mWd, P.wd, DM, FF, 64, 32, CU_TENSOR_MAP_SWIZZLE_128B, 16, 4);
  make_map(fn, &P.mOut, P.out, DM, SEQ, 64, 16, CU_TENSOR_MAP_SWIZZLE_128B);
  make_map(fn, &P.mWgT, P.wg, FF, DM, 8, TROWS, CU_TENSOR_MAP_SWIZZLE_NONE);
  make_map(fn, &P.mWuT, P.wu, FF, DM, 8, TROWS, CU_TENSOR_MAP_SWIZZLE_NONE);
  make_map(fn, &P.mWdT, P.wd, 64, FF * 16, 8, TROWS, CU_TENSOR_MAP_SWIZZLE_NONE);
  fused_kernel<<<NCTA, NTHREADS, SMEM_BYTES, cudaStreamPerThread>>>(P);
}
```

```cpp
#include <cuda_runtime.h>
#include <cuda_bf16.h>
#include <cuda.h>
#include <stdint.h>

namespace {

constexpr int SEQ = 2048, DM = 1024, FF = 3584;
constexpr int NCTA = 128, NTHREADS = 512, NFFN = 112;
constexpr int SPIN = 1 << 17;
constexpr int RSTQ = 3;
constexpr int PSPL = 1;
constexpr int PIN = 145;
constexpr int RCPG = 4;
constexpr int THR = 1;
constexpr int QORD = 2;
constexpr int KH2 = 0;
constexpr int KSH = 0;
constexpr int LPUB = 5;
constexpr int PAD = 0;
constexpr int GATE = 6;
constexpr int FLAGW = 3;
constexpr int LATE = 0x78;
constexpr int SXN = 4;
constexpr int SX0 = 2;
constexpr int SXD = 2;
constexpr int CSW = 0x65431234;
constexpr int SKIP = 0;
constexpr int WEF = 0;
constexpr int TROWS = 16;
constexpr int DYN = 1;
constexpr int MAP = 1;
constexpr int OUTG = 1;
constexpr int EB = 0;
constexpr int FLAGP = 2;
constexpr int FLAGB = 0;
constexpr int QD = 5;
constexpr int U3L = 2;
constexpr int KSPL = 0;
constexpr int K1E = 1;
constexpr int FINE = 1;
constexpr int K2W = 2;
constexpr int K3B = 161;
constexpr int K1M = 0;
constexpr int QSPL = 2;
constexpr int QW2 = 1;
constexpr int SQN = 4;
constexpr int TREG = 32;
constexpr int DORD = 8;
constexpr int YDLY = 0;
constexpr int KSUM = 1;
constexpr int GSPEC = 1;
constexpr int QPIN = 1;

constexpr uint32_t SLOT = 16384;
constexpr uint32_t OFF_MISC = 13 * SLOT;
constexpr uint32_t OFF_PHIK = OFF_MISC;
constexpr uint32_t OFF_PHIQ = OFF_MISC + 4096;
constexpr uint32_t OFF_ONES = OFF_MISC + 12288;
constexpr uint32_t OFF_RSTAT = OFF_MISC + 13312;
constexpr uint32_t OFF_EYE = OFF_MISC + 14336;
constexpr uint32_t OFF_CS = OFF_MISC + 15360;
constexpr uint32_t OFF_WR = OFF_MISC + 16384;
constexpr uint32_t OFF_BAR = OFF_MISC + 16896;
constexpr uint32_t OFF_RED = OFF_MISC + 18304;
constexpr uint32_t OFF_SEL = OFF_RED + 320;
constexpr uint32_t OFF_TCH = OFF_MISC + 19072;
constexpr uint32_t SMEM_BYTES = OFF_MISC + 19456;

enum {
  B_FKV = 0, B_DKV = 16, B_FQ = 32, B_DQ = 48,
  B_PHI = 64, B_RESET = 65, B_RESET2 = 66, B_ROW = 67, B_FX = 68, B_KEY = 69, B_TCH = 70, B_REL = 72,
  B_FB = 80, B_DC = 96, B_QD = 112, B_STAT = 114,
  B_KVFREE = 120, B_QGO = 121, B_QGO2 = 122, B_CSD = 123, B_XDONE = 124, B_QREAD = 125, B_XREAD = 126, B_KVRDY = 127,
  B_FS = 128, B_FW = 144, B_F0 = 160
};
constexpr unsigned long long MISC_COUNTS = 0x0502020203020202ull;

struct Params {
  CUtensorMap mX2, mW2, mX, mW, mWo, mPhi, mWg, mWu, mWs, mWd, mOut, mWgT, mWuT, mWdT;
  const __nv_bfloat16 *x, *wqkv, *wo, *wr, *wg, *wu, *wd;
  __nv_bfloat16* out;
};

__device__ unsigned g_epoch;
__device__ __align__(128) uint4 g_rowstat[SEQ];
__device__ __align__(128) uint2 g_colsum[4][3 * DM];
__device__ __align__(128) uint4 g_kvp[32][8][3][128];
__device__ __align__(128) uint4 g_kvr[32][3][128];
__device__ __align__(128) uint4 g_o[16][18][8][4][32];
__device__ __align__(128) uint4 g_oflag[16][8][16];
__device__ __align__(128) uint2 g_key[8][16][16];
__device__ __align__(128) uint4 g_ypart[128][NFFN][2];

__device__ __forceinline__ uint32_t smem_u32(const void* p) { return (uint32_t)__cvta_generic_to_shared(p); }
__device__ __forceinline__ bool elect() {
  uint32_t p;
  asm volatile("{\n.reg .pred P;\nelect.sync _|P, 0xffffffff;\nselp.u32 %0, 1, 0, P;\n}\n" : "=r"(p));
  return p != 0;
}
__device__ __forceinline__ void mbar_init(uint32_t bar, uint32_t cnt) { asm volatile("mbarrier.init.shared::cta.b64 [%0], %1;" :: "r"(bar), "r"(cnt)); }
__device__ __forceinline__ void mbar_expect_tx(uint32_t bar, uint32_t bytes) { asm volatile("mbarrier.arrive.expect_tx.shared::cta.b64 _, [%0], %1;" :: "r"(bar), "r"(bytes) : "memory"); }
__device__ __forceinline__ void mbar_arrive(uint32_t bar) { asm volatile("mbarrier.arrive.shared::cta.b64 _, [%0];" :: "r"(bar) : "memory"); }
template <int PARITY = 0>
__device__ __forceinline__ void mbar_wait(uint32_t bar) {
#pragma unroll 1
  for (int it = 0; it < SPIN; it++) {
    uint32_t ok;
    asm volatile("{\n.reg .pred p;\nmbarrier.try_wait.parity.shared::cta.b64 p, [%1], %2;\nselp.u32 %0, 1, 0, p;\n}\n" : "=r"(ok) : "r"(bar), "n"(PARITY) : "memory");
    if (ok) break;
  }
}
__device__ __forceinline__ void tma_load_2d(uint32_t dst, const CUtensorMap* m, uint32_t bar, int c0, int c1) {
  asm volatile("cp.async.bulk.tensor.2d.shared::cluster.global.mbarrier::complete_tx::bytes [%0], [%1, {%3, %4}], [%2];"
    :: "r"(dst), "l"(m), "r"(bar), "r"(c0), "r"(c1) : "memory");
}
__device__ __forceinline__ void tma_load_2d_ef(uint32_t dst, const CUtensorMap* m, uint32_t bar, int c0, int c1) {
  uint64_t pol;
  asm("createpolicy.fractional.L2::evict_first.b64 %0, 1.0;" : "=l"(pol));
  asm volatile("cp.async.bulk.tensor.2d.shared::cluster.global.mbarrier::complete_tx::bytes.L2::cache_hint [%0], [%1, {%3, %4}], [%2], %5;"
    :: "r"(dst), "l"(m), "r"(bar), "r"(c0), "r"(c1), "l"(pol) : "memory");
}
__device__ __forceinline__ void tma_load_3d_ef(uint32_t dst, const CUtensorMap* m, uint32_t bar, int c0, int c1, int c2) {
  uint64_t pol;
  asm("createpolicy.fractional.L2::evict_first.b64 %0, 1.0;" : "=l"(pol));
  asm volatile("cp.async.bulk.tensor.3d.shared::cluster.global.mbarrier::complete_tx::bytes.L2::cache_hint [%0], [%1, {%3, %4, %5}], [%2], %6;"
    :: "r"(dst), "l"(m), "r"(bar), "r"(c0), "r"(c1), "r"(c2), "l"(pol) : "memory");
}
template <int EF> __device__ __forceinline__ void tma_load_w(uint32_t dst, const CUtensorMap* m, uint32_t bar, int c0, int c1) {
  if (EF) tma_load_2d_ef(dst, m, bar, c0, c1); else tma_load_2d(dst, m, bar, c0, c1);
}
__device__ __forceinline__ void tma_store_2d(const CUtensorMap* m, uint32_t src, int c0, int c1) {
  asm volatile("cp.async.bulk.tensor.2d.global.shared::cta.bulk_group [%0, {%2, %3}], [%1];"
    :: "l"(m), "r"(src), "r"(c0), "r"(c1) : "memory");
}
__device__ __forceinline__ void cp_async16(uint32_t dst, const void* src) { asm volatile("cp.async.cg.shared.global [%0], [%1], 16;" :: "r"(dst), "l"(src) : "memory"); }
__device__ __forceinline__ void cp_commit() { asm volatile("cp.async.commit_group;" ::: "memory"); }
template <int N> __device__ __forceinline__ void cp_wait() { asm volatile("cp.async.wait_group %0;" :: "n"(N) : "memory"); }
__device__ __forceinline__ void l2_prefetch(const void* src, uint32_t bytes) {
  asm volatile("cp.async.bulk.prefetch.L2.global [%0], %1;" :: "l"(src), "r"(bytes) : "memory");
}
__device__ __forceinline__ void wg_fence() { asm volatile("wgmma.fence.sync.aligned;" ::: "memory"); }
__device__ __forceinline__ void wg_commit() { asm volatile("wgmma.commit_group.sync.aligned;" ::: "memory"); }
template <int N> __device__ __forceinline__ void wg_wait() { asm volatile("wgmma.wait_group.sync.aligned %0;" :: "n"(N) : "memory"); }
__device__ __forceinline__ void fence_async_smem() { asm volatile("fence.proxy.async.shared::cta;" ::: "memory"); }
__device__ __forceinline__ void bar_sync(int id, int n) { asm volatile("bar.sync %0, %1;" :: "r"(id), "r"(n) : "memory"); }
__device__ __forceinline__ void bar_arrive(int id, int n) { asm volatile("bar.arrive %0, %1;" :: "r"(id), "r"(n) : "memory"); }
__device__ __forceinline__ uint64_t mk_desc(uint32_t addr, uint32_t lbo, uint32_t sbo, uint32_t swz) {
  return (uint64_t)((addr & 0x3FFFF) >> 4) | ((uint64_t)((lbo & 0x3FFFF) >> 4) << 16) | ((uint64_t)(sbo >> 4) << 32) | ((uint64_t)swz << 62);
}
__device__ __forceinline__ void stsm_x4(uint32_t addr, uint32_t r0, uint32_t r1, uint32_t r2, uint32_t r3) {
  asm volatile("stmatrix.sync.aligned.m8n8.x4.shared.b16 [%0], {%1, %2, %3, %4};" :: "r"(addr), "r"(r0), "r"(r1), "r"(r2), "r"(r3) : "memory");
}
__device__ __forceinline__ void ldsm_x4(uint32_t& r0, uint32_t& r1, uint32_t& r2, uint32_t& r3, uint32_t addr) {
  asm volatile("ldmatrix.sync.aligned.m8n8.x4.shared.b16 {%0, %1, %2, %3}, [%4];" : "=r"(r0), "=r"(r1), "=r"(r2), "=r"(r3) : "r"(addr) : "memory");
}
__device__ __forceinline__ void ldsm_x4_t(uint32_t (&r)[4], uint32_t addr) {
  asm volatile("ldmatrix.sync.aligned.m8n8.x4.trans.shared.b16 {%0, %1, %2, %3}, [%4];" : "=r"(r[0]), "=r"(r[1]), "=r"(r[2]), "=r"(r[3]) : "r"(addr) : "memory");
}
__device__ __forceinline__ void mma_bf16(float* d, const uint32_t (&a)[4], uint32_t b0, uint32_t b1) {
  asm volatile("mma.sync.aligned.m16n8k16.row.col.f32.bf16.bf16.f32 {%0, %1, %2, %3}, {%4, %5, %6, %7}, {%8, %9}, {%0, %1, %2, %3};"
    : "+f"(d[0]), "+f"(d[1]), "+f"(d[2]), "+f"(d[3]) : "r"(a[0]), "r"(a[1]), "r"(a[2]), "r"(a[3]), "r"(b0), "r"(b1));
}
__device__ __forceinline__ uint32_t zero_after(uint32_t v) { uint32_t r; asm volatile("prmt.b32 %0, %1, 0, 0x4444;" : "=r"(r) : "r"(v)); return r; }
__device__ __forceinline__ uint32_t now() { uint32_t t; asm volatile("mov.u32 %0, %%globaltimer_lo;" : "=r"(t)); return t; }
__device__ __forceinline__ int fresh_tid() { int v; asm volatile("mov.u32 %0, %%tid.x;" : "=r"(v)); return v; }
template <int ID> __device__ __forceinline__ void pin_at() {
  asm volatile("{\n.reg .pred p;\nsetp.eq.u32 p, %0, %1;\nPIN:\n@p nanosleep.u32 0;\n@p bra.uni PIN;\n}\n" :: "r"(blockIdx.x), "n"(4096 + ID) : "memory");
}
#define pin_order() pin_at<__LINE__>()
__device__ __forceinline__ uint32_t pack_bf16(float lo, float hi) {
  uint32_t r; asm("cvt.rn.bf16x2.f32 %0, %1, %2;" : "=r"(r) : "f"(hi), "f"(lo)); return r;
}
__device__ __forceinline__ uint32_t pack_pin(float lo, float hi) {
  uint32_t r; asm volatile("cvt.rn.bf16x2.f32 %0, %1, %2;" : "=r"(r) : "f"(hi), "f"(lo)); return r;
}
__device__ __forceinline__ uint32_t hadd2(uint32_t a, uint32_t b) { uint32_t r; asm("add.rn.bf16x2 %0, %1, %2;" : "=r"(r) : "r"(a), "r"(b)); return r; }
template <int H> __device__ __forceinline__ uint32_t hmul2(uint32_t a, uint32_t b) {
  uint32_t r;
  if (H) asm("{\n.reg .b16 l, h;\n.reg .b32 t;\nmov.b32 {l, h}, %2;\nmov.b32 t, {h, h};\nmul.rn.bf16x2 %0, %1, t;\n}\n" : "=r"(r) : "r"(a), "r"(b));
  else asm("{\n.reg .b16 l, h;\n.reg .b32 t;\nmov.b32 {l, h}, %2;\nmov.b32 t, {l, l};\nmul.rn.bf16x2 %0, %1, t;\n}\n" : "=r"(r) : "r"(a), "r"(b));
  return r;
}
template <int H> __device__ __forceinline__ uint32_t hfma2(uint32_t a, uint32_t b, uint32_t c) {
  uint32_t r;
  if (H) asm("{\n.reg .b16 l, h;\n.reg .b32 t;\nmov.b32 {l, h}, %2;\nmov.b32 t, {h, h};\nfma.rn.bf16x2 %0, %1, t, %3;\n}\n" : "=r"(r) : "r"(a), "r"(b), "r"(c));
  else asm("{\n.reg .b16 l, h;\n.reg .b32 t;\nmov.b32 {l, h}, %2;\nmov.b32 t, {l, l};\nfma.rn.bf16x2 %0, %1, t, %3;\n}\n" : "=r"(r) : "r"(a), "r"(b), "r"(c));
  return r;
}
__device__ __forceinline__ uint32_t hsq2(uint32_t a, uint32_t c) { uint32_t r; asm("fma.rn.bf16x2 %0, %1, %1, %2;" : "=r"(r) : "r"(a), "r"(c)); return r; }
__device__ __forceinline__ float bf_lo_p(uint32_t v) { float r; asm("prmt.b32 %0, %1, 0, 0x1044;" : "=f"(r) : "r"(v)); return r; }
__device__ __forceinline__ float bf_lo(uint32_t v) { return __uint_as_float(v << 16); }
__device__ __forceinline__ float bf_hi(uint32_t v) { return __uint_as_float(v & 0xFFFF0000u); }
__device__ __forceinline__ float bf_round(float v) { return bf_lo(pack_bf16(v, 0.f)); }
__device__ __forceinline__ float ex2(float v) { float r; asm("ex2.approx.ftz.f32 %0, %1;" : "=f"(r) : "f"(v)); return r; }
__device__ __forceinline__ float rsq(float v) { float r; asm("rsqrt.approx.ftz.f32 %0, %1;" : "=f"(r) : "f"(v)); return r; }
__device__ __forceinline__ float rcp(float v) { float r; asm("rcp.approx.ftz.f32 %0, %1;" : "=f"(r) : "f"(v)); return r; }
__device__ __forceinline__ void st_rec16(uint4* p, uint32_t a, uint32_t b, uint32_t c, uint32_t d) {
  asm volatile("{\n.reg .b128 r;\n.reg .b64 lo, hi;\nmov.b64 lo, {%1, %2};\nmov.b64 hi, {%3, %4};\nmov.b128 r, {lo, hi};\nst.relaxed.gpu.global.b128 [%0], r;\n}\n"
    :: "l"(p), "r"(a), "r"(b), "r"(c), "r"(d) : "memory");
}
__device__ __forceinline__ void st_rec16_if(bool on, uint4* p, uint32_t a, uint32_t b, uint32_t c, uint32_t d) {
  asm volatile("{\n.reg .pred p;\n.reg .b128 r;\n.reg .b64 lo, hi;\nsetp.ne.u32 p, %5, 0;\nmov.b64 lo, {%1, %2};\nmov.b64 hi, {%3, %4};\nmov.b128 r, {lo, hi};\n@p st.relaxed.gpu.global.b128 [%0], r;\n}\n"
    :: "l"(p), "r"(a), "r"(b), "r"(c), "r"(d), "r"((uint32_t)on) : "memory");
}
__device__ __forceinline__ uint4 ld_rec16(const uint4* p) {
  uint4 v;
  asm volatile("{\n.reg .b128 r;\n.reg .b64 lo, hi;\nld.relaxed.gpu.global.b128 r, [%4];\nmov.b128 {lo, hi}, r;\nmov.b64 {%0, %1}, lo;\nmov.b64 {%2, %3}, hi;\n}\n"
    : "=r"(v.x), "=r"(v.y), "=r"(v.z), "=r"(v.w) : "l"(p) : "memory");
  return v;
}
__device__ __forceinline__ void ld_rec16_stale(uint4& v, const uint4* p, uint32_t tag) {
  asm volatile("{\n.reg .pred p;\n.reg .b128 r;\n.reg .b64 lo, hi;\n.reg .b32 t;\nmov.b64 lo, {%0, %1};\nmov.b64 hi, {%2, %3};\nmov.b128 r, {lo, hi};\n"
    "xor.b32 t, %0, %5;\nand.b32 t, t, 0x00010001;\nsetp.ne.u32 p, t, 0;\n"
    "@p ld.relaxed.gpu.global.b128 r, [%4];\nmov.b128 {lo, hi}, r;\nmov.b64 {%0, %1}, lo;\nmov.b64 {%2, %3}, hi;\n}\n"
    : "+r"(v.x), "+r"(v.y), "+r"(v.z), "+r"(v.w) : "l"(p), "r"(tag) : "memory");
}
__device__ __forceinline__ void st_rec8(uint2* p, uint32_t a, uint32_t b) {
  asm volatile("{\n.reg .b64 r;\nmov.b64 r, {%1, %2};\nst.relaxed.gpu.global.b64 [%0], r;\n}\n" :: "l"(p), "r"(a), "r"(b) : "memory");
}
__device__ __forceinline__ uint2 ld_rec8(const uint2* p) {
  uint2 v;
  asm volatile("{\n.reg .b64 r;\nld.relaxed.gpu.global.b64 r, [%2];\nmov.b64 {%0, %1}, r;\n}\n" : "=r"(v.x), "=r"(v.y) : "l"(p) : "memory");
  return v;
}
__device__ __forceinline__ unsigned ld_relaxed(const unsigned* p) { unsigned v; asm volatile("ld.relaxed.gpu.global.u32 %0, [%1];" : "=r"(v) : "l"(p) : "memory"); return v; }
__device__ __forceinline__ uint4 ldg_nc16(const void* p) {
  uint4 v; asm volatile("ld.global.nc.L1::no_allocate.v4.u32 {%0, %1, %2, %3}, [%4];" : "=r"(v.x), "=r"(v.y), "=r"(v.z), "=r"(v.w) : "l"(p)); return v;
}
__device__ __forceinline__ void stg16(void* p, uint4 v) { asm volatile("st.global.v4.u32 [%0], {%1, %2, %3, %4};" :: "l"(p), "r"(v.x), "r"(v.y), "r"(v.z), "r"(v.w) : "memory"); }
__device__ __forceinline__ float2 lds_f2(uint32_t a) { float2 v; asm volatile("ld.shared.v2.f32 {%0, %1}, [%2];" : "=f"(v.x), "=f"(v.y) : "r"(a)); return v; }
__device__ __forceinline__ float lds_f(uint32_t a) { float v; asm volatile("ld.shared.f32 %0, [%1];" : "=f"(v) : "r"(a)); return v; }
__device__ __forceinline__ uint32_t lds_u(uint32_t a) { uint32_t v; asm volatile("ld.shared.u32 %0, [%1];" : "=r"(v) : "r"(a)); return v; }
__device__ __forceinline__ uint2 lds_u2(uint32_t a) { uint2 v; asm volatile("ld.shared.v2.u32 {%0, %1}, [%2];" : "=r"(v.x), "=r"(v.y) : "r"(a)); return v; }
__device__ __forceinline__ uint4 lds_u4(uint32_t a) { uint4 v; asm volatile("ld.shared.v4.u32 {%0, %1, %2, %3}, [%4];" : "=r"(v.x), "=r"(v.y), "=r"(v.z), "=r"(v.w) : "r"(a)); return v; }
__device__ __forceinline__ void sts_f(uint32_t a, float v) { asm volatile("st.shared.f32 [%0], %1;" :: "r"(a), "f"(v) : "memory"); }
__device__ __forceinline__ void sts_f2(uint32_t a, float x, float y) { asm volatile("st.shared.v2.f32 [%0], {%1, %2};" :: "r"(a), "f"(x), "f"(y) : "memory"); }
__device__ __forceinline__ void sts_u2(uint32_t a, uint32_t x, uint32_t y) { asm volatile("st.shared.v2.u32 [%0], {%1, %2};" :: "r"(a), "r"(x), "r"(y) : "memory"); }
__device__ __forceinline__ void sts_u4(uint32_t a, uint32_t x, uint32_t y, uint32_t z, uint32_t w) { asm volatile("st.shared.v4.u32 [%0], {%1, %2, %3, %4};" :: "r"(a), "r"(x), "r"(y), "r"(z), "r"(w) : "memory"); }
__device__ __forceinline__ void sts_h(uint32_t a, uint32_t v) { asm volatile("st.shared.u16 [%0], %1;" :: "r"(a), "h"((uint16_t)v) : "memory"); }
__device__ __forceinline__ void sts_u(uint32_t a, uint32_t v) { asm volatile("st.shared.u32 [%0], %1;" :: "r"(a), "r"(v) : "memory"); }

template <int TA, int TB>
__device__ __forceinline__ void wg_n128(float (&d)[64], uint64_t da, uint64_t db, int sd) {
  asm volatile("{\n.reg .pred p;\nsetp.ne.b32 p, %66, 0;\n"
    "wgmma.mma_async.sync.aligned.m64n128k16.f32.bf16.bf16 {%0, %1, %2, %3, %4, %5, %6, %7, %8, %9, %10, %11, %12, %13, %14, %15, %16, %17, %18, %19, %20, %21, %22, %23, %24, %25, %26, %27, %28, %29, %30, %31, %32, %33, %34, %35, %36, %37, %38, %39, %40, %41, %42, %43, %44, %45, %46, %47, %48, %49, %50, %51, %52, %53, %54, %55, %56, %57, %58, %59, %60, %61, %62, %63}, %64, %65, p, 1, 1, %67, %68;\n}\n"
    : "+f"(d[0]), "+f"(d[1]), "+f"(d[2]), "+f"(d[3]), "+f"(d[4]), "+f"(d[5]), "+f"(d[6]), "+f"(d[7]), "+f"(d[8]), "+f"(d[9]), "+f"(d[10]), "+f"(d[11]), "+f"(d[12]), "+f"(d[13]), "+f"(d[14]), "+f"(d[15]), "+f"(d[16]), "+f"(d[17]), "+f"(d[18]), "+f"(d[19]), "+f"(d[20]), "+f"(d[21]), "+f"(d[22]), "+f"(d[23]), "+f"(d[24]), "+f"(d[25]), "+f"(d[26]), "+f"(d[27]), "+f"(d[28]), "+f"(d[29]), "+f"(d[30]), "+f"(d[31]), "+f"(d[32]), "+f"(d[33]), "+f"(d[34]), "+f"(d[35]), "+f"(d[36]), "+f"(d[37]), "+f"(d[38]), "+f"(d[39]), "+f"(d[40]), "+f"(d[41]), "+f"(d[42]), "+f"(d[43]), "+f"(d[44]), "+f"(d[45]), "+f"(d[46]), "+f"(d[47]), "+f"(d[48]), "+f"(d[49]), "+f"(d[50]), "+f"(d[51]), "+f"(d[52]), "+f"(d[53]), "+f"(d[54]), "+f"(d[55]), "+f"(d[56]), "+f"(d[57]), "+f"(d[58]), "+f"(d[59]), "+f"(d[60]), "+f"(d[61]), "+f"(d[62]), "+f"(d[63])
    : "l"(da), "l"(db), "r"(sd), "n"(TA), "n"(TB));
}

template <int TA, int TB, int O>
__device__ __forceinline__ void wg_n64(float (&d)[64], uint64_t da, uint64_t db, int sd) {
  asm volatile("{\n.reg .pred p;\nsetp.ne.b32 p, %34, 0;\n"
    "wgmma.mma_async.sync.aligned.m64n64k16.f32.bf16.bf16 {%0, %1, %2, %3, %4, %5, %6, %7, %8, %9, %10, %11, %12, %13, %14, %15, %16, %17, %18, %19, %20, %21, %22, %23, %24, %25, %26, %27, %28, %29, %30, %31}, %32, %33, p, 1, 1, %35, %36;\n}\n"
    : "+f"(d[O + 0]), "+f"(d[O + 1]), "+f"(d[O + 2]), "+f"(d[O + 3]), "+f"(d[O + 4]), "+f"(d[O + 5]), "+f"(d[O + 6]), "+f"(d[O + 7]), "+f"(d[O + 8]), "+f"(d[O + 9]), "+f"(d[O + 10]), "+f"(d[O + 11]), "+f"(d[O + 12]), "+f"(d[O + 13]), "+f"(d[O + 14]), "+f"(d[O + 15]), "+f"(d[O + 16]), "+f"(d[O + 17]), "+f"(d[O + 18]), "+f"(d[O + 19]), "+f"(d[O + 20]), "+f"(d[O + 21]), "+f"(d[O + 22]), "+f"(d[O + 23]), "+f"(d[O + 24]), "+f"(d[O + 25]), "+f"(d[O + 26]), "+f"(d[O + 27]), "+f"(d[O + 28]), "+f"(d[O + 29]), "+f"(d[O + 30]), "+f"(d[O + 31])
    : "l"(da), "l"(db), "r"(sd), "n"(TA), "n"(TB));
}

template <int TA, int TB>
__device__ __forceinline__ void wg_n40(float (&d)[20], uint64_t da, uint64_t db, int sd) {
  asm volatile("{\n.reg .pred p;\nsetp.ne.b32 p, %22, 0;\n"
    "wgmma.mma_async.sync.aligned.m64n40k16.f32.bf16.bf16 {%0, %1, %2, %3, %4, %5, %6, %7, %8, %9, %10, %11, %12, %13, %14, %15, %16, %17, %18, %19}, %20, %21, p, 1, 1, %23, %24;\n}\n"
    : "+f"(d[0]), "+f"(d[1]), "+f"(d[2]), "+f"(d[3]), "+f"(d[4]), "+f"(d[5]), "+f"(d[6]), "+f"(d[7]), "+f"(d[8]), "+f"(d[9]), "+f"(d[10]), "+f"(d[11]), "+f"(d[12]), "+f"(d[13]), "+f"(d[14]), "+f"(d[15]), "+f"(d[16]), "+f"(d[17]), "+f"(d[18]), "+f"(d[19])
    : "l"(da), "l"(db), "r"(sd), "n"(TA), "n"(TB));
}

template <int TA, int TB>
__device__ __forceinline__ void wg_n32(float (&d)[16], uint64_t da, uint64_t db, int sd) {
  asm volatile("{\n.reg .pred p;\nsetp.ne.b32 p, %18, 0;\n"
    "wgmma.mma_async.sync.aligned.m64n32k16.f32.bf16.bf16 {%0, %1, %2, %3, %4, %5, %6, %7, %8, %9, %10, %11, %12, %13, %14, %15}, %16, %17, p, 1, 1, %19, %20;\n}\n"
    : "+f"(d[0]), "+f"(d[1]), "+f"(d[2]), "+f"(d[3]), "+f"(d[4]), "+f"(d[5]), "+f"(d[6]), "+f"(d[7]), "+f"(d[8]), "+f"(d[9]), "+f"(d[10]), "+f"(d[11]), "+f"(d[12]), "+f"(d[13]), "+f"(d[14]), "+f"(d[15])
    : "l"(da), "l"(db), "r"(sd), "n"(TA), "n"(TB));
}

template <int TB>
__device__ __forceinline__ void wg_n40_rs(float (&d)[20], uint32_t a0, uint32_t a1, uint32_t a2, uint32_t a3, uint64_t db, int sd) {
  asm volatile("{\n.reg .pred p;\nsetp.ne.b32 p, %25, 0;\n"
    "wgmma.mma_async.sync.aligned.m64n40k16.f32.bf16.bf16 {%0, %1, %2, %3, %4, %5, %6, %7, %8, %9, %10, %11, %12, %13, %14, %15, %16, %17, %18, %19}, {%20, %21, %22, %23}, %24, p, 1, 1, %26;\n}\n"
    : "+f"(d[0]), "+f"(d[1]), "+f"(d[2]), "+f"(d[3]), "+f"(d[4]), "+f"(d[5]), "+f"(d[6]), "+f"(d[7]), "+f"(d[8]), "+f"(d[9]), "+f"(d[10]), "+f"(d[11]), "+f"(d[12]), "+f"(d[13]), "+f"(d[14]), "+f"(d[15]), "+f"(d[16]), "+f"(d[17]), "+f"(d[18]), "+f"(d[19])
    : "r"(a0), "r"(a1), "r"(a2), "r"(a3), "l"(db), "r"(sd), "n"(TB));
}

template <int TB>
__device__ __forceinline__ void wg_n32_rs(float (&d)[16], uint32_t a0, uint32_t a1, uint32_t a2, uint32_t a3, uint64_t db, int sd) {
  asm volatile("{\n.reg .pred p;\nsetp.ne.b32 p, %21, 0;\n"
    "wgmma.mma_async.sync.aligned.m64n32k16.f32.bf16.bf16 {%0, %1, %2, %3, %4, %5, %6, %7, %8, %9, %10, %11, %12, %13, %14, %15}, {%16, %17, %18, %19}, %20, p, 1, 1, %22;\n}\n"
    : "+f"(d[0]), "+f"(d[1]), "+f"(d[2]), "+f"(d[3]), "+f"(d[4]), "+f"(d[5]), "+f"(d[6]), "+f"(d[7]), "+f"(d[8]), "+f"(d[9]), "+f"(d[10]), "+f"(d[11]), "+f"(d[12]), "+f"(d[13]), "+f"(d[14]), "+f"(d[15])
    : "r"(a0), "r"(a1), "r"(a2), "r"(a3), "l"(db), "r"(sd), "n"(TB));
}

template <int TB>
__device__ __forceinline__ void wg_n8_rs(float (&d)[4], uint32_t a0, uint32_t a1, uint32_t a2, uint32_t a3, uint64_t db, int sd) {
  asm volatile("{\n.reg .pred p;\nsetp.ne.b32 p, %9, 0;\n"
    "wgmma.mma_async.sync.aligned.m64n8k16.f32.bf16.bf16 {%0, %1, %2, %3}, {%4, %5, %6, %7}, %8, p, 1, 1, %10;\n}\n"
    : "+f"(d[0]), "+f"(d[1]), "+f"(d[2]), "+f"(d[3])
    : "r"(a0), "r"(a1), "r"(a2), "r"(a3), "l"(db), "r"(sd), "n"(TB));
}

template <int TB>
__device__ __forceinline__ void wg_n128_rs(float (&d)[64], uint32_t a0, uint32_t a1, uint32_t a2, uint32_t a3, uint64_t db, int sd) {
  asm volatile("{\n.reg .pred p;\nsetp.ne.b32 p, %69, 0;\n"
    "wgmma.mma_async.sync.aligned.m64n128k16.f32.bf16.bf16 {%0, %1, %2, %3, %4, %5, %6, %7, %8, %9, %10, %11, %12, %13, %14, %15, %16, %17, %18, %19, %20, %21, %22, %23, %24, %25, %26, %27, %28, %29, %30, %31, %32, %33, %34, %35, %36, %37, %38, %39, %40, %41, %42, %43, %44, %45, %46, %47, %48, %49, %50, %51, %52, %53, %54, %55, %56, %57, %58, %59, %60, %61, %62, %63}, {%64, %65, %66, %67}, %68, p, 1, 1, %70;\n}\n"
    : "+f"(d[0]), "+f"(d[1]), "+f"(d[2]), "+f"(d[3]), "+f"(d[4]), "+f"(d[5]), "+f"(d[6]), "+f"(d[7]), "+f"(d[8]), "+f"(d[9]), "+f"(d[10]), "+f"(d[11]), "+f"(d[12]), "+f"(d[13]), "+f"(d[14]), "+f"(d[15]), "+f"(d[16]), "+f"(d[17]), "+f"(d[18]), "+f"(d[19]), "+f"(d[20]), "+f"(d[21]), "+f"(d[22]), "+f"(d[23]), "+f"(d[24]), "+f"(d[25]), "+f"(d[26]), "+f"(d[27]), "+f"(d[28]), "+f"(d[29]), "+f"(d[30]), "+f"(d[31]), "+f"(d[32]), "+f"(d[33]), "+f"(d[34]), "+f"(d[35]), "+f"(d[36]), "+f"(d[37]), "+f"(d[38]), "+f"(d[39]), "+f"(d[40]), "+f"(d[41]), "+f"(d[42]), "+f"(d[43]), "+f"(d[44]), "+f"(d[45]), "+f"(d[46]), "+f"(d[47]), "+f"(d[48]), "+f"(d[49]), "+f"(d[50]), "+f"(d[51]), "+f"(d[52]), "+f"(d[53]), "+f"(d[54]), "+f"(d[55]), "+f"(d[56]), "+f"(d[57]), "+f"(d[58]), "+f"(d[59]), "+f"(d[60]), "+f"(d[61]), "+f"(d[62]), "+f"(d[63])
    : "r"(a0), "r"(a1), "r"(a2), "r"(a3), "l"(db), "r"(sd), "n"(TB));
}


template <int N>
__device__ __forceinline__ void feature_shifted(const float (&p)[16], const float (&p2)[16], float sc0, float sc1, uint32_t (&o)[N]) {
  __align__(16) float t[N];
  __align__(16) uint32_t w[N];
#pragma unroll
  for (int i = 0; i < N; i++) t[i] = i < 16 ? p[i] : p2[i & 15];
#pragma unroll 1
  for (int it = 0; it < N / 4; it++) {
    const float* x = t + (it >> 2) * 16 + (it & 1) * 2;
    const int h = (it >> 1) & 1;
    const float sg = h ? -1.f : 1.f, sc = (it & 1) ? sc1 : sc0;
    float mx = sg * x[0], s = 0.f;
#pragma unroll 1
    for (int j = 0; j < 16; j += 4) mx = fmaxf(mx, fmaxf(sg * x[j], sg * x[j + 1]));
    mx = fmaxf(mx, __shfl_xor_sync(0xffffffffu, mx, 1));
    mx = fmaxf(mx, __shfl_xor_sync(0xffffffffu, mx, 2));
#pragma unroll 1
    for (int j = 0; j < 32; j += 4) {
      const float a = ex2((sg * x[(j & 15) + h] - mx) * sc), c = ex2((sg * x[(j & 15) + 1 - h] - mx) * sc);
      if (j < 16) s += a + c;
      else w[(it >> 1) * 8 + (j >> 1) - 8 + (it & 1)] = pack_bf16(a * s, c * s);
      if (j == 12) {
        s += __shfl_xor_sync(0xffffffffu, s, 1);
        s += __shfl_xor_sync(0xffffffffu, s, 2);
        s = rcp(s);
      }
    }
  }
#pragma unroll
  for (int i = 0; i < N; i++) o[i] = w[i];
}
constexpr float FAST_LIMIT = RCPG == 2 ? 0x1p60f : RCPG == 4 ? 0x1p30f : 0x1p15f;
__device__ __forceinline__ void feature_exp(const float* p, float sc0, float sc1, uint32_t* o, float (&d)[4], uint64_t sel) {
  float e[16], r[8];
#pragma unroll
  for (int i = 0; i < 16; i++) e[i] = ex2(p[i] * ((i & 2) ? sc1 : sc0));
#pragma unroll
  for (int i = 0; i < 8; i++) r[i] = e[2 * i] * e[2 * i + 1];
#pragma unroll
  for (int i = 0; i < 8; i++) o[i] = pack_bf16(e[2 * i], e[2 * i + 1]);
  uint32_t a[4];
#pragma unroll
  for (int i = 0; i < 2; i++) {
    if (RCPG == 2) {
      o[8 + i] = pack_bf16(rcp(r[i]), rcp(r[2 + i]));
      o[10 + i] = pack_bf16(rcp(r[4 + i]), rcp(r[6 + i]));
    } else {
      float u = r[i] * r[2 + i], w = r[4 + i] * r[6 + i];
      if (RCPG == 4) { u = rcp(u); w = rcp(w); }
      else { const float z = rcp(u * w), y = z * u; u = z * w; w = y; }
      o[8 + i] = pack_bf16(u * r[2 + i], u * r[i]);
      o[10 + i] = pack_bf16(w * r[6 + i], w * r[4 + i]);
    }
    a[i] = hadd2(hadd2(o[i], o[2 + i]), hadd2(o[4 + i], o[6 + i]));
    a[2 + i] = hfma2<1>(o[6 + i], o[10 + i], hfma2<0>(o[4 + i], o[10 + i], hfma2<1>(o[2 + i], o[8 + i], hmul2<0>(o[i], o[8 + i]))));
  }
  wg_fence();
  wg_n8_rs<0>(d, a[0], a[1], a[2], a[3], sel, 0);
  wg_commit();
}
template <bool FULL>
__device__ __forceinline__ float feature_norm(uint32_t* o, const float (&d)[4]) {
  uint32_t c[4];
  if (FULL) {
#pragma unroll
    for (int i = 0; i < 2; i++) {
      const float z = rcp(d[2 * i] * d[2 * i + 1]);
      const uint32_t n = pack_bf16(z * d[2 * i + 1], z * d[2 * i]);
      c[i] = hmul2<1>(o[8 + i], n); c[2 + i] = hmul2<1>(o[10 + i], n);
#pragma unroll
      for (int j = i; j < 8; j += 2) {
        o[8 + j] = (j & 2) ? hmul2<1>(o[j], c[(j >> 2) * 2 + i]) : hmul2<0>(o[j], c[(j >> 2) * 2 + i]);
        o[j] = hmul2<0>(o[j], n);
      }
    }
  } else {
    const uint32_t n = pack_bf16(d[0] * rcp(d[1]), d[2] * rcp(d[3]));
    c[0] = hmul2<0>(o[8], n); c[1] = hmul2<1>(o[9], n); c[2] = hmul2<0>(o[10], n); c[3] = hmul2<1>(o[11], n);
#pragma unroll
    for (int j = 0; j < 8; j++) o[8 + j] = (j & 2) ? hmul2<1>(o[j], c[(j >> 2) * 2 + (j & 1)]) : hmul2<0>(o[j], c[(j >> 2) * 2 + (j & 1)]);
  }
  return (d[0] + d[1]) + (d[2] + d[3]);
}
__device__ __forceinline__ float feature_norm32(const float (&e)[16], const float (&r)[8], const float (&d)[4], uint32_t* o) {
#pragma unroll
  for (int i = 0; i < 2; i++) {
    const float z = rcp(d[2 * i] * d[2 * i + 1]), np = z * d[2 * i + 1], nm = z * d[2 * i];
    if (KH2) {
      const float q = nm * d[2 * i];
      const uint32_t c0 = pack_bf16(r[i] * q, r[2 + i] * q), c1 = pack_bf16(r[4 + i] * q, r[6 + i] * q);
#pragma unroll
      for (int j = i; j < 8; j += 2) {
        o[j] = pack_bf16(e[2 * j] * np, e[2 * j + 1] * np);
        o[8 + j] = (j & 2) ? hmul2<1>(o[j], (j & 4) ? c1 : c0) : hmul2<0>(o[j], (j & 4) ? c1 : c0);
      }
    } else {
#pragma unroll
      for (int j = i; j < 8; j += 2) {
        const float c = r[j] * nm;
        o[j] = pack_bf16(e[2 * j] * np, e[2 * j + 1] * np);
        o[8 + j] = pack_bf16(e[2 * j] * c, e[2 * j + 1] * c);
      }
    }
  }
  return (d[0] + d[1]) + (d[2] + d[3]);
}
template <class H>
__device__ __forceinline__ float feature_fast(const float* p, float sc0, float sc1, uint32_t* o, H hook) {
  float e[16], r[8], sp[2] = {0.f, 0.f}, sm[2] = {0.f, 0.f};
#pragma unroll
  for (int i = 0; i < 16; i++) e[i] = ex2(p[i] * ((i & 2) ? sc1 : sc0));
#pragma unroll
  for (int i = 0; i < 8; i++) r[i] = e[2 * i] * e[2 * i + 1];
#pragma unroll
  for (int i = 0; i < 2; i++) {
    float u = r[i] * r[2 + i], w = r[4 + i] * r[6 + i];
    if (RCPG == 4) { u = rcp(u); w = rcp(w); }
    else { const float z = rcp(u * w), y = z * u; u = z * w; w = y; }
    const float c = u * r[i], d = w * r[4 + i];
    r[i] = u * r[2 + i]; r[2 + i] = c; r[4 + i] = w * r[6 + i]; r[6 + i] = d;
  }
#pragma unroll
  for (int i = 0; i < 8; i++) {
    const float t = e[2 * i] + e[2 * i + 1];
    sp[i & 1] += t; sm[i & 1] = fmaf(t, r[i], sm[i & 1]);
  }
  const float tot = (sp[0] + sp[1]) + (sm[0] + sm[1]);
  if (KSH == 1) {
#pragma unroll
    for (int i = 0; i < 2; i++) {
      uint32_t v = pack_bf16(sp[i], sm[i]);
      v = hadd2(v, __shfl_xor_sync(0xffffffffu, v, 1));
      const uint32_t w = __shfl_xor_sync(0xffffffffu, v, 2);
      sp[i] = bf_lo(v) + bf_lo(w); sm[i] = bf_hi(v) + bf_hi(w);
    }
  } else {
#pragma unroll
    for (int m = 1; m <= 2; m <<= 1)
#pragma unroll
      for (int i = 0; i < 2; i++) { sp[i] += __shfl_xor_sync(0xffffffffu, sp[i], m); sm[i] += __shfl_xor_sync(0xffffffffu, sm[i], m); }
  }
  hook();
  const float d[4] = {sp[0], sm[0], sp[1], sm[1]};
  feature_norm32(e, r, d, o);
  return tot;
}
__device__ __forceinline__ bool warp_fails(bool ok) { return __builtin_expect(!__all_sync(0xffffffffu, ok), 0); }
constexpr uint32_t OTAG = 0x00010001u;
__device__ __forceinline__ void attn_out(const float (&u)[20], uint32_t tg, uint32_t* r, uint4* dst, bool pub) {
  const float d0 = rcp(fmaf(u[17], 0.5e-6f, u[16])), d1 = rcp(fmaf(u[19], 0.5e-6f, u[18]));
#pragma unroll
  for (int j = 0; j < 8; j++) r[j] = pack_bf16(u[2 * j] * ((j & 1) ? d1 : d0), u[2 * j + 1] * ((j & 1) ? d1 : d0));
  r[0] = (r[0] & ~OTAG) | tg; r[4] = (r[4] & ~OTAG) | tg;
  if (pub) {
    st_rec16(dst, r[0], r[1], r[2], r[3]);
    st_rec16(dst + 32, r[4], r[5], r[6], r[7]);
  }
}

__device__ __forceinline__ uint32_t with_tag(uint32_t w, uint32_t tg) {
  const uint32_t m = (w ^ tg) & OTAG;
  return w + m - (w & (m + m));
}

constexpr float L2E = 1.4426950408889634f;

__device__ __forceinline__ int pc_chunk(int j, int cb) {
  const int c = j > 8, e = j - 2 - 7 * c;
  return j < 2 ? 2 * cb + j : 2 * (e == cb ? 7 : e) + c;
}
constexpr unsigned long long Q_ASLOTS = 0x1896308963089630ull, Q_BSLOTS = 0x754217542175421ull;
constexpr unsigned long long Q_CHUNKS = 0xAB9876543210FEDCull;
constexpr unsigned long long PC_ASLOTS = 0x2BA02BA02BA02BAull, PC_BSLOTS = 0x3765437654376543ull;
constexpr unsigned long long FFN_SLOTS = 0xBA8954C11897ull;
constexpr unsigned long long FFN_ORDER = 0xB74A69583210ull;
constexpr unsigned long long FFN_WAIT0 = 0x6B4A65497E7E3D3Eull, FFN_WAIT1 = 0x6C6C4B6Bull;
constexpr unsigned long long FFN_PACE0 = 0x6A67647F51ull, FFN_PACE1 = 0x0ull;
constexpr unsigned long long WO_WAIT0 = 0x626160483C3D3C3Bull, WO_WAIT1 = 0x6A69686766656463ull;
constexpr unsigned long long WO_PACE0 = 0x527F502Full, WO_PACE1 = 0x0ull;
constexpr unsigned long long PF_PACE0 = 0x0ull, PF_PACE1 = 0x1D1D1C1C00000000ull, PF_PACE2 = 0x313130301F1F1E1Eull, PF_PACE3 = 0x3232ull;
constexpr unsigned long long PF_EARLY = 0x111111111111ull;
constexpr int PF_FIRST = 12;
__device__ __forceinline__ uint32_t tab4(unsigned long long t, int i) { return (uint32_t)(t >> (4 * i)) & 15u; }
__device__ __forceinline__ uint32_t tab8(unsigned long long lo, unsigned long long hi, int i) { return (uint32_t)((i < 8 ? lo : hi) >> (8 * (i & 7))) & 255u; }

__device__ __forceinline__ float sum8(uint4 v) {
  return ((bf_lo(v.x) + bf_hi(v.x)) + (bf_lo(v.y) + bf_hi(v.y))) + ((bf_lo(v.z) + bf_hi(v.z)) + (bf_lo(v.w) + bf_hi(v.w)));
}
__device__ __forceinline__ float warp_sum(float s) {
#pragma unroll
  for (int m = 16; m >= 1; m >>= 1) s += __shfl_xor_sync(0xffffffffu, s, m);
  return s;
}
template <class T> __device__ __forceinline__ T* settle(T* p, int lane) {
  return reinterpret_cast<T*>(__shfl_sync(0xffffffffu, reinterpret_cast<unsigned long long>(p), lane));
}
__device__ __forceinline__ float pick4(int c, float a, float b, float d, float e) {
  float r;
  asm("{\n.reg .pred p, q;\n.reg .f32 u, v;\n.reg .b32 t;\nand.b32 t, %1, 1;\nsetp.ne.u32 p, t, 0;\nsetp.gt.u32 q, %1, 1;\n"
      "selp.f32 u, %3, %2, p;\nselp.f32 v, %5, %4, p;\nselp.f32 %0, v, u, q;\n}\n" : "=f"(r) : "r"(c), "f"(a), "f"(b), "f"(d), "f"(e));
  return r;
}
__device__ __forceinline__ uint32_t differ(uint32_t a, uint32_t b, uint32_t t) { uint32_t r; asm("lop3.b32 %0, %1, %2, %3, 0x7E;" : "=r"(r) : "r"(a), "r"(b), "r"(t)); return r; }
__device__ __forceinline__ uint32_t ln_res(uint32_t h, float a, float c, uint32_t& n) {
  const float l = bf_lo(h), u = bf_hi(h);
  n = pack_bf16(fmaf(l, a, c), fmaf(u, a, c));
  return hadd2(h, n);
}

__device__ __forceinline__ uint64_t ext_a(uint32_t sb, uint32_t row) { return mk_desc(sb + 12 * SLOT + 4096 + row * 16, 4096 - row * 16, 128, 0); }
__device__ __forceinline__ uint64_t ext_b(uint32_t sb, uint32_t part) { return mk_desc(sb + 12 * SLOT + part * 2048, 1024, 0, 1); }
__device__ __forceinline__ uint64_t sum_b(uint32_t sb) { return mk_desc(sb + OFF_SEL, 16, 128, 0); }
__device__ __forceinline__ uint32_t split_bf16(float v) { return pack_bf16(v, v - bf_round(v)); }

template <int N> __device__ __forceinline__ void padn() { if constexpr (N > 1) { padn<N / 2>(); padn<N - N / 2>(); } else if constexpr (N == 1) asm volatile("nanosleep.u32 1;"); }
__global__ void __launch_bounds__(NTHREADS, 1) fused_kernel(const __grid_constant__ Params P) {
  extern __shared__ __align__(1024) uint8_t smem_raw[];
  const uint32_t sb = smem_u32(smem_raw);
  const uint32_t bars = sb + OFF_BAR;
  const int tid = threadIdx.x;
  const int wg = __shfl_sync(0xffffffffu, tid >> 7, 0);
  const int warp = __shfl_sync(0xffffffffu, (tid >> 5) & 3, 0);
  const int lane = tid & 31;
  const int b = MAP == 0 ? (blockIdx.x & 1) * 64 + (blockIdx.x >> 1)
              : MAP == 1 ? (blockIdx.x >> 5) * 32 + (blockIdx.x & 3) * 8 + ((blockIdx.x >> 2) & 7)
              : MAP == 2 ? (blockIdx.x >> 5) * 32 + ((blockIdx.x >> 2) & 3) * 8 + ((blockIdx.x >> 4) & 1) * 4 + (blockIdx.x & 3)
              : MAP == 3 ? (blockIdx.x & 3) * 32 + (blockIdx.x >> 5) * 8 + ((blockIdx.x >> 2) & 7)
              : (blockIdx.x & 1) * 64 + ((blockIdx.x >> 1) & 1) * 8 + (blockIdx.x >> 5) * 16 + ((blockIdx.x >> 2) & 7);
  const bool ffn = (blockIdx.x & 7) != 7;
  const int fi = blockIdx.x - (blockIdx.x >> 3);
  const int rbk = b >> 4, hp = b & 15;
  const int rb = b >> 3, cb = b & 7;
#define BAR(i) (bars + 8u * (uint32_t)(i))
#define MMA_IDS \
    const int tid = fresh_tid(), lane = tid & 31; \
    const bool leader = (tid & 127) == 0; \
    const uint32_t srow = (uint32_t)(warp * 16 + (lane & 7) + ((lane >> 3) & 1) * 8); \
    const uint32_t sx = (uint32_t)(lane >> 4) ^ (srow & 7); \
    const int c2 = (lane & 3) * 2, lr = warp * 16 + (lane >> 2); \
    (void)leader; (void)sx; (void)c2; (void)lr;

  auto load_kv = [&](int it) {
    const uint32_t s = sb + (uint32_t)(it & 3) * 3 * SLOT, fb = BAR(B_FKV + it);
    mbar_expect_tx(fb, ((SKIP & 8) ? 0 : 2 * SLOT) + ((SKIP & 16) ? 0 : SLOT));
    if (!(SKIP & 8)) {
    tma_load_2d(s, &P.mX, fb, it * 64, rb * 128);
    tma_load_2d(s + SLOT, &P.mX, fb, it * 64, (rb ^ 1) * 128);
    }
    if (!(SKIP & 16)) {
    tma_load_w<WEF & 1>(s + 2 * SLOT, &P.mW, fb, 1024 + hp * 64, it * 64);
    tma_load_w<WEF & 1>(s + 2 * SLOT + 8192, &P.mW, fb, 2048 + hp * 64, it * 64);
    }
  };
  auto prefetch = [&](int c) {
    if (c < 2) { l2_prefetch(P.wo + b * 8192 + c * 4096, 8192); return; }
    if (!ffn) return;
    const int e = c - 2;
    if (e == 0) mbar_expect_tx(BAR(B_TCH), 24 * 1024);
    const CUtensorMap* mp = e >= 16 ? &P.mWdT : (e & 1) ? &P.mWuT : &P.mWgT;
    const int r = e >= 16 ? fi * 512 + (e - 16) * 64 : (e >> 1) * 128 + (fi & 1) * 64;
#pragma unroll 1
    for (int q = 0; q < 64; q += TROWS) tma_load_2d(sb + OFF_TCH, mp, BAR(B_TCH), e >= 16 ? 0 : (fi >> 1) * 64, r + q);
  };

  {
    const int w16 = wg * 4 + warp;
    const uint32_t cnt = w16 == 14 ? 128u : ((0x300Cu >> w16) & 1u) + 1u;
    if (elect()) {
      if (w16 == 11) {
#pragma unroll
        for (int i = 0; i < 4; i++) mbar_init(BAR(B_FKV + i), 1u);
        if (FINE) { mbar_init(BAR(B_F0), 1u); mbar_init(BAR(B_F0 + 1), 1u); }
        asm volatile("fence.mbarrier_init.release.cluster;" ::: "memory");
        if (FINE) {
          mbar_expect_tx(BAR(B_FKV), 24576);
          tma_load_2d(sb, &P.mX2, BAR(B_FKV), 0, rb * 128);
          tma_load_2d(sb + 2 * SLOT, &P.mW2, BAR(B_FKV), 1024 + hp * 64, 0);
          tma_load_2d(sb + 2 * SLOT + 8192, &P.mW2, BAR(B_FKV), 2048 + hp * 64, 0);
          tma_load_2d(sb + SLOT, &P.mX2, BAR(B_FKV), 0, (rb ^ 1) * 128);
          mbar_expect_tx(BAR(B_F0), 8192);
          tma_load_2d(sb + 2 * SLOT + 4096, &P.mW2, BAR(B_F0), 1024 + hp * 64, 32);
          tma_load_2d(sb + 2 * SLOT + 12288, &P.mW2, BAR(B_F0), 2048 + hp * 64, 32);
          mbar_expect_tx(BAR(B_F0 + 1), 16384);
          tma_load_2d(sb + 8192, &P.mX2, BAR(B_F0 + 1), 0, rb * 128 + 64);
          tma_load_2d(sb + SLOT + 8192, &P.mX2, BAR(B_F0 + 1), 0, (rb ^ 1) * 128 + 64);
        } else load_kv(0);
#pragma unroll
        for (int i = 1; i < K1E; i++) load_kv(i);
      }
#pragma unroll
      for (int i = 0; i < 8; i++)
      {
        if (w16 || i >= 4) mbar_init(BAR(w16 * 8 + i), w16 == 15 ? (uint32_t)(MISC_COUNTS >> (8 * i)) & 255u : cnt);
        if (K1M && i == K1M - 1 && w16 == 11) load_kv(1);
      }
      mbar_init(BAR(B_FS + w16), w16 >= 14 ? 2u : 1u);
      mbar_init(BAR(B_FW + w16), 1u);
      asm volatile("fence.mbarrier_init.release.cluster;" ::: "memory");
    }
    __syncwarp();
    if (w16 == 11 && elect()) {
#pragma unroll 1
      for (int i = K1M ? 2 : K1E; i < K2W; i++) { load_kv(i); }
    }
    __syncwarp();
  }

  if (wg >= 2) {
    if (wg == 3) {
      asm volatile("setmaxnreg.dec.sync.aligned.u32 64;");
      asm volatile("barrier.sync 0;" ::: "memory");
        if (warp) {
          const int q = 3 * b + warp - 1, cg = q % 96, kq = q / 96;
          const uint32_t buf = sb + (warp == 3 ? OFF_PHIQ : 12 * SLOT + (warp - 1) * 8192);
          const uint32_t fb = BAR(B_FS + (warp - 1) * 4);
          mbar_wait(BAR(B_FKV + ((CSW >> (4 * (kq + (cg < 32 ? 0 : 4)))) & 15)));
          if (elect()) {
#pragma unroll
            for (int p = 0; p < 2; p++) { mbar_expect_tx(fb + p * 8, 4096); tma_load_w<WEF & 4>(buf + p * 4096, &P.mWs, fb + p * 8, cg * 32, kq * 256 + p * 64); }
          }
          float cs[8];
#pragma unroll
          for (int i = 0; i < 8; i++) cs[i] = 0.f;
          const unsigned ep = ld_relaxed(&g_epoch);
#pragma unroll 1
          for (int p = 0; p < 4; p++) {
            mbar_wait(fb + p * 8);
            uint4 v[8];
#pragma unroll
            for (int i = 0; i < 8; i++) v[i] = lds_u4(buf + (p & 1) * 4096 + i * 512 + lane * 16);
            if (p < 2) {
              uint32_t dep = 0;
#pragma unroll
              for (int i = 0; i < 8; i++) dep ^= v[i].x;
              const int n = p + 2 + (int)__shfl_sync(0xffffffffu, zero_after(dep), 0);
              if (elect()) {
                mbar_expect_tx(fb + n * 8, 4096);
                tma_load_w<WEF & 4>(buf + (n & 1) * 4096, &P.mWs, fb + n * 8, cg * 32, kq * 256 + n * 64);
              }
            }
#pragma unroll
            for (int i = 0; i < 8; i += 2) {
              cs[0] += bf_lo(v[i].x) + bf_lo(v[i + 1].x); cs[1] += bf_hi(v[i].x) + bf_hi(v[i + 1].x);
              cs[2] += bf_lo(v[i].y) + bf_lo(v[i + 1].y); cs[3] += bf_hi(v[i].y) + bf_hi(v[i + 1].y);
              cs[4] += bf_lo(v[i].z) + bf_lo(v[i + 1].z); cs[5] += bf_hi(v[i].z) + bf_hi(v[i + 1].z);
              cs[6] += bf_lo(v[i].w) + bf_lo(v[i + 1].w); cs[7] += bf_hi(v[i].w) + bf_hi(v[i + 1].w);
            }
          }
          {
            const bool u4 = lane & 16, u2 = lane & 8, u1 = lane & 4;
#pragma unroll
            for (int i = 0; i < 4; i++) cs[i] = (u4 ? cs[4 + i] : cs[i]) + __shfl_xor_sync(0xffffffffu, u4 ? cs[i] : cs[4 + i], 16);
#pragma unroll
            for (int i = 0; i < 2; i++) cs[i] = (u2 ? cs[2 + i] : cs[i]) + __shfl_xor_sync(0xffffffffu, u2 ? cs[i] : cs[2 + i], 8);
            cs[0] = (u1 ? cs[1] : cs[0]) + __shfl_xor_sync(0xffffffffu, u1 ? cs[0] : cs[1], 4);
          }
          if (warp == 3 && elect()) {
            mbar_expect_tx(BAR(B_PHI), 12288);
            tma_load_2d(sb + OFF_PHIK, &P.mPhi, BAR(B_PHI), 0, hp * 64);
            tma_load_2d(sb + OFF_PHIQ, &P.mPhi, BAR(B_PHI), (int)zero_after(__float_as_uint(cs[0])), cb * 128);
            tma_load_2d(sb + OFF_PHIQ + 4096, &P.mPhi, BAR(B_PHI), (int)zero_after(__float_as_uint(cs[0])), cb * 128 + 64);
          }
          st_rec8(&g_colsum[kq][cg * 32 + (lane & 3) * 8 + (lane >> 2)], __float_as_uint(cs[0]), ep + 1);
          if (lane == 0) mbar_arrive(BAR(B_CSD));
        }
      asm volatile("setmaxnreg.dec.sync.aligned.u32 32;");
      if (warp == 0) {
        int pc = 0;
#pragma unroll 1
        for (int it = K2W; it < 16; it++) {
          mbar_wait(BAR(it >= 4 ? B_DKV + it - 4 : it == 3 ? K3B : B_FKV));
          if (elect()) {
            load_kv(it);
#pragma unroll 1
            for (int n = tab4(PF_EARLY << 16, it); n > 0; n--) prefetch(pc++);
          }
        }
#pragma unroll 1
        for (int it = 0; it < 16; it++) {
          const uint32_t fb = BAR(B_FQ + it), s = sb + tab4(Q_BSLOTS, it) * SLOT;
          int kc = (int)tab4(Q_CHUNKS, it);
          const bool own = (kc >> 1) == cb;
          kc = (own ? 10 + (kc & 1) : it >= 14 ? 2 * cb + (kc & 1) : kc) * 64;
          if (it == 5) mbar_wait(BAR(B_DKV + 15));
          mbar_wait(it >= QD ? BAR(B_DQ + it - QD) : BAR(B_DKV + 12 + (own && it < 4 ? it : it >> 1)));
          if (elect()) {
            mbar_expect_tx(fb, it < 4 && !own ? SLOT : 2 * SLOT);
            if (it >= 4 || own) tma_load_2d(sb + tab4(Q_ASLOTS, it) * SLOT, &P.mX, fb, kc, rb * 128);
            tma_load_2d(s, &P.mW, fb, cb * 128, kc);
            tma_load_2d(s + 8192, &P.mW, fb, cb * 128 + 64, kc);
          }
        }
        mbar_wait(BAR(B_KVRDY));
        const unsigned tag = lds_u(sb + OFF_RED + 4);
        const unsigned* fp = &g_oflag[rb][cb][lane & 15].x;
        uint32_t seen = 0, all = 0, perm = 0, pv = ld_relaxed(fp), left = cb < 3 ? (0x4015u ^ (1u << (2 * cb))) : 0x15u;
#pragma unroll 1
        for (int j = 2; j < 16; j++) {
          if (!DYN || j >= 5) left = 1u << pc_chunk(j, cb);
          if (j == GATE) all = 0xFFFFu;
#pragma unroll 1
          for (int it = 0; it < SPIN && j <= 8 && !((seen & (seen >> 1) & left) && (seen & all) == all); it++) {
            seen |= __ballot_sync(0xffffffffu, pv == tag);
            pv = ld_relaxed(fp);
          }
          const int kc = (__ffs(j <= 8 ? seen & (seen >> 1) & left : left) - 1) & 15;
          left ^= 1u << kc;
          const int dj = j < 5 ? (kc == 14 ? cb : kc >> 1) + 2 - j : 0;
          const int ds = j < 5 ? dj : (int)(perm << 12) >> 28;
          perm = (perm << 4) | (ds & 15);
          mbar_wait(BAR(j < 4 ? B_KVRDY : j < (EB ? 5 : 6) ? B_QREAD : B_DC + j - 5));
          if (elect()) {
            if (DYN) sts_u2(sb + OFF_RED + 64 + j * 8, dj * 8, ds * 1024);
            mbar_expect_tx(BAR(B_FKV + j), (SKIP & 2) ? 0 : SLOT);
            if (!(SKIP & 2)) asm volatile("cp.async.bulk.shared::cluster.global.mbarrier::complete_tx::bytes [%0], [%1], %2, [%3];"
              :: "r"(sb + tab4(PC_ASLOTS, j) * SLOT), "l"(&g_o[rb][kc][0][0][0]), "n"(SLOT), "r"(BAR(B_FKV + j)) : "memory");
          }
        }
      } else {
        if (warp == 1) {
#pragma unroll 1
          for (int j = 0; j < 16; j++) {
            uint32_t s = sb + tab4(PC_BSLOTS, j) * SLOT;
            const uint32_t fb = BAR(B_FB + j);
            const int kc = pc_chunk(j, cb);
            mbar_wait(BAR(tab8(WO_WAIT0, WO_WAIT1, j)));
            mbar_wait(BAR(tab8(WO_PACE0, WO_PACE1, j)));
            if (DYN && j >= 7) s += lds_u(sb + OFF_RED + 28 + j * 8) * 16;
            if (elect()) {
              mbar_expect_tx(fb, (SKIP & 1) ? 0 : SLOT);
              if (!(SKIP & 1)) {
              tma_load_2d(s, &P.mWo, fb, cb * 128, kc * 64);
              tma_load_2d(s + 8192, &P.mWo, fb, cb * 128 + 64, kc * 64);
              }
            }
          }
        } else if (warp == 3) {
#pragma unroll 1
          for (int c = PF_FIRST; c < 26; c++) {
            mbar_wait(BAR(c < 16 ? tab8(PF_PACE0, PF_PACE1, c) : tab8(PF_PACE2, PF_PACE3, c - 16)));
            if (elect()) prefetch(c);
          }
          __syncwarp();
          if (lane == 0) mbar_arrive(BAR(B_KVRDY));
          if (ffn) mbar_wait(BAR(B_TCH));
          mbar_wait(BAR(B_DC + 10));
#pragma unroll 1
          for (int i = 0; i < 4; i++) st_rec16(&g_o[rb][16][2 * i + (lane >> 4)][cb & 3][(lane & 14) * 2 + (lane & 1) + (cb >> 2) * 2], 0u, 0u, 0u, 0u);
          st_rec16(&g_o[rb][17][0][cb][lane], 0u, 0u, 0u, 0u);
          if (lane < 2) st_rec16(reinterpret_cast<uint4*>(&g_key[cb][rb >> 2][(rb & 3) * 4]) + lane, 0u, 0u, 0u, 0u);
          __syncwarp();
          if (lane == 0) mbar_arrive(BAR(B_RESET2));
        } else {
          mbar_wait(BAR(B_DQ + RSTQ));
#pragma unroll 1
          for (int i = 0; i < 9; i++) {
            st_rec16(&g_kvp[2 * hp][rbk][0][i * 32 + lane], 0u, 0u, 0u, 0u);
            st_rec16(&g_kvp[2 * hp + 1][rbk][0][i * 32 + lane], 0u, 0u, 0u, 0u);
          }
#pragma unroll 1
          for (int i = 0; i < 3; i++) st_rec16(&g_kvr[2 * hp + (lane >> 4)][i][i < 2 ? rbk * 16 + (lane & 15) : rbk * 4 + (lane & 3)], 0u, 0u, 0u, 0u);
          if (lane < 16) st_rec16(&g_oflag[rb][lane >> 1][cb * 2 + (lane & 1)], 0u, 0u, 0u, 0u);
          __syncwarp();
          if (lane == 0) mbar_arrive(BAR(B_RESET));
          if (ffn) {
#pragma unroll 1
            for (int n = 0; n < 12; n++) {
              const int i = (int)tab4(FFN_ORDER, n);
              uint32_t s = sb + tab4(FFN_SLOTS, i) * SLOT;
              const uint32_t fb = BAR(B_FW + i);
              mbar_wait(BAR(tab8(FFN_WAIT0, FFN_WAIT1, n)));
              mbar_wait(BAR(tab8(FFN_PACE0, FFN_PACE1, n)));
              if (DYN && i == 7) s += lds_u(sb + OFF_RED + 84) * 16;
              if (elect()) {
                mbar_expect_tx(fb, (SKIP & 4) ? 0 : SLOT);
                if (!(SKIP & 4)) tma_load_3d_ef(s, i >= 8 ? &P.mWd : (i & 1) ? &P.mWu : &P.mWg, fb, i < 8 ? fi * 32 : 0, i < 8 ? (i >> 1) * 256 : fi * 32, i < 8 ? 0 : (i - 8) * 4);
              }
            }
          }
        }
      }
    } else {
      asm volatile("barrier.sync 0;" ::: "memory");
      const int t = tid - 256;
      const unsigned tag = ld_relaxed(&g_epoch) + 1;
      if (warp == 0) {
        float s = 0.f;
#pragma unroll
        for (int i = 0; i < 4; i++) s += sum8(ldg_nc16(P.wr + i * 256 + lane * 8));
        const uint2 w = *reinterpret_cast<const uint2*>(P.wr + cb * 128 + lane * 4);
        s = warp_sum(s);
        if (lane == 0) { sts_f(sb + OFF_RED, s); sts_u(sb + OFF_RED + 4, tag); sts_u(sb + OFF_RED + 16, 0u); }
        if (lane == 1) { const uint32_t t3 = tag % 3u + 1u; sts_u2(sb + OFF_RED + 8, (t3 & 1u) | ((t3 & 2u) << 15), t3); }
        const uint32_t a = sb + OFF_WR + (lane & 1) * 128 + (lane >> 1) * 4;
        sts_u(a, w.x); sts_u(a + 64, w.y);
      }
      __syncwarp();
      {
        const __nv_bfloat16* xp = P.x + (size_t)(b * 16 + warp * 4 + (lane >> 3)) * DM + (lane & 7) * 8;
        float sh = 0.f, s0 = 0.f, q0 = 0.f, s1 = 0.f, q1 = 0.f;
        uint32_t ns = 0;
#pragma unroll 1
        for (int g = 0; g < 16 / SXN; g++) {
          uint4 xv[SXN];
          mbar_wait(BAR(B_FKV + SX0 + g * SXD));
#pragma unroll
          for (int i = 0; i < SXN; i++) xv[i] = ldg_nc16(xp + (g * SXN + i) * 64);
          if (g == 0) {
            sh = __shfl_sync(0xffffffffu, bf_lo(xv[0].x), lane & 24);
            ns = pack_bf16(-sh, -sh);
          }
#pragma unroll
          for (int i = 0; i < SXN; i++) {
              const uint32_t a = hadd2(xv[i].x, ns), c = hadd2(xv[i].y, ns), d = hadd2(xv[i].z, ns), e = hadd2(xv[i].w, ns);
              const uint32_t u = hadd2(hadd2(a, c), hadd2(d, e)), w = hsq2(a, hsq2(c, hsq2(d, hsq2(e, 0u))));
              s0 += bf_lo_p(u); s1 += bf_hi(u); q0 += bf_lo_p(w); q1 += bf_hi(w);
          }
        }
        s0 += s1; q0 += q1;
#pragma unroll
        for (int m = 4; m >= 1; m >>= 1) { s0 += __shfl_xor_sync(0xffffffffu, s0, m); q0 += __shfl_xor_sync(0xffffffffu, q0, m); }
        s0 *= (1.f / DM);
        const float var = fmaxf(q0 * (1.f / DM) - s0 * s0, 0.f);
        if ((lane & 7) == 0) st_rec16(&g_rowstat[b * 16 + warp * 4 + (lane >> 3)], __float_as_uint(rsq(var + 1e-5f)), __float_as_uint(-(s0 + sh)), 0u, tag);
      }
      {
        const uint4* rp = &g_rowstat[rb * 128 + t];
        const uint4* rq = &g_rowstat[(rb ^ 1) * 128 + t];
        const uint2* c0 = &g_colsum[0][1024 + (t >> 6) * 1024 + hp * 64 + (t & 63)];
        const uint2* c1 = &g_colsum[0][cb * 128 + t];
        uint4 v0, v1; uint2 u[8];
#pragma unroll 1
        for (int it = 0; it < SPIN; it++) {
          v0 = ld_rec16(rp); v1 = ld_rec16(rq);
          bool ok = true;
#pragma unroll
          for (int i = 0; i < 4; i++) { u[i] = ld_rec8(c0 + i * 3072); u[4 + i] = ld_rec8(c1 + i * 3072); }
#pragma unroll
          for (int i = 0; i < 8; i++) ok = ok && u[i].y == tag;
          if (__all_sync(0xffffffffu, ok && v0.w == tag && v1.w == tag)) break;
          __nanosleep(100);
        }
        sts_u(sb + OFF_RSTAT + t * 4, v0.x); sts_u(sb + OFF_RSTAT + (t + 128) * 4, v1.x);
        mbar_wait(BAR(B_CSD));
        {
          const uint32_t m0 = split_bf16(__uint_as_float(v0.y)), m1 = split_bf16(__uint_as_float(v1.y));
          sts_u4(sb + 12 * SLOT + 4096 + t * 16, m0, m0 & 0xFFFFu, 0u, 0u);
          sts_u4(sb + 12 * SLOT + 6144 + t * 16, m1, m1 & 0xFFFFu, 0u, 0u);
          sts_u2(sb + 12 * SLOT + 8192 + t * 8, 0u, 0u);
        }
#pragma unroll
        for (int e = 0; e < 2; e++) {
          const uint32_t hl = split_bf16((__uint_as_float(u[4 * e].x) + __uint_as_float(u[4 * e + 1].x)) + (__uint_as_float(u[4 * e + 2].x) + __uint_as_float(u[4 * e + 3].x)));
          const uint32_t a = sb + 12 * SLOT + e * 2048 + (t >> 6) * 1024 + (t & 7) * 2, ch = (uint32_t)(t >> 3) & 7u;
#pragma unroll
          for (uint32_t r = 0; r < 8; r++) sts_h(a + r * 128 + ((ch ^ r) << 4), r < 2 ? hl : r == 2 ? hl >> 16 : 0u);
        }
        sts_u(sb + OFF_ONES + t * 4, 0x3F803F80u);
        sts_u(sb + OFF_ONES + 512 + t * 4, 0x3F803F80u);
        if (t < 36) sts_u(sb + OFF_SEL + t * 4, (t & 4) ? 0u : 0x3F803F80u);
        {
          const uint32_t one = (t & 56) == 24 ? 0x3F80u << ((t & 1) * 16) : 0u, w = (t >> 1) & 3;
          sts_u4(sb + OFF_EYE + t * 16, w == 0 ? one : 0u, w == 1 ? one : 0u, w == 2 ? one : 0u, w == 3 ? one : 0u);
        }
        fence_async_smem();
        bar_sync(3, 128);
      }
      asm volatile("setmaxnreg.inc.sync.aligned.u32 160;");
      {
        float a0[64], a1[64];
        {
          wg_fence();
          wg_n128<0, 1>(a0, ext_a(sb, 0), ext_b(sb, 1), 0);
          wg_n128<0, 1>(a1, ext_a(sb, 64), ext_b(sb, 1), 0);
          wg_commit();
          wg_wait<0>();
          mbar_arrive(BAR(B_STAT));
        }
        {
#pragma unroll 1
          for (int it = 12; it < 16; it++) mbar_wait(BAR(B_FKV + it));
          mbar_wait(BAR(B_QGO));
#pragma unroll 1
          for (int it = 0; it < 16; it++) {
            mbar_wait(BAR(B_FQ + it));
            const uint64_t da = mk_desc(sb + tab4(Q_ASLOTS, it) * SLOT, 16, 1024, 1);
            const uint64_t db = mk_desc(sb + tab4(Q_BSLOTS, it) * SLOT, 8192, 1024, 1);
#pragma unroll
            for (int hf = 0; hf < 2; hf++) {
              int yt = THR > hf ? fresh_tid() : tid;
              if (hf && THR > 1) asm volatile("mov.u32 %0, %%tid.y;" : "=r"(yt));
              wg_fence();
#pragma unroll
              for (int kk = hf ? QSPL : 0; kk < (hf ? 4 : QSPL); kk++) {
                wg_n128<0, 1>(a0, da + kk * 2, db + kk * 128, 1);
                if (THR > 2 && kk == 2 * hf && yt == 8192) pin_order();
                wg_n128<0, 1>(a1, da + kk * 2 + 512, db + kk * 128, 1);
              }
              wg_commit();
              if (hf == 0 || QW2) wg_wait<1>();
              if (hf == 0 && it > 0 && (yt & 127) == 0) mbar_arrive(BAR(B_DQ + it - 1));
            }
          }
        }
        MMA_IDS
        const uint32_t qa = __shfl_sync(0xffffffffu, sb + 10 * SLOT + srow * 128 + (sx << 4), lane);
        mbar_wait(BAR(B_KVFREE));
        wg_wait<0>();
        if (leader) mbar_arrive(BAR(B_DQ + 15));
#pragma unroll
        for (int c = 0; c < 2; c++) {
#pragma unroll
          for (int jj = 0; jj < 4; jj++)
#pragma unroll
            for (int mb = 0; mb < 2; mb++) {
              const float* a = mb ? &a1[32 * c + 8 * jj] : &a0[32 * c + 8 * jj];
              stsm_x4((qa ^ (32 * jj)) + c * SLOT + mb * 8192, pack_bf16(a[0], a[1]), pack_bf16(a[2], a[3]), pack_bf16(a[4], a[5]), pack_bf16(a[6], a[7]));
            }
          fence_async_smem();
          mbar_arrive(BAR(B_QD + c));
          if ((QPIN >> c) & 1) pin_order();
        }
        const uint32_t tg = lds_u(sb + OFF_RED + 8);
        const uint32_t ka = sb + 12 * SLOT + srow * 64 + (((uint32_t)(lane >> 4) ^ ((srow >> 1) & 3)) << 4);
        const uint4* const src = &g_kvr[4 * cb][0][tid & 127];
        const uint2* const srz = reinterpret_cast<const uint2*>(&g_kvr[4 * cb][2][(tid & 127) >> 2]);
        uint4 a[8];
        uint2 z[4];
#pragma unroll
        for (int i = 0; i < 8; i++) a[i] = make_uint4(0u, 0u, 0u, 0u);
        auto put = [&]() {
#pragma unroll
          for (int h = 0; h < 4; h++) {
            stsm_x4(ka + h * 4096, a[2 * h].x, a[2 * h].y, a[2 * h].z, a[2 * h].w);
            stsm_x4((ka ^ 32) + h * 4096, a[2 * h + 1].x, a[2 * h + 1].y, a[2 * h + 1].z, a[2 * h + 1].w);
            if (h & 1)
              stsm_x4((ka ^ ((h - 1) * 16)) + SLOT, __byte_perm(z[h - 1].y, 0x3F80u, 0x5410), __byte_perm(z[h - 1].y, 0x3F80u, 0x5432),
                      __byte_perm(z[h].y, 0x3F80u, 0x5410), __byte_perm(z[h].y, 0x3F80u, 0x5432));
          }
        };
#pragma unroll 1
        for (int it = 0; it < SPIN; it++) {
#pragma unroll
          for (int i = 0; i < 8; i++) {
            ld_rec16_stale(a[i], src + (i >> 1) * 384 + (i & 1) * 128, tg);
            if (i & 1) z[i >> 1] = ld_rec8(srz + (i >> 1) * 768);
          }
          const uint32_t bad = ((differ(a[0].x, a[1].x, tg) | differ(a[2].x, a[3].x, tg)) | (differ(a[4].x, a[5].x, tg) | differ(a[6].x, a[7].x, tg))) |
                               (differ(z[0].x, z[1].x, tg) | differ(z[2].x, z[3].x, tg));
          if (GSPEC) put();
          if (__all_sync(0xffffffffu, (bad & OTAG) == 0)) break;
        }
        if (!GSPEC) put();
        fence_async_smem();
        __syncwarp();
        if (lane == 0) mbar_arrive(BAR(B_KVRDY));
      }
    }
    if (wg == 3) mbar_wait(BAR(B_DC + 15));
    asm volatile("setmaxnreg.inc.sync.aligned.u32 160;");
    const int w8 = (wg - 2) * 4 + warp;
    uint32_t wf[32][4], wd[16][4];
    {
      const int lane = fresh_tid() & 31;
      const uint32_t mrow = (uint32_t)((lane & 7) + (lane >> 4) * 8), mch = (uint32_t)(lane >> 3) & 1u;
      if (ffn) mbar_wait(BAR(B_FW + w8));
      uint32_t wsm = sb + tab4(FFN_SLOTS, w8) * SLOT + mrow * 64;
      if (DYN && w8 == 7) wsm += lds_u(sb + OFF_RED + 84) * 16;
      const uint32_t sw = (mrow >> 1) & 3;
#pragma unroll
      for (int i = 0; i < 16; i++) {
        ldsm_x4_t(wf[2 * i], wsm + i * 1024 + ((mch ^ sw) << 4));
        ldsm_x4_t(wf[2 * i + 1], wsm + i * 1024 + (((2 + mch) ^ sw) << 4));
      }
      uint32_t dep = 0;
#pragma unroll
      for (int i = 0; i < 32; i++) dep ^= wf[i][0];
      if (w8 < 4 && lane == 0) mbar_arrive(BAR(B_REL + w8) + zero_after(dep));
    }
    if (ffn) {
      const int lane = fresh_tid() & 31;
      if (wg == 2) mbar_wait(BAR(B_DC + 12));
      st_rec16(&g_ypart[w8 * 16 + (lane >> 1)][fi][lane & 1], 0u, 0u, 0u, 0u);
      __syncwarp();
    }
    mbar_wait(BAR(B_DC + 15));
    asm volatile("setmaxnreg.inc.sync.aligned.u32 %0;" :: "n"(256 - TREG));
    {
      const int lane = fresh_tid() & 31;
      const uint32_t mrow = (uint32_t)((lane & 7) + (lane >> 4) * 8), mch = (uint32_t)(lane >> 3) & 1u;
      if (ffn) mbar_wait(BAR(B_FW + 8 + (w8 >> 1)));
      const uint32_t dsm = sb + tab4(FFN_SLOTS, 8 + (w8 >> 1)) * SLOT + (w8 & 1) * 8192 + mrow * 128;
#pragma unroll
      for (int i = 0; i < 8; i++) {
        const uint32_t a = dsm + (i >> 2) * 4096 + ((((uint32_t)(i & 3) * 2 + mch) ^ (mrow & 7)) << 4);
        ldsm_x4_t(wd[2 * i], a);
        ldsm_x4_t(wd[2 * i + 1], a + 2048);
      }
    }
    {
      const int t = fresh_tid() - 256, lane = t & 31, c = lane & 3;
      const unsigned tag = lds_u(sb + OFF_RED + 4);
      uint32_t xw = sb + OFF_PHIQ + w8 * 512 + (lane >> 4) * 64 + c * 16 + (lane & 12);
      uint32_t xr = sb + OFF_PHIQ + w8 * 512 + c * 16;
      uint32_t pw = sb + OFF_CS + (uint32_t)(w8 * 32 + c * 8 + (lane >> 2)) * 4;
      const uint32_t t3 = lds_u(sb + OFF_RED + 12);
      const uint2* kp = &g_key[cb][0][(lane & 15) * 4];
      const char* src = reinterpret_cast<const char*>(&g_o[0][17][0][w8 & 6][lane]);
      uint32_t* yd = &g_ypart[w8 * 16 + c][fi][0].x + (lane >> 2);
      xw = __shfl_sync(0xffffffffu, xw, lane); xr = __shfl_sync(0xffffffffu, xr, lane); pw = __shfl_sync(0xffffffffu, pw, lane);
      kp = settle(kp, lane); src = settle(src, lane); yd = settle(yd, lane);
      uint32_t wkey;
      {
        uint2 v;
        mbar_wait(BAR(B_KEY));
#pragma unroll 1
        for (int it = 0; it < SPIN; it++) {
          v = ld_rec8(kp);
          if (__all_sync(0xffffffffu, v.y == tag)) break;
        }
        wkey = __reduce_max_sync(0xffffffffu, v.x);
      }
      {
        asm volatile("mad.wide.u32 %0, %1, 2304, %0;" : "+l"(src) : "r"(wkey & 0x780u));
        uint4 v0, v1;
#pragma unroll 1
        for (int it = 0; it < SPIN; it++) {
          v0 = ld_rec16(reinterpret_cast<const uint4*>(src)); v1 = ld_rec16(reinterpret_cast<const uint4*>(src) + 32);
          if (__all_sync(0xffffffffu, v0.w == tag && v1.w == tag)) break;
        }
        sts_u(xw, v0.x); sts_u(xw + 128, v0.y); sts_u(xw + 256, v1.x); sts_u(xw + 384, v1.y);
        __syncwarp();
      }
      if (t == 0) mbar_arrive(BAR(B_ROW));
      if (ffn) {
        {
          uint4 xb[8];
#pragma unroll
          for (int i = 0; i < 8; i++) xb[i] = lds_u4(xr + i * 64);
          float d[16];
#pragma unroll
          for (int i = 0; i < 16; i++) d[i] = 0.f;
#pragma unroll
          for (int i = 0; i < 8; i++) {
            mma_bf16(&d[0], wf[4 * i], xb[i].x, xb[i].y); mma_bf16(&d[4], wf[4 * i + 1], xb[i].x, xb[i].y);
            mma_bf16(&d[8], wf[4 * i + 2], xb[i].z, xb[i].w); mma_bf16(&d[12], wf[4 * i + 3], xb[i].z, xb[i].w);
          }
          const float v = pick4(c, d[0], d[2], d[4], d[6]) + pick4(c, d[8], d[10], d[12], d[14]);
          sts_f(pw, v);
        }
        bar_sync(2, 256);
        uint32_t ab[4];
        {
          const uint32_t pr = sb + OFF_CS + lane * 4;
          float p[8];
#pragma unroll
          for (int i = 0; i < 8; i++) p[i] = lds_f(pr + (i & 3) * 256 + (i >> 2) * 128);
          const float g = (p[0] + p[1]) + (p[2] + p[3]);
          const float u = (p[4] + p[5]) + (p[6] + p[7]);
          const float act = (g * u) * rcp(1.f + ex2(-g * L2E));
          const uint32_t pair = pack_bf16(act, __shfl_down_sync(0xffffffffu, act, 1));
#pragma unroll
          for (int i = 0; i < 4; i++) ab[i] = __shfl_sync(0xffffffffu, pair, i * 8 + c * 2);
        }
        float d[32];
#pragma unroll
        for (int i = 0; i < 32; i++) d[i] = 0.f;
#pragma unroll
        for (int h = 0; h < 8; h += DORD) {
#pragma unroll
          for (int i = h; i < h + DORD; i++) mma_bf16(&d[4 * i], wd[2 * i], ab[0], ab[1]);
#pragma unroll
          for (int i = h; i < h + DORD; i++) mma_bf16(&d[4 * i], wd[2 * i + 1], ab[2], ab[3]);
        }
#pragma unroll
        for (int i = 0; i < 4; i++)
          asm volatile("st.relaxed.gpu.global.u32 [%0], %1;" :: "l"(yd + i * 4 * NFFN * 8),
                       "r"((__float_as_uint(pick4(c, d[8 * i], d[8 * i + 2], d[8 * i + 4], d[8 * i + 6])) & ~3u) | t3) : "memory");
      }
      if (b == 0 && t == 32) g_epoch = tag;
      if (w8 == 0) {
        const int wrow = wkey & (SEQ - 1);
        const uint4* fp = &g_o[wrow >> 7][17][2][0][b * 4 + (lane & 1) * 2 + ((lane >> 1) & 1)];
        const uint4* yp = &g_ypart[b][0][0] + lane;
        uint32_t* const op = settle(reinterpret_cast<uint32_t*>(P.out + (size_t)wrow * DM + b * 8 + (lane & 1) * 4 + (lane & 2)), lane);
        const float sig = __shfl_sync(0xffffffffu, rcp(1.f + ex2(-__uint_as_float(wkey ^ (~(uint32_t)((int)wkey >> 31) | 0x80000000u)) * L2E)), lane);
        uint4 fin;
#pragma unroll 1
        for (int it = 0; it < SPIN; it++) {
          fin = ld_rec16(fp);
          if (__all_sync(0xffffffffu, fin.w == tag)) break;
        }
        if (YDLY) {
          const uint32_t c0 = clock();
#pragma unroll 1
          for (int it = 0; it < 1000 && (uint32_t)clock() - c0 < YDLY; it++) { }
        }
        const bool up = lane & 2;
        float y0, y1;
#pragma unroll 1
        for (int it = 0; it < SPIN; it++) {
          uint4 v[7];
#pragma unroll
          for (int i = 0; i < 7; i++) v[i] = ld_rec16(yp + i * 32);
          uint32_t bad[4];
          float y[4];
#pragma unroll
          for (int i = 0; i < 4; i++) {
            const uint32_t* q = reinterpret_cast<const uint32_t*>(v) + i;
            const float* f = reinterpret_cast<const float*>(v) + i;
            bad[i] = (differ(q[0], q[4], t3) | differ(q[8], q[12], t3)) | (differ(q[16], q[20], t3) | (q[24] ^ t3));
            y[i] = ((f[0] + f[4]) + (f[8] + f[12])) + ((f[16] + f[20]) + f[24]);
          }
          y0 = (up ? y[2] : y[0]) + __shfl_xor_sync(0xffffffffu, up ? y[0] : y[2], 2);
          y1 = (up ? y[3] : y[1]) + __shfl_xor_sync(0xffffffffu, up ? y[1] : y[3], 2);
          if (__all_sync(0xffffffffu, (((bad[0] | bad[1]) | (bad[2] | bad[3])) & 3u) == 0)) break;
        }
#pragma unroll
        for (int m = 4; m <= 16; m <<= 1) { y0 += __shfl_xor_sync(0xffffffffu, y0, m); y1 += __shfl_xor_sync(0xffffffffu, y1, m); }
        asm volatile("{\n.reg .pred p;\nsetp.lt.u32 p, %2, 4;\n@p st.global.u32 [%0], %1;\n}\n" :: "l"(op),
                     "r"(pack_bf16(fmaf(y0, sig, bf_lo(fin.y) + bf_lo(fin.x)), fmaf(y1, sig, bf_hi(fin.y) + bf_hi(fin.x)))), "r"(lane) : "memory");
      }
    }
  } else {
    if (PAD && blockIdx.x == 5000) padn<PAD>();
    asm volatile("setmaxnreg.inc.sync.aligned.u32 160;");
    asm volatile("barrier.sync 0;" ::: "memory");
    {
      const bool leader = (tid & 127) == 0;
      {
        float a0[64], a1[64];
        if (FINE) {
          const uint64_t da = mk_desc(sb + wg * SLOT, 16, 1024, 1), db = mk_desc(sb + 2 * SLOT, 8192, 1024, 1);
          mbar_wait(BAR(B_FKV));
          wg_fence();
          wg_n128<0, 1>(a0, da, db, 0);
          wg_n128<0, 1>(a0, da + 2, db + 128, 1);
          mbar_wait(BAR(B_F0));
          wg_fence();
          wg_n128<0, 1>(a0, da + 4, db + 256, 1);
          wg_n128<0, 1>(a0, da + 6, db + 384, 1);
          mbar_wait(BAR(B_F0 + 1));
          wg_fence();
#pragma unroll
          for (int kk = 0; kk < 4; kk++) wg_n128<0, 1>(a1, da + kk * 2 + 512, db + kk * 128, kk != 0);
          wg_commit();
        }
#pragma unroll 1
        for (int it = FINE; it < 16; it++) {
          mbar_wait(BAR(B_FKV + it));
          const uint32_t s = sb + (uint32_t)(it & 3) * 3 * SLOT;
          const uint64_t da = mk_desc(s + wg * SLOT, 16, 1024, 1), db = mk_desc(s + 2 * SLOT, 8192, 1024, 1);
          wg_fence();
#pragma unroll
          for (int kk = 0; kk < 4; kk++) {
            wg_n128<0, 1>(a0, da + kk * 2, db + kk * 128, (it | kk) != 0);
            wg_n128<0, 1>(a1, da + kk * 2 + 512, db + kk * 128, (it | kk) != 0);
            if (kk == KSPL) {
              wg_commit();
              wg_wait<1>();
              if (it > 0 && leader) mbar_arrive(BAR(B_DKV + it - 1));
              if (kk < 3) wg_fence();
            }
          }
          if (KSPL < 3) wg_commit();
        }
        mbar_wait(BAR(B_STAT));
        wg_fence();
        wg_n128<0, 1>(a0, ext_a(sb, wg * 128), ext_b(sb, 0), 1);
        wg_n128<0, 1>(a1, ext_a(sb, wg * 128 + 64), ext_b(sb, 0), 1);
        wg_commit();
        if (leader) mbar_arrive(BAR(B_QGO));
        mbar_wait(BAR(B_PHI));
        wg_wait<0>();
        if (leader) mbar_arrive(BAR(B_DKV + 15));
        if (PIN & 2) pin_order();
        MMA_IDS
        const uint32_t rs = sb + OFF_RSTAT + (uint32_t)(wg * 128 + lr) * 4;
        const uint32_t vt = sb + 12 * SLOT + wg * 4096 + srow * 64 + (((uint32_t)(lane >> 4) ^ ((srow >> 1) & 3)) << 4);
        float pa[16], pb[16];
        uint32_t vp[16];
        const uint64_t dw = mk_desc(sb + OFF_PHIK, 16, 512, 2);
        auto pack_v = [&](const float* a, int mb) {
          const float r0 = lds_f(rs + mb * 256), r1 = lds_f(rs + mb * 256 + 32);
#pragma unroll
          for (int i = 0; i < 16; i++) vp[i] = pack_bf16(a[32 + 2 * i] * ((i & 1) ? r1 : r0), a[33 + 2 * i] * ((i & 1) ? r1 : r0));
        };
        auto put_v = [&]() {
#pragma unroll
          for (int jj = 0; jj < 4; jj++) stsm_x4((vt + (jj >> 1) * 8192) ^ (32 * (jj & 1)), vp[4 * jj], vp[4 * jj + 1], vp[4 * jj + 2], vp[4 * jj + 3]);
        };
        bar_sync(1, 256);
        pack_v(a0, 0);
        put_v();
        auto logits = [&](const uint32_t (&k)[16]) {
          wg_fence();
          wg_n32_rs<1>(pa, k[0], k[1], k[2], k[3], dw, 0);
          wg_n32_rs<1>(pb, k[8], k[9], k[10], k[11], dw + 128, 0);
          wg_n32_rs<1>(pa, k[4], k[5], k[6], k[7], dw + 64, 1);
          wg_n32_rs<1>(pb, k[12], k[13], k[14], k[15], dw + 192, 1);
          wg_commit();
        };
        uint32_t k0[16], k1[16];
        pin_order();
#pragma unroll
        for (int i = 0; i < 16; i++) k0[i] = pack_pin(a0[2 * i], a0[2 * i + 1]);
        logits(k0);
#pragma unroll
        for (int i = 0; i < 16; i++) k1[i] = pack_pin(a1[2 * i], a1[2 * i + 1]);
        pack_v(a1, 1);
        if (PIN & 1) pin_order();
        wg_wait<0>();
        float kv[20];
        auto half = [&](float (&p0)[16], float (&p1)[16], int mb) {
          const float sc0 = lds_f(rs + mb * 256) * L2E, sc1 = lds_f(rs + mb * 256 + 32) * L2E;
          const uint32_t ft = sb + 10 * SLOT + wg * 8192 + srow * 128 + (sx << 4);
          uint32_t fo[32];
          auto put = [&](int h) {
#pragma unroll
            for (int g = 4 * h; g < 4 * h + 4; g++) stsm_x4((ft + h * SLOT) ^ (32 * (g & 3)), fo[4 * g], fo[4 * g + 1], fo[4 * g + 2], fo[4 * g + 3]);
          };
          float tot;
          {
            tot = feature_fast(p0, sc0, sc1, &fo[0], [&]() {
              if (mb) {
                if (PIN & 128) pin_order();
                wg_wait<0>();
                bar_arrive(6 + wg, 256);
              }
            });
            if (mb) {
              bar_sync(7 - wg, 256);
              put_v();
            }
            put(0);
            tot += feature_fast(p1, sc0, sc1, &fo[16], []() {});
          }
          put(1);
          if (warp_fails(tot < FAST_LIMIT)) {
            feature_shifted(p0, p1, sc0, sc1, fo);
            put(0);
            put(1);
          }
          if (mb == 0) logits(k1);
          fence_async_smem();
          bar_sync(1, 256);
          if (PIN & 4) pin_order();
          const uint64_t d = mk_desc(sb + (10 + wg) * SLOT, 16, 1024, 1);
          const uint64_t e = mk_desc(sb + 12 * SLOT + wg * 8192, OFF_ONES - 12 * SLOT - wg * 8192, 512, 2);
          wg_fence();
#pragma unroll
          for (int kk = 0; kk < 8; kk++) wg_n40<1, 1>(kv, d + kk * 128, e + kk * (64 - (64 << 16)), (mb | kk) != 0);
          wg_commit();
        };
        half(pa, pb, 0);
        wg_wait<1>();
        half(pa, pb, 1);
        mbar_wait(BAR(B_RESET));
        const uint32_t tg = lds_u(sb + OFF_RED + 8);
        uint4* const dst = settle(&g_kvp[2 * hp + wg][rbk][0][tid & 127], lane);
        uint4* const dsz = settle(&g_kvp[2 * hp + wg][rbk][2][(tid & 127) >> 2], lane);
        const int si = warp < 2 ? rbk * 16 + (lane & 15) : rbk * 4 + (lane & 3);
        const uint4* const src = &g_kvp[2 * hp + (lane >> 4)][0][warp][si];
        uint4 a[8];
        if (wg == 0 && warp < 3) {
#pragma unroll
          for (int p = 0; p < 8; p++) a[p] = ld_rec16(src + p * 384);
        }
        pin_order();
        wg_wait<0>();
        if (PIN & 8) pin_order();
        {
          uint32_t w[8];
#pragma unroll
          for (int i = 0; i < 8; i++) w[i] = pack_bf16(kv[2 * i], kv[2 * i + 1]);
          w[0] = with_tag(w[0], tg); w[4] = with_tag(w[4], tg);
          st_rec16(dst, w[0], w[1], w[2], w[3]);
          st_rec16(dst + 128, w[4], w[5], w[6], w[7]);
          st_rec16_if((lane & 3) == 0, dsz, tg, pack_bf16(kv[16], kv[18]), 0u, 0u);
          if (leader) mbar_arrive(BAR(B_KVFREE));
        }
        if (wg == 0 && warp < 3) {
          uint32_t v[4];
          uint4* const red = settle(&g_kvr[2 * hp + (lane >> 4)][warp][si], lane);
#pragma unroll 1
          for (int it = 0; it < SPIN; it++) {
#pragma unroll
            for (int p = 0; p < 8; p++) ld_rec16_stale(a[p], src + p * 384, tg);
            const uint32_t bad = (differ(a[0].x, a[1].x, tg) | differ(a[2].x, a[3].x, tg)) | (differ(a[4].x, a[5].x, tg) | differ(a[6].x, a[7].x, tg));
#pragma unroll
            for (int i = 0; i < 4; i++) {
              const uint32_t* q = reinterpret_cast<const uint32_t*>(a) + i;
              if (KSUM) v[i] = hadd2(hadd2(hadd2(q[0], q[4]), hadd2(q[8], q[12])), hadd2(hadd2(q[16], q[20]), hadd2(q[24], q[28])));
            }
            if (__all_sync(0xffffffffu, (bad & OTAG) == 0)) break;
          }
          if (!KSUM) {
#pragma unroll
            for (int i = 0; i < 4; i++) {
              const uint32_t* q = reinterpret_cast<const uint32_t*>(a) + i;
              const uint32_t c0 = hadd2(q[0], q[4]), c1 = hadd2(q[8], q[12]), c2 = hadd2(q[16], q[20]), c3 = hadd2(q[24], q[28]);
              v[i] = pack_bf16((bf_lo(c0) + bf_lo(c1)) + (bf_lo(c2) + bf_lo(c3)), (bf_hi(c0) + bf_hi(c1)) + (bf_hi(c2) + bf_hi(c3)));
            }
          }
          st_rec16(red, with_tag(v[0], tg), v[1], v[2], v[3]);
        }
      }
    }
    const uint32_t stg = sb + wg * 8192;
    uint4* hsrc;
    int trow;
    {
      MMA_IDS
      const unsigned tag = lds_u(sb + OFF_RED + 4);
      const uint32_t tg = lds_u(sb + OFF_RED + 8);
      const uint32_t ln = __shfl_sync(0xffffffffu, (uint32_t)lane, lane);
      uint4* const og = &g_o[rb][0][wg * 4 + warp][0][ln];
      const uint32_t af = sb + (uint32_t)(wg * 4 + warp) * 2048 + ln * 16;
      float acc[64];
      auto tile_addr = [&]() {
        uint32_t l = ln;
        asm volatile("" : "+r"(l));
        return stg + (uint32_t)warp * 2048 + (l & 15) * 128 + (((l >> 4) ^ (l & 7)) << 4);
      };
      auto add_x = [&]() {
        mbar_wait(BAR(B_FQ + 14));
        mbar_wait(BAR(B_FQ + 15));
        const uint64_t da = mk_desc(sb + OFF_EYE + 384, 512, 128, 0), db = mk_desc(stg + SLOT, 7 * SLOT, 4096, 1);
        wg_fence();
#pragma unroll
        for (int s = 0; s < 4; s++) wg_n128<0, 1>(acc, da - s * 8, db + s * 64, s != 0);
        wg_commit();
      };
      auto announce = [&]() {
        if (FLAGB) { if (warp == FLAGW) bar_sync(4 + wg, 128); else bar_arrive(4 + wg, 128); }
        if (warp == FLAGW && ln < 8) asm volatile("st.relaxed.gpu.global.u32 [%0], %1;" :: "l"(&g_oflag[rb][ln][cb * 2 + wg].x), "r"(tag) : "memory");
      };
      auto send = [&](const uint32_t (&a)[16], uint32_t flip, uint32_t slot, int c) {
#pragma unroll
        for (int i = 0; i < 4; i++) sts_u4(af + slot * SLOT + i * 512, a[4 * i] ^ flip, a[4 * i + 1], a[4 * i + 2], a[4 * i + 3]);
        fence_async_smem();
        __syncwarp();
        if (ln == 0) {
          asm volatile("cp.async.bulk.global.shared::cta.bulk_group [%0], [%1], 2048;" :: "l"(og + cb * 2048 + c * 1024), "r"(af + slot * SLOT) : "memory");
          asm volatile("cp.async.bulk.commit_group;" ::: "memory");
        }
        __syncwarp();
      };
      const bool early = !((LATE >> cb) & 1);
      uint32_t A[2][16];
      float u3[20];
      const bool lead = warp == 0 && ln == 0;
      {
        const float sc0 = lds_f(sb + OFF_RSTAT + (uint32_t)(wg * 64 + lr) * 4) * L2E, sc1 = lds_f(sb + OFF_RSTAT + (uint32_t)(wg * 64 + lr + 8) * 4) * L2E;
        auto logits = [&](float (&p0)[16], float (&p1)[16], int c) {
          const uint64_t dq = mk_desc(sb + (10 + c) * SLOT + wg * 8192, 16, 1024, 1), dw = mk_desc(sb + OFF_PHIQ + c * 4096, 16, 512, 2);
          mbar_wait(BAR(B_QD + c));
          wg_fence();
          wg_n32<0, 1>(p0, dq, dw, 0);
          wg_n32<0, 1>(p1, dq + 4, dw + 128, 0);
          wg_n32<0, 1>(p0, dq + 2, dw + 64, 1);
          wg_n32<0, 1>(p1, dq + 6, dw + 192, 1);
          wg_commit();
        };
        auto norm = [&](float (&p)[16], uint32_t (&f)[16], const float (&d)[4]) {
          if (warp_fails(feature_norm<false>(f, d) < FAST_LIMIT)) feature_shifted(p, p, sc0, sc1, f);
        };
        auto apply = [&](float (&u)[20], const uint32_t (&f)[16], int h) {
          const uint64_t d = mk_desc(sb + 12 * SLOT + h * 4096, SLOT - h * 4096 + h * 16, 512, 2);
          wg_fence();
#pragma unroll
          for (int s = 0; s < 4; s++) wg_n40_rs<1>(u, f[4 * s], f[4 * s + 1], f[4 * s + 2], f[4 * s + 3], d + s * 64, s != 0);
          wg_commit();
        };
        float pa[16], pb[16], pc[16], pd[16], u0[20], u1[20], u2[20], da[4], db[4];
        uint32_t f0[16], f1[16], f2[16], f3[16];
        uint4* const od = og + cb * 2048;
        logits(pa, pb, 0);
        wg_wait<0>();
        feature_exp(pa, sc0, sc1, f0, da, sum_b(sb));
        if (PIN & 64) pin_order();
        logits(pc, pd, 1);
        feature_exp(pb, sc0, sc1, f1, db, sum_b(sb));
        wg_wait<1>();
        norm(pa, f0, da);
        if (QORD == 2) {
          feature_exp(pc, sc0, sc1, f2, da, sum_b(sb));
          wg_wait<1>();
          norm(pb, f1, db);
          wg_wait<0>();
          if (lead) mbar_arrive(BAR(B_QREAD));
          norm(pc, f2, da);
          mbar_wait(BAR(B_KVRDY));
          apply(u0, f0, 0);
          apply(u1, f1, 1);
          wg_wait<1>();
          attn_out(u0, tg, &A[0][0], od, early && !(EB & 2));
          if (FLAGP == 2 && early && (EB & 6) != 2) announce();
          wg_wait<0>();
          apply(u2, f2, 2);
          attn_out(u1, tg, &A[0][8], od + 64, early && !(EB & 2));
          if (FLAGP == 3 && early) announce();
          if (early && (EB & 2)) {
            send(A[0], 0u, 11, 0);
            if (!(EB & 4)) announce();
          }
          if (PIN & 16) pin_order();
          feature_exp(pd, sc0, sc1, f3, db, sum_b(sb));
          wg_wait<1>();
          attn_out(u2, tg, &A[1][0], od + 1024, !LPUB);
          wg_wait<0>();
          norm(pd, f3, db);
          apply(u3, f3, 3);
          add_x();
          wg_wait<1>();
        } else {
          wg_wait<0>();
          if (lead) mbar_arrive(BAR(B_QREAD));
          norm(pb, f1, db);
          mbar_wait(BAR(B_KVRDY));
          apply(u0, f0, 0);
          apply(u1, f1, 1);
          if (QORD == 3) {
            feature_exp(pc, sc0, sc1, f2, da, sum_b(sb));
            wg_wait<1>();
            attn_out(u0, tg, &A[0][0], od, early);
            if (early) announce();
            attn_out(u1, tg, &A[0][8], od + 64, early);
          } else {
            wg_wait<1>();
            attn_out(u0, tg, &A[0][0], od, early);
            if (early) announce();
            wg_wait<0>();
            attn_out(u1, tg, &A[0][8], od + 64, early);
            if (PIN & 16) pin_order();
            feature_exp(pc, sc0, sc1, f2, da, sum_b(sb));
          }
          if (PIN & 16) pin_order();
          feature_exp(pd, sc0, sc1, f3, db, sum_b(sb));
          wg_wait<1>();
          norm(pc, f2, da);
          apply(u2, f2, 2);
          wg_wait<1>();
          norm(pd, f3, db);
          apply(u3, f3, 3);
          wg_wait<1>();
          attn_out(u2, tg, &A[1][0], od + 1024, !LPUB);
          add_x();
          wg_wait<1>();
        }
        if (lead) mbar_arrive(BAR(B_XDONE));
        if (!U3L) attn_out(u3, tg, &A[1][8], od + 1088, !LPUB);
        if (U3L < 2 && !early) {
#pragma unroll
          for (int i = 0; i < 4; i++) st_rec16(od + i * 32, A[0][4 * i], A[0][4 * i + 1], A[0][4 * i + 2], A[0][4 * i + 3]);
          announce();
        }
      }
      auto take = [&](uint32_t (&a)[16], int j) {
        const uint32_t s = af + tab4(PC_ASLOTS, j) * SLOT;
#pragma unroll
        for (int i = 0; i < 4; i++) {
          const uint4 v = lds_u4(s + i * 512);
          a[4 * i] = v.x; a[4 * i + 1] = v.y; a[4 * i + 2] = v.z; a[4 * i + 3] = v.w;
        }
      };
      auto check = [&](uint32_t (&a)[16], int j) {
        if (PIN & 256) pin_order();
#pragma unroll
        for (int i = 0; i < 4; i++) a[4 * i] ^= tg;
        if (!(SKIP & 2) && warp_fails((((a[0] | a[4]) | (a[8] | a[12])) & OTAG) == 0)) {
          const uint4* p = og + pc_chunk(j, cb) * 1024;
#pragma unroll 1
          for (int it = 0; it < SPIN; it++) {
#pragma unroll
            for (int i = 0; i < 4; i++) {
              const uint4 v = ld_rec16(p + i * 32);
              a[4 * i] = v.x ^ tg; a[4 * i + 1] = v.y; a[4 * i + 2] = v.z; a[4 * i + 3] = v.w;
            }
            if (__all_sync(0xffffffffu, (((a[0] | a[4]) | (a[8] | a[12])) & OTAG) == 0)) break;
          }
        }
      };
#pragma unroll
      for (int i = 0; i < 4; i++) A[0][4 * i] ^= tg;
      {
        uint32_t bt = (uint32_t)mk_desc(sb + 3 * SLOT, 8192, 1024, 1);
        const uint32_t bl = bt + 4096;
        uint2 dl = make_uint2(0u, 0u), dn = dl;
#pragma unroll 1
        for (int m = 0; m < 16; m += 4) {
#pragma unroll
          for (int e = 0; e < 4; e++) {
            const int j = m + e;
            const uint32_t (&a)[16] = A[e & 1];
            mbar_wait(BAR(B_FB + j) + dl.x);
            const uint64_t db = (mk_desc(0, 0, 1024, 1)) | (bt + dl.y);
            wg_fence();
#pragma unroll
            for (int kk = 0; kk < 4; kk++) {
              wg_n128_rs<1>(acc, a[4 * kk], a[4 * kk + 1], a[4 * kk + 2], a[4 * kk + 3], db + kk * 128, 1);
              if (kk == PSPL) {
                wg_commit();
                if (U3L && e == 0 && m == 0) {
                  if (U3L == 2 && !early) {
#pragma unroll
                    for (int i = 0; i < 4; i++) st_rec16(og + cb * 2048 + i * 32, A[0][4 * i] ^ tg, A[0][4 * i + 1], A[0][4 * i + 2], A[0][4 * i + 3]);
                    announce();
                  }
                  attn_out(u3, tg, &A[1][8], og, false);
                }
                wg_wait<1>();
                if (lead) mbar_arrive(BAR(j ? B_DC + j - 1 : B_XREAD));
                if (LPUB == 3 && e == 2 && m == 0) {
#pragma unroll
                  for (int i = 0; i < 4; i++) st_rec16(og + cb * 2048 + 1024 + i * 32, A[1][4 * i] ^ tg, A[1][4 * i + 1], A[1][4 * i + 2], A[1][4 * i + 3]);
                }
                if (e || m) {
                  if (e < 3 || m < 12) mbar_wait<1>(BAR(B_FKV + j + 1));
                  take(A[(e & 1) ^ 1], (e + 1) & 3);
                  if (DYN) dn = lds_u2(sb + OFF_RED + 72 + j * 8);
                }
                else if (LPUB == 1) {
#pragma unroll
                  for (int i = 0; i < 4; i++) st_rec16(og + cb * 2048 + 1024 + i * 32, A[1][4 * i], A[1][4 * i + 1], A[1][4 * i + 2], A[1][4 * i + 3]);
                }
                if (LPUB >= 4 && LPUB < 6 && e == LPUB - 4 && m == 0) {
                  mbar_wait(BAR(B_XDONE));
                  send(A[1], e ? tg : 0u, 12, 1);
                }
                if (e == (EB ? 0 : 3)) asm volatile("cp.async.bulk.wait_group.read 0;" ::: "memory");
                if (LPUB == 2 && e == 1 && m == 0) {
#pragma unroll
                  for (int i = 0; i < 4; i++) st_rec16(og + cb * 2048 + 1024 + i * 32, A[1][4 * i] ^ tg, A[1][4 * i + 1], A[1][4 * i + 2], A[1][4 * i + 3]);
                }
                wg_fence();
              }
            }
            wg_commit();
            if (LPUB >= 6 && e == LPUB - 6 && m == 0) {
              mbar_wait(BAR(B_XDONE));
              send(A[1], e ? tg : 0u, 12, 1);
            }
            asm volatile("{\n.reg .pred p;\nsetp.eq.u32 p, %0, %1;\nadd.u32 %0, %0, 1024;\n@p sub.u32 %0, %0, 5120;\n}\n" : "+r"(bt) : "r"(bl));
            dl = dn;
            if (e < 3 || m < 12) check(A[(e & 1) ^ 1], j + 1 + ((int)dl.x >> 3));
          }
        }
      }
      uint4 wb[4];
#pragma unroll
      for (int i = 0; i < 4; i++) wb[i] = lds_u4(sb + ((ln & 4) ? OFF_ONES : OFF_WR + (ln & 3) * 64) + i * 16);
      mbar_wait(BAR(B_RESET2));
      wg_wait<0>();
      if (lead) mbar_arrive(BAR(B_DC + 15));
      uint32_t hp2[8][4];
      float ds[8], q[4];
#pragma unroll 1
      for (int rep = 0; rep < 1; rep++) {
#pragma unroll
      for (int i = 0; i < 8; i++) ds[i] = q[i & 3] = 0.f;
#pragma unroll
      for (int k = 0; k < 8; k++) {
#pragma unroll
        for (int i = 0; i < 4; i++) hp2[k][i] = pack_pin(acc[8 * k + 2 * i], acc[8 * k + 2 * i + 1]);
        mma_bf16(&ds[(k & 1) * 4], hp2[k], (k & 1) ? wb[k >> 1].z : wb[k >> 1].x, (k & 1) ? wb[k >> 1].w : wb[k >> 1].y);
#pragma unroll
        for (int i = SQN * k; i < SQN * (k + 1) && i < 64; i++) asm volatile("fma.rn.f32 %0, %1, %1, %0;" : "+f"(q[i & 3]) : "f"(acc[i]));
      }
#pragma unroll
      for (int i = SQN * 8; i < 64; i++) asm volatile("fma.rn.f32 %0, %1, %1, %0;" : "+f"(q[i & 3]) : "f"(acc[i]));
      const bool hi = ln & 1;
      q[0] += q[1]; q[2] += q[3];
      q[0] = (hi ? q[2] : q[0]) + __shfl_xor_sync(0xffffffffu, hi ? q[0] : q[2], 1);
      q[0] += __shfl_xor_sync(0xffffffffu, q[0], 2);
      st_rec16_if(((ln >> 1) & 1) == (cb >> 2), og + 16384 + (cb & 3) * 32, __float_as_uint((hi ? ds[3] : ds[1]) + (hi ? ds[7] : ds[5])), __float_as_uint(q[0]),
                  __float_as_uint((hi ? ds[2] : ds[0]) + (hi ? ds[6] : ds[4])), tag);
      }
      pin_order();
      hsrc = og + 16384;
      trow = rb * 128 + wg * 64 + warp * 16 + (ln >> 2) + (ln & 1) * 8;
      const uint32_t ha = tile_addr();
#pragma unroll
      for (int jj = 0; jj < 8; jj++) stsm_x4((ha ^ (32 * (jj & 3))) + (jj >> 2) * 2 * SLOT, hp2[jj][0], hp2[jj][1], hp2[jj][2], hp2[jj][3]);
    }
    asm volatile("setmaxnreg.dec.sync.aligned.u32 %0;" :: "n"(TREG));
    {
    const int tid = fresh_tid(), lane = tid & 31;
    const unsigned tag = lds_u(sb + OFF_RED + 4);
    const float sumw = lds_f(sb + OFF_RED);
    uint2* const kp = settle(&g_key[cb][0][rb * 4], lane);
    uint32_t key;
    {
      uint4 r[4];
#pragma unroll 1
      for (int it = 0; it < SPIN; it++) {
#pragma unroll
        for (int i = 0; i < 4; i++) r[i] = ld_rec16(hsrc + i * 32);
        if (__all_sync(0xffffffffu, r[0].w == tag && r[1].w == tag && r[2].w == tag && r[3].w == tag)) break;
      }
      float s = (__uint_as_float(r[0].x) + __uint_as_float(r[1].x)) + (__uint_as_float(r[2].x) + __uint_as_float(r[3].x));
      float q = (__uint_as_float(r[0].y) + __uint_as_float(r[1].y)) + (__uint_as_float(r[2].y) + __uint_as_float(r[3].y));
      float d = (__uint_as_float(r[0].z) + __uint_as_float(r[1].z)) + (__uint_as_float(r[2].z) + __uint_as_float(r[3].z));
      s += __shfl_xor_sync(0xffffffffu, s, 2); q += __shfl_xor_sync(0xffffffffu, q, 2); d += __shfl_xor_sync(0xffffffffu, d, 2);
      const float mean = s * (1.f / DM);
      const float rstd = rsq(fmaxf(fmaf(-mean, mean, q * (1.f / DM)), 0.f) + 1e-5f);
      const uint32_t u = __float_as_uint(rstd * fmaf(-mean, sumw, d));
      key = ((u ^ ((uint32_t)((int)u >> 31) | 0x80000000u)) & ~(uint32_t)(SEQ - 1)) | (uint32_t)trow;
      asm volatile("red.shared.max.u32 [%0], %1;" :: "r"(sb + OFF_RED + 16), "r"(key) : "memory");
      if ((lane & 2) == 0) sts_f2(sb + OFF_RSTAT + (trow & 127) * 8, rstd, -mean * rstd);
      bar_sync(1, 256);
      key = lds_u(sb + OFF_RED + 16 + (trow >> 20));
    }
    if (tid == 0) { st_rec8(kp, key, tag); mbar_arrive(BAR(B_KEY)); }
    const int crow = key & 127;
    const bool own = (crow >> 4) == wg * 4 + warp;
    uint32_t co0 = 0, co1 = 0;
    if (own) {
      const uint32_t r = (uint32_t)(crow & 63);
      const float2 st = lds_f2(sb + OFF_RSTAT + crow * 8);
      const uint32_t a = stg + r * 128 + ((((uint32_t)lane >> 2) ^ (r & 7)) << 4) + (lane & 3) * 4;
      const uint32_t h0 = lds_u(a), h1 = lds_u(a + 2 * SLOT);
      uint32_t n0, n1;
      co0 = ln_res(h0, st.x, st.y, n0); co1 = ln_res(h1, st.x, st.y, n1);
      uint4* const cx = hsrc + (cb * 32 + 1024 - (crow >> 4) * 128);
      st_rec16(cx, n0, n1, key, tag);
      st_rec16(cx + 256 + cb * 32, n0, h0, key, tag);
      st_rec16(cx + 288 + cb * 32, n1, h1, key, tag);
    }
    __nv_bfloat16* ob = P.out + (size_t)(rb * 128 + wg * 64) * DM + cb * 128;
#pragma unroll 4
    for (int i = 0; i < 8; i++) {
      const uint32_t r = (uint32_t)(warp * 16 + (i & 3) * 4 + (lane >> 3));
      const uint32_t a = stg + (i >> 2) * 2 * SLOT + r * 128 + ((((uint32_t)lane & 7) ^ (r & 7)) << 4);
      const uint4 h = lds_u4(a);
      const float2 st = lds_f2(sb + OFF_RSTAT + ((tid >> 7) * 64 + r) * 8);
      uint32_t n;
      uint4 o;
      o.x = ln_res(h.x, st.x, st.y, n); o.y = ln_res(h.y, st.x, st.y, n); o.z = ln_res(h.z, st.x, st.y, n); o.w = ln_res(h.w, st.x, st.y, n);
      if (!own) sts_u4(a, o.x, o.y, o.z, o.w);
      else if ((int)r != (crow & 63)) stg16(ob + (size_t)r * DM + (i >> 2) * 64 + (lane & 7) * 8, o);
      if ((i & 3) == 3) {
        fence_async_smem();
        __syncwarp();
        if (OUTG == 1 ? i == 7 : OUTG == 2 ? i == 3 : OUTG == 3 ? i == 7 || wg : OUTG == 4 ? i == 7 && wg : false) mbar_wait(BAR(B_ROW));
        if (elect()) {
          if (!own) tma_store_2d(&P.mOut, stg + (i >> 2) * 2 * SLOT + warp * 2048, cb * 128 + (i >> 2) * 64, rb * 128 + wg * 64 + warp * 16);
          asm volatile("cp.async.bulk.commit_group;" ::: "memory");
        }
        __syncwarp();
      }
    }
    if (elect()) {
      asm volatile("cp.async.bulk.wait_group.read 0;" ::: "memory");
    }
    __syncwarp();
    if (own) {
      uint2 v;
#pragma unroll 1
      for (int it = 0; it < SPIN; it++) {
        v = ld_rec8(&g_key[cb][0][(lane & 15) * 4]);
        if (__all_sync(0xffffffffu, v.y == tag)) break;
      }
      if (__reduce_max_sync(0xffffffffu, v.x) != key) {
        uint32_t* op = reinterpret_cast<uint32_t*>(ob + (size_t)(crow & 63) * DM);
        op[lane] = co0; op[32 + lane] = co1;
      }
    }
    }
  }
#undef BAR
}

typedef CUresult (*EncodeFn)(CUtensorMap*, CUtensorMapDataType, cuuint32_t, void*, const cuuint64_t*, const cuuint64_t*,
                             const cuuint32_t*, const cuuint32_t*, CUtensorMapInterleave, CUtensorMapSwizzle,
                             CUtensorMapL2promotion, CUtensorMapFloatOOBfill);

void make_map(EncodeFn fn, CUtensorMap* m, const void* ptr, uint64_t cols, uint64_t rows, uint32_t bc, uint32_t br, CUtensorMapSwizzle swz,
              uint32_t parts = 0, uint32_t bp = 1) {
  cuuint64_t dims[3] = {parts ? cols / parts : cols, rows, parts};
  cuuint64_t strides[2] = {cols * 2, dims[0] * 2};
  cuuint32_t box[3] = {bc, br, bp};
  cuuint32_t es[3] = {1, 1, 1};
  fn(m, CU_TENSOR_MAP_DATA_TYPE_BFLOAT16, parts ? 3 : 2, const_cast<void*>(ptr), dims, strides, box, es, CU_TENSOR_MAP_INTERLEAVE_NONE, swz,
     CU_TENSOR_MAP_L2_PROMOTION_L2_128B, CU_TENSOR_MAP_FLOAT_OOB_FILL_NONE);
}

}

extern "C" void kernel_launch(void* const* d_in, const int* in_sizes, int n_in, void* d_out, int out_size) {
  static EncodeFn fn = nullptr;
  if (!fn) {
    cudaDriverEntryPointQueryResult q;
    cudaGetDriverEntryPoint("cuTensorMapEncodeTiled", (void**)&fn, cudaEnableDefault, &q);
    cudaFuncSetAttribute(fused_kernel, cudaFuncAttributeMaxDynamicSharedMemorySize, SMEM_BYTES);
  }
  Params P;
  P.x = (const __nv_bfloat16*)d_in[0];
  P.wqkv = (const __nv_bfloat16*)d_in[1];
  const __nv_bfloat16* wphi = (const __nv_bfloat16*)d_in[2];
  P.wo = (const __nv_bfloat16*)d_in[3];
  P.wr = (const __nv_bfloat16*)d_in[5];
  P.wg = (const __nv_bfloat16*)d_in[6];
  P.wu = (const __nv_bfloat16*)d_in[7];
  P.wd = (const __nv_bfloat16*)d_in[8];
  P.out = (__nv_bfloat16*)d_out;
  make_map(fn, &P.mX, P.x, DM, SEQ, 64, 128, CU_TENSOR_MAP_SWIZZLE_128B);
  make_map(fn, &P.mW, P.wqkv, 3 * DM, DM, 64, 64, CU_TENSOR_MAP_SWIZZLE_128B);
  make_map(fn, &P.mX2, P.x, DM, SEQ, 64, 64, CU_TENSOR_MAP_SWIZZLE_128B);
  make_map(fn, &P.mW2, P.wqkv, 3 * DM, DM, 64, 32, CU_TENSOR_MAP_SWIZZLE_128B);
  make_map(fn, &P.mWo, P.wo, DM, DM, 64, 64, CU_TENSOR_MAP_SWIZZLE_128B);
  make_map(fn, &P.mPhi, wphi, 32, 1024, 32, 64, CU_TENSOR_MAP_SWIZZLE_64B);
  make_map(fn, &P.mWg, P.wg, FF, DM, 32, 256, CU_TENSOR_MAP_SWIZZLE_64B, 1);
  make_map(fn, &P.mWu, P.wu, FF, DM, 32, 256, CU_TENSOR_MAP_SWIZZLE_64B, 1);
  make_map(fn, &P.mWs, P.wqkv, 3 * DM, DM, 32, 64, CU_TENSOR_MAP_SWIZZLE_NONE);
  make_map(fn, &P.mWd, P.wd, DM, FF, 64, 32, CU_TENSOR_MAP_SWIZZLE_128B, 16, 4);
  make_map(fn, &P.mOut, P.out, DM, SEQ, 64, 16, CU_TENSOR_MAP_SWIZZLE_128B);
  make_map(fn, &P.mWgT, P.wg, FF, DM, 8, TROWS, CU_TENSOR_MAP_SWIZZLE_NONE);
  make_map(fn, &P.mWuT, P.wu, FF, DM, 8, TROWS, CU_TENSOR_MAP_SWIZZLE_NONE);
  make_map(fn, &P.mWdT, P.wd, 64, FF * 16, 8, TROWS, CU_TENSOR_MAP_SWIZZLE_NONE);
  fused_kernel<<<NCTA, NTHREADS, SMEM_BYTES, cudaStreamPerThread>>>(P);
}
```

```cpp
#include <cuda_runtime.h>
#include <cuda_bf16.h>
#include <cuda.h>
#include <stdint.h>

namespace {

constexpr int SEQ = 2048, DM = 1024, FF = 3584;
constexpr int NCTA = 128, NTHREADS = 512, NFFN = 112;
constexpr int SPIN = 1 << 17;
constexpr int RSTQ = 3;
constexpr int PIN = 145;
constexpr int RCPG = 4;
constexpr int THR = 1;
constexpr int KH2 = 0;
constexpr int KSH = 0;
constexpr int PAD = 0;
constexpr int GATE = 6;
constexpr int FLAGW = 3;
constexpr int LATE = 0x78;
constexpr int SXN = 4;
constexpr int SX0 = 2;
constexpr int SXD = 2;
constexpr int CSW = 0x65431234;
constexpr int SKIP = 0;
constexpr int WEF = 0;
constexpr int TROWS = 16;
constexpr int DYN = 1;
constexpr int MAP = 1;
constexpr int OUTG = 1;
constexpr int QD = 5;
constexpr int KSPL = 0;
constexpr int K1E = 1;
constexpr int FINE = 1;
constexpr int K2W = 2;
constexpr int K3B = 161;
constexpr int K1M = 0;
constexpr int QSPL = 2;
constexpr int QW2 = 1;
constexpr int SQN = 4;
constexpr int TREG = 32;
constexpr int DORD = 8;
constexpr int YDLY = 0;
constexpr int KSUM = 1;
constexpr int GSPEC = 1;
constexpr int QWIN = 3;
constexpr int QGATE = 13;

constexpr uint32_t SLOT = 16384;
constexpr uint32_t OFF_MISC = 13 * SLOT;
constexpr uint32_t OFF_PHIK = OFF_MISC;
constexpr uint32_t OFF_PHIQ = OFF_MISC + 4096;
constexpr uint32_t OFF_ONES = OFF_MISC + 12288;
constexpr uint32_t OFF_RSTAT = OFF_MISC + 13312;
constexpr uint32_t OFF_EYE = OFF_MISC + 14336;
constexpr uint32_t OFF_CS = OFF_MISC + 15360;
constexpr uint32_t OFF_WR = OFF_MISC + 16384;
constexpr uint32_t OFF_BAR = OFF_MISC + 16896;
constexpr uint32_t OFF_RED = OFF_MISC + 18304;
constexpr uint32_t OFF_SEL = OFF_RED + 320;
constexpr uint32_t OFF_TCH = OFF_MISC + 19072;
constexpr uint32_t SMEM_BYTES = OFF_MISC + 19456;

enum {
  B_FKV = 0, B_DKV = 16, B_FQ = 32, B_DQ = 48,
  B_PHI = 64, B_RESET = 65, B_RESET2 = 66, B_ROW = 67, B_FX = 68, B_KEY = 69, B_TCH = 70, B_REL = 72,
  B_FB = 80, B_DC = 96, B_QD = 112, B_STAT = 114,
  B_KVFREE = 120, B_QGO = 121, B_QGO2 = 122, B_CSD = 123, B_XDONE = 124, B_QREAD = 125, B_XREAD = 126, B_KVRDY = 127,
  B_FS = 128, B_FW = 144, B_F0 = 160
};
constexpr unsigned long long MISC_COUNTS = 0x0502020203020202ull;

struct Params {
  CUtensorMap mX2, mW2, mX, mW, mWo, mPhi, mWg, mWu, mWs, mWd, mOut, mWgT, mWuT, mWdT;
  const __nv_bfloat16 *x, *wqkv, *wo, *wr, *wg, *wu, *wd;
  __nv_bfloat16* out;
};

__device__ unsigned g_epoch;
__device__ __align__(128) uint4 g_rowstat[SEQ];
__device__ __align__(128) uint2 g_colsum[4][3 * DM];
__device__ __align__(128) uint4 g_kvp[32][8][3][128];
__device__ __align__(128) uint4 g_kvr[32][3][128];
__device__ __align__(128) uint4 g_o[16][18][8][4][32];
__device__ __align__(128) uint4 g_oflag[16][8][16];
__device__ __align__(128) uint2 g_key[8][16][16];
__device__ __align__(128) uint4 g_ypart[128][NFFN][2];

__device__ __forceinline__ uint32_t smem_u32(const void* p) { return (uint32_t)__cvta_generic_to_shared(p); }
__device__ __forceinline__ bool elect() {
  uint32_t p;
  asm volatile("{\n.reg .pred P;\nelect.sync _|P, 0xffffffff;\nselp.u32 %0, 1, 0, P;\n}\n" : "=r"(p));
  return p != 0;
}
__device__ __forceinline__ void mbar_init(uint32_t bar, uint32_t cnt) { asm volatile("mbarrier.init.shared::cta.b64 [%0], %1;" :: "r"(bar), "r"(cnt)); }
__device__ __forceinline__ void mbar_expect_tx(uint32_t bar, uint32_t bytes) { asm volatile("mbarrier.arrive.expect_tx.shared::cta.b64 _, [%0], %1;" :: "r"(bar), "r"(bytes) : "memory"); }
__device__ __forceinline__ void mbar_arrive(uint32_t bar) { asm volatile("mbarrier.arrive.shared::cta.b64 _, [%0];" :: "r"(bar) : "memory"); }
template <int PARITY = 0>
__device__ __forceinline__ void mbar_wait(uint32_t bar) {
#pragma unroll 1
  for (int it = 0; it < SPIN; it++) {
    uint32_t ok;
    asm volatile("{\n.reg .pred p;\nmbarrier.try_wait.parity.shared::cta.b64 p, [%1], %2;\nselp.u32 %0, 1, 0, p;\n}\n" : "=r"(ok) : "r"(bar), "n"(PARITY) : "memory");
    if (ok) break;
  }
}
__device__ __forceinline__ void tma_load_2d(uint32_t dst, const CUtensorMap* m, uint32_t bar, int c0, int c1) {
  asm volatile("cp.async.bulk.tensor.2d.shared::cluster.global.mbarrier::complete_tx::bytes [%0], [%1, {%3, %4}], [%2];"
    :: "r"(dst), "l"(m), "r"(bar), "r"(c0), "r"(c1) : "memory");
}
__device__ __forceinline__ void tma_load_2d_ef(uint32_t dst, const CUtensorMap* m, uint32_t bar, int c0, int c1) {
  uint64_t pol;
  asm("createpolicy.fractional.L2::evict_first.b64 %0, 1.0;" : "=l"(pol));
  asm volatile("cp.async.bulk.tensor.2d.shared::cluster.global.mbarrier::complete_tx::bytes.L2::cache_hint [%0], [%1, {%3, %4}], [%2], %5;"
    :: "r"(dst), "l"(m), "r"(bar), "r"(c0), "r"(c1), "l"(pol) : "memory");
}
__device__ __forceinline__ void tma_load_3d_ef(uint32_t dst, const CUtensorMap* m, uint32_t bar, int c0, int c1, int c2) {
  uint64_t pol;
  asm("createpolicy.fractional.L2::evict_first.b64 %0, 1.0;" : "=l"(pol));
  asm volatile("cp.async.bulk.tensor.3d.shared::cluster.global.mbarrier::complete_tx::bytes.L2::cache_hint [%0], [%1, {%3, %4, %5}], [%2], %6;"
    :: "r"(dst), "l"(m), "r"(bar), "r"(c0), "r"(c1), "r"(c2), "l"(pol) : "memory");
}
template <int EF> __device__ __forceinline__ void tma_load_w(uint32_t dst, const CUtensorMap* m, uint32_t bar, int c0, int c1) {
  if (EF) tma_load_2d_ef(dst, m, bar, c0, c1); else tma_load_2d(dst, m, bar, c0, c1);
}
__device__ __forceinline__ void tma_store_2d(const CUtensorMap* m, uint32_t src, int c0, int c1) {
  asm volatile("cp.async.bulk.tensor.2d.global.shared::cta.bulk_group [%0, {%2, %3}], [%1];"
    :: "l"(m), "r"(src), "r"(c0), "r"(c1) : "memory");
}
__device__ __forceinline__ void cp_async16(uint32_t dst, const void* src) { asm volatile("cp.async.cg.shared.global [%0], [%1], 16;" :: "r"(dst), "l"(src) : "memory"); }
__device__ __forceinline__ void cp_commit() { asm volatile("cp.async.commit_group;" ::: "memory"); }
template <int N> __device__ __forceinline__ void cp_wait() { asm volatile("cp.async.wait_group %0;" :: "n"(N) : "memory"); }
__device__ __forceinline__ void l2_prefetch(const void* src, uint32_t bytes) {
  asm volatile("cp.async.bulk.prefetch.L2.global [%0], %1;" :: "l"(src), "r"(bytes) : "memory");
}
__device__ __forceinline__ void wg_fence() { asm volatile("wgmma.fence.sync.aligned;" ::: "memory"); }
__device__ __forceinline__ void wg_commit() { asm volatile("wgmma.commit_group.sync.aligned;" ::: "memory"); }
template <int N> __device__ __forceinline__ void wg_wait() { asm volatile("wgmma.wait_group.sync.aligned %0;" :: "n"(N) : "memory"); }
__device__ __forceinline__ void fence_async_smem() { asm volatile("fence.proxy.async.shared::cta;" ::: "memory"); }
__device__ __forceinline__ void bar_sync(int id, int n) { asm volatile("bar.sync %0, %1;" :: "r"(id), "r"(n) : "memory"); }
__device__ __forceinline__ void bar_arrive(int id, int n) { asm volatile("bar.arrive %0, %1;" :: "r"(id), "r"(n) : "memory"); }
__device__ __forceinline__ uint64_t mk_desc(uint32_t addr, uint32_t lbo, uint32_t sbo, uint32_t swz) {
  return (uint64_t)((addr & 0x3FFFF) >> 4) | ((uint64_t)((lbo & 0x3FFFF) >> 4) << 16) | ((uint64_t)(sbo >> 4) << 32) | ((uint64_t)swz << 62);
}
__device__ __forceinline__ void stsm_x4(uint32_t addr, uint32_t r0, uint32_t r1, uint32_t r2, uint32_t r3) {
  asm volatile("stmatrix.sync.aligned.m8n8.x4.shared.b16 [%0], {%1, %2, %3, %4};" :: "r"(addr), "r"(r0), "r"(r1), "r"(r2), "r"(r3) : "memory");
}
__device__ __forceinline__ void ldsm_x4(uint32_t& r0, uint32_t& r1, uint32_t& r2, uint32_t& r3, uint32_t addr) {
  asm volatile("ldmatrix.sync.aligned.m8n8.x4.shared.b16 {%0, %1, %2, %3}, [%4];" : "=r"(r0), "=r"(r1), "=r"(r2), "=r"(r3) : "r"(addr) : "memory");
}
__device__ __forceinline__ void ldsm_x4_t(uint32_t (&r)[4], uint32_t addr) {
  asm volatile("ldmatrix.sync.aligned.m8n8.x4.trans.shared.b16 {%0, %1, %2, %3}, [%4];" : "=r"(r[0]), "=r"(r[1]), "=r"(r[2]), "=r"(r[3]) : "r"(addr) : "memory");
}
__device__ __forceinline__ void mma_bf16(float* d, const uint32_t (&a)[4], uint32_t b0, uint32_t b1) {
  asm volatile("mma.sync.aligned.m16n8k16.row.col.f32.bf16.bf16.f32 {%0, %1, %2, %3}, {%4, %5, %6, %7}, {%8, %9}, {%0, %1, %2, %3};"
    : "+f"(d[0]), "+f"(d[1]), "+f"(d[2]), "+f"(d[3]) : "r"(a[0]), "r"(a[1]), "r"(a[2]), "r"(a[3]), "r"(b0), "r"(b1));
}
__device__ __forceinline__ uint32_t zero_after(uint32_t v) { uint32_t r; asm volatile("prmt.b32 %0, %1, 0, 0x4444;" : "=r"(r) : "r"(v)); return r; }
__device__ __forceinline__ uint32_t now() { uint32_t t; asm volatile("mov.u32 %0, %%globaltimer_lo;" : "=r"(t)); return t; }
__device__ __forceinline__ int fresh_tid() { int v; asm volatile("mov.u32 %0, %%tid.x;" : "=r"(v)); return v; }
template <int ID> __device__ __forceinline__ void pin_at() {
  asm volatile("{\n.reg .pred p;\nsetp.eq.u32 p, %0, %1;\nPIN:\n@p nanosleep.u32 0;\n@p bra.uni PIN;\n}\n" :: "r"(blockIdx.x), "n"(4096 + ID) : "memory");
}
#define pin_order() pin_at<__LINE__>()
__device__ __forceinline__ uint32_t pack_bf16(float lo, float hi) {
  uint32_t r; asm("cvt.rn.bf16x2.f32 %0, %1, %2;" : "=r"(r) : "f"(hi), "f"(lo)); return r;
}
__device__ __forceinline__ uint32_t pack_pin(float lo, float hi) {
  uint32_t r; asm volatile("cvt.rn.bf16x2.f32 %0, %1, %2;" : "=r"(r) : "f"(hi), "f"(lo)); return r;
}
__device__ __forceinline__ uint32_t hadd2(uint32_t a, uint32_t b) { uint32_t r; asm("add.rn.bf16x2 %0, %1, %2;" : "=r"(r) : "r"(a), "r"(b)); return r; }
template <int H> __device__ __forceinline__ uint32_t hmul2(uint32_t a, uint32_t b) {
  uint32_t r;
  if (H) asm("{\n.reg .b16 l, h;\n.reg .b32 t;\nmov.b32 {l, h}, %2;\nmov.b32 t, {h, h};\nmul.rn.bf16x2 %0, %1, t;\n}\n" : "=r"(r) : "r"(a), "r"(b));
  else asm("{\n.reg .b16 l, h;\n.reg .b32 t;\nmov.b32 {l, h}, %2;\nmov.b32 t, {l, l};\nmul.rn.bf16x2 %0, %1, t;\n}\n" : "=r"(r) : "r"(a), "r"(b));
  return r;
}
template <int H> __device__ __forceinline__ uint32_t hfma2(uint32_t a, uint32_t b, uint32_t c) {
  uint32_t r;
  if (H) asm("{\n.reg .b16 l, h;\n.reg .b32 t;\nmov.b32 {l, h}, %2;\nmov.b32 t, {h, h};\nfma.rn.bf16x2 %0, %1, t, %3;\n}\n" : "=r"(r) : "r"(a), "r"(b), "r"(c));
  else asm("{\n.reg .b16 l, h;\n.reg .b32 t;\nmov.b32 {l, h}, %2;\nmov.b32 t, {l, l};\nfma.rn.bf16x2 %0, %1, t, %3;\n}\n" : "=r"(r) : "r"(a), "r"(b), "r"(c));
  return r;
}
__device__ __forceinline__ uint32_t hsq2(uint32_t a, uint32_t c) { uint32_t r; asm("fma.rn.bf16x2 %0, %1, %1, %2;" : "=r"(r) : "r"(a), "r"(c)); return r; }
__device__ __forceinline__ float bf_lo_p(uint32_t v) { float r; asm("prmt.b32 %0, %1, 0, 0x1044;" : "=f"(r) : "r"(v)); return r; }
__device__ __forceinline__ float bf_lo(uint32_t v) { return __uint_as_float(v << 16); }
__device__ __forceinline__ float bf_hi(uint32_t v) { return __uint_as_float(v & 0xFFFF0000u); }
__device__ __forceinline__ float bf_round(float v) { return bf_lo(pack_bf16(v, 0.f)); }
__device__ __forceinline__ float ex2(float v) { float r; asm("ex2.approx.ftz.f32 %0, %1;" : "=f"(r) : "f"(v)); return r; }
__device__ __forceinline__ float rsq(float v) { float r; asm("rsqrt.approx.ftz.f32 %0, %1;" : "=f"(r) : "f"(v)); return r; }
__device__ __forceinline__ float rcp(float v) { float r; asm("rcp.approx.ftz.f32 %0, %1;" : "=f"(r) : "f"(v)); return r; }
__device__ __forceinline__ void st_rec16(uint4* p, uint32_t a, uint32_t b, uint32_t c, uint32_t d) {
  asm volatile("{\n.reg .b128 r;\n.reg .b64 lo, hi;\nmov.b64 lo, {%1, %2};\nmov.b64 hi, {%3, %4};\nmov.b128 r, {lo, hi};\nst.relaxed.gpu.global.b128 [%0], r;\n}\n"
    :: "l"(p), "r"(a), "r"(b), "r"(c), "r"(d) : "memory");
}
__device__ __forceinline__ void st_rec16_if(bool on, uint4* p, uint32_t a, uint32_t b, uint32_t c, uint32_t d) {
  asm volatile("{\n.reg .pred p;\n.reg .b128 r;\n.reg .b64 lo, hi;\nsetp.ne.u32 p, %5, 0;\nmov.b64 lo, {%1, %2};\nmov.b64 hi, {%3, %4};\nmov.b128 r, {lo, hi};\n@p st.relaxed.gpu.global.b128 [%0], r;\n}\n"
    :: "l"(p), "r"(a), "r"(b), "r"(c), "r"(d), "r"((uint32_t)on) : "memory");
}
__device__ __forceinline__ uint4 ld_rec16(const uint4* p) {
  uint4 v;
  asm volatile("{\n.reg .b128 r;\n.reg .b64 lo, hi;\nld.relaxed.gpu.global.b128 r, [%4];\nmov.b128 {lo, hi}, r;\nmov.b64 {%0, %1}, lo;\nmov.b64 {%2, %3}, hi;\n}\n"
    : "=r"(v.x), "=r"(v.y), "=r"(v.z), "=r"(v.w) : "l"(p) : "memory");
  return v;
}
__device__ __forceinline__ void ld_rec16_stale(uint4& v, const uint4* p, uint32_t tag) {
  asm volatile("{\n.reg .pred p;\n.reg .b128 r;\n.reg .b64 lo, hi;\n.reg .b32 t;\nmov.b64 lo, {%0, %1};\nmov.b64 hi, {%2, %3};\nmov.b128 r, {lo, hi};\n"
    "xor.b32 t, %0, %5;\nand.b32 t, t, 0x00010001;\nsetp.ne.u32 p, t, 0;\n"
    "@p ld.relaxed.gpu.global.b128 r, [%4];\nmov.b128 {lo, hi}, r;\nmov.b64 {%0, %1}, lo;\nmov.b64 {%2, %3}, hi;\n}\n"
    : "+r"(v.x), "+r"(v.y), "+r"(v.z), "+r"(v.w) : "l"(p), "r"(tag) : "memory");
}
__device__ __forceinline__ void st_rec8(uint2* p, uint32_t a, uint32_t b) {
  asm volatile("{\n.reg .b64 r;\nmov.b64 r, {%1, %2};\nst.relaxed.gpu.global.b64 [%0], r;\n}\n" :: "l"(p), "r"(a), "r"(b) : "memory");
}
__device__ __forceinline__ uint2 ld_rec8(const uint2* p) {
  uint2 v;
  asm volatile("{\n.reg .b64 r;\nld.relaxed.gpu.global.b64 r, [%2];\nmov.b64 {%0, %1}, r;\n}\n" : "=r"(v.x), "=r"(v.y) : "l"(p) : "memory");
  return v;
}
__device__ __forceinline__ unsigned ld_relaxed(const unsigned* p) { unsigned v; asm volatile("ld.relaxed.gpu.global.u32 %0, [%1];" : "=r"(v) : "l"(p) : "memory"); return v; }
__device__ __forceinline__ uint4 ldg_nc16(const void* p) {
  uint4 v; asm volatile("ld.global.nc.L1::no_allocate.v4.u32 {%0, %1, %2, %3}, [%4];" : "=r"(v.x), "=r"(v.y), "=r"(v.z), "=r"(v.w) : "l"(p)); return v;
}
__device__ __forceinline__ void stg16(void* p, uint4 v) { asm volatile("st.global.v4.u32 [%0], {%1, %2, %3, %4};" :: "l"(p), "r"(v.x), "r"(v.y), "r"(v.z), "r"(v.w) : "memory"); }
__device__ __forceinline__ float2 lds_f2(uint32_t a) { float2 v; asm volatile("ld.shared.v2.f32 {%0, %1}, [%2];" : "=f"(v.x), "=f"(v.y) : "r"(a)); return v; }
__device__ __forceinline__ float lds_f(uint32_t a) { float v; asm volatile("ld.shared.f32 %0, [%1];" : "=f"(v) : "r"(a)); return v; }
__device__ __forceinline__ uint32_t lds_u(uint32_t a) { uint32_t v; asm volatile("ld.shared.u32 %0, [%1];" : "=r"(v) : "r"(a)); return v; }
__device__ __forceinline__ uint2 lds_u2(uint32_t a) { uint2 v; asm volatile("ld.shared.v2.u32 {%0, %1}, [%2];" : "=r"(v.x), "=r"(v.y) : "r"(a)); return v; }
__device__ __forceinline__ uint4 lds_u4(uint32_t a) { uint4 v; asm volatile("ld.shared.v4.u32 {%0, %1, %2, %3}, [%4];" : "=r"(v.x), "=r"(v.y), "=r"(v.z), "=r"(v.w) : "r"(a)); return v; }
__device__ __forceinline__ void sts_f(uint32_t a, float v) { asm volatile("st.shared.f32 [%0], %1;" :: "r"(a), "f"(v) : "memory"); }
__device__ __forceinline__ void sts_f2(uint32_t a, float x, float y) { asm volatile("st.shared.v2.f32 [%0], {%1, %2};" :: "r"(a), "f"(x), "f"(y) : "memory"); }
__device__ __forceinline__ void sts_u2(uint32_t a, uint32_t x, uint32_t y) { asm volatile("st.shared.v2.u32 [%0], {%1, %2};" :: "r"(a), "r"(x), "r"(y) : "memory"); }
__device__ __forceinline__ void sts_u4(uint32_t a, uint32_t x, uint32_t y, uint32_t z, uint32_t w) { asm volatile("st.shared.v4.u32 [%0], {%1, %2, %3, %4};" :: "r"(a), "r"(x), "r"(y), "r"(z), "r"(w) : "memory"); }
__device__ __forceinline__ void sts_h(uint32_t a, uint32_t v) { asm volatile("st.shared.u16 [%0], %1;" :: "r"(a), "h"((uint16_t)v) : "memory"); }
__device__ __forceinline__ void sts_u(uint32_t a, uint32_t v) { asm volatile("st.shared.u32 [%0], %1;" :: "r"(a), "r"(v) : "memory"); }

template <int TA, int TB>
__device__ __forceinline__ void wg_n128(float (&d)[64], uint64_t da, uint64_t db, int sd) {
  asm volatile("{\n.reg .pred p;\nsetp.ne.b32 p, %66, 0;\n"
    "wgmma.mma_async.sync.aligned.m64n128k16.f32.bf16.bf16 {%0, %1, %2, %3, %4, %5, %6, %7, %8, %9, %10, %11, %12, %13, %14, %15, %16, %17, %18, %19, %20, %21, %22, %23, %24, %25, %26, %27, %28, %29, %30, %31, %32, %33, %34, %35, %36, %37, %38, %39, %40, %41, %42, %43, %44, %45, %46, %47, %48, %49, %50, %51, %52, %53, %54, %55, %56, %57, %58, %59, %60, %61, %62, %63}, %64, %65, p, 1, 1, %67, %68;\n}\n"
    : "+f"(d[0]), "+f"(d[1]), "+f"(d[2]), "+f"(d[3]), "+f"(d[4]), "+f"(d[5]), "+f"(d[6]), "+f"(d[7]), "+f"(d[8]), "+f"(d[9]), "+f"(d[10]), "+f"(d[11]), "+f"(d[12]), "+f"(d[13]), "+f"(d[14]), "+f"(d[15]), "+f"(d[16]), "+f"(d[17]), "+f"(d[18]), "+f"(d[19]), "+f"(d[20]), "+f"(d[21]), "+f"(d[22]), "+f"(d[23]), "+f"(d[24]), "+f"(d[25]), "+f"(d[26]), "+f"(d[27]), "+f"(d[28]), "+f"(d[29]), "+f"(d[30]), "+f"(d[31]), "+f"(d[32]), "+f"(d[33]), "+f"(d[34]), "+f"(d[35]), "+f"(d[36]), "+f"(d[37]), "+f"(d[38]), "+f"(d[39]), "+f"(d[40]), "+f"(d[41]), "+f"(d[42]), "+f"(d[43]), "+f"(d[44]), "+f"(d[45]), "+f"(d[46]), "+f"(d[47]), "+f"(d[48]), "+f"(d[49]), "+f"(d[50]), "+f"(d[51]), "+f"(d[52]), "+f"(d[53]), "+f"(d[54]), "+f"(d[55]), "+f"(d[56]), "+f"(d[57]), "+f"(d[58]), "+f"(d[59]), "+f"(d[60]), "+f"(d[61]), "+f"(d[62]), "+f"(d[63])
    : "l"(da), "l"(db), "r"(sd), "n"(TA), "n"(TB));
}

template <int TA, int TB, int O>
__device__ __forceinline__ void wg_n64(float (&d)[64], uint64_t da, uint64_t db, int sd) {
  asm volatile("{\n.reg .pred p;\nsetp.ne.b32 p, %34, 0;\n"
    "wgmma.mma_async.sync.aligned.m64n64k16.f32.bf16.bf16 {%0, %1, %2, %3, %4, %5, %6, %7, %8, %9, %10, %11, %12, %13, %14, %15, %16, %17, %18, %19, %20, %21, %22, %23, %24, %25, %26, %27, %28, %29, %30, %31}, %32, %33, p, 1, 1, %35, %36;\n}\n"
    : "+f"(d[O + 0]), "+f"(d[O + 1]), "+f"(d[O + 2]), "+f"(d[O + 3]), "+f"(d[O + 4]), "+f"(d[O + 5]), "+f"(d[O + 6]), "+f"(d[O + 7]), "+f"(d[O + 8]), "+f"(d[O + 9]), "+f"(d[O + 10]), "+f"(d[O + 11]), "+f"(d[O + 12]), "+f"(d[O + 13]), "+f"(d[O + 14]), "+f"(d[O + 15]), "+f"(d[O + 16]), "+f"(d[O + 17]), "+f"(d[O + 18]), "+f"(d[O + 19]), "+f"(d[O + 20]), "+f"(d[O + 21]), "+f"(d[O + 22]), "+f"(d[O + 23]), "+f"(d[O + 24]), "+f"(d[O + 25]), "+f"(d[O + 26]), "+f"(d[O + 27]), "+f"(d[O + 28]), "+f"(d[O + 29]), "+f"(d[O + 30]), "+f"(d[O + 31])
    : "l"(da), "l"(db), "r"(sd), "n"(TA), "n"(TB));
}

template <int TA, int TB>
__device__ __forceinline__ void wg_n40(float (&d)[20], uint64_t da, uint64_t db, int sd) {
  asm volatile("{\n.reg .pred p;\nsetp.ne.b32 p, %22, 0;\n"
    "wgmma.mma_async.sync.aligned.m64n40k16.f32.bf16.bf16 {%0, %1, %2, %3, %4, %5, %6, %7, %8, %9, %10, %11, %12, %13, %14, %15, %16, %17, %18, %19}, %20, %21, p, 1, 1, %23, %24;\n}\n"
    : "+f"(d[0]), "+f"(d[1]), "+f"(d[2]), "+f"(d[3]), "+f"(d[4]), "+f"(d[5]), "+f"(d[6]), "+f"(d[7]), "+f"(d[8]), "+f"(d[9]), "+f"(d[10]), "+f"(d[11]), "+f"(d[12]), "+f"(d[13]), "+f"(d[14]), "+f"(d[15]), "+f"(d[16]), "+f"(d[17]), "+f"(d[18]), "+f"(d[19])
    : "l"(da), "l"(db), "r"(sd), "n"(TA), "n"(TB));
}

template <int TA, int TB>
__device__ __forceinline__ void wg_n32(float (&d)[16], uint64_t da, uint64_t db, int sd) {
  asm volatile("{\n.reg .pred p;\nsetp.ne.b32 p, %18, 0;\n"
    "wgmma.mma_async.sync.aligned.m64n32k16.f32.bf16.bf16 {%0, %1, %2, %3, %4, %5, %6, %7, %8, %9, %10, %11, %12, %13, %14, %15}, %16, %17, p, 1, 1, %19, %20;\n}\n"
    : "+f"(d[0]), "+f"(d[1]), "+f"(d[2]), "+f"(d[3]), "+f"(d[4]), "+f"(d[5]), "+f"(d[6]), "+f"(d[7]), "+f"(d[8]), "+f"(d[9]), "+f"(d[10]), "+f"(d[11]), "+f"(d[12]), "+f"(d[13]), "+f"(d[14]), "+f"(d[15])
    : "l"(da), "l"(db), "r"(sd), "n"(TA), "n"(TB));
}

template <int TB>
__device__ __forceinline__ void wg_n40_rs(float (&d)[20], uint32_t a0, uint32_t a1, uint32_t a2, uint32_t a3, uint64_t db, int sd) {
  asm volatile("{\n.reg .pred p;\nsetp.ne.b32 p, %25, 0;\n"
    "wgmma.mma_async.sync.aligned.m64n40k16.f32.bf16.bf16 {%0, %1, %2, %3, %4, %5, %6, %7, %8, %9, %10, %11, %12, %13, %14, %15, %16, %17, %18, %19}, {%20, %21, %22, %23}, %24, p, 1, 1, %26;\n}\n"
    : "+f"(d[0]), "+f"(d[1]), "+f"(d[2]), "+f"(d[3]), "+f"(d[4]), "+f"(d[5]), "+f"(d[6]), "+f"(d[7]), "+f"(d[8]), "+f"(d[9]), "+f"(d[10]), "+f"(d[11]), "+f"(d[12]), "+f"(d[13]), "+f"(d[14]), "+f"(d[15]), "+f"(d[16]), "+f"(d[17]), "+f"(d[18]), "+f"(d[19])
    : "r"(a0), "r"(a1), "r"(a2), "r"(a3), "l"(db), "r"(sd), "n"(TB));
}

template <int TB>
__device__ __forceinline__ void wg_n32_rs(float (&d)[16], uint32_t a0, uint32_t a1, uint32_t a2, uint32_t a3, uint64_t db, int sd) {
  asm volatile("{\n.reg .pred p;\nsetp.ne.b32 p, %21, 0;\n"
    "wgmma.mma_async.sync.aligned.m64n32k16.f32.bf16.bf16 {%0, %1, %2, %3, %4, %5, %6, %7, %8, %9, %10, %11, %12, %13, %14, %15}, {%16, %17, %18, %19}, %20, p, 1, 1, %22;\n}\n"
    : "+f"(d[0]), "+f"(d[1]), "+f"(d[2]), "+f"(d[3]), "+f"(d[4]), "+f"(d[5]), "+f"(d[6]), "+f"(d[7]), "+f"(d[8]), "+f"(d[9]), "+f"(d[10]), "+f"(d[11]), "+f"(d[12]), "+f"(d[13]), "+f"(d[14]), "+f"(d[15])
    : "r"(a0), "r"(a1), "r"(a2), "r"(a3), "l"(db), "r"(sd), "n"(TB));
}

template <int TB>
__device__ __forceinline__ void wg_n8_rs(float (&d)[4], uint32_t a0, uint32_t a1, uint32_t a2, uint32_t a3, uint64_t db, int sd) {
  asm volatile("{\n.reg .pred p;\nsetp.ne.b32 p, %9, 0;\n"
    "wgmma.mma_async.sync.aligned.m64n8k16.f32.bf16.bf16 {%0, %1, %2, %3}, {%4, %5, %6, %7}, %8, p, 1, 1, %10;\n}\n"
    : "+f"(d[0]), "+f"(d[1]), "+f"(d[2]), "+f"(d[3])
    : "r"(a0), "r"(a1), "r"(a2), "r"(a3), "l"(db), "r"(sd), "n"(TB));
}

template <int TB>
__device__ __forceinline__ void wg_n128_rs(float (&d)[64], uint32_t a0, uint32_t a1, uint32_t a2, uint32_t a3, uint64_t db, int sd) {
  asm volatile("{\n.reg .pred p;\nsetp.ne.b32 p, %69, 0;\n"
    "wgmma.mma_async.sync.aligned.m64n128k16.f32.bf16.bf16 {%0, %1, %2, %3, %4, %5, %6, %7, %8, %9, %10, %11, %12, %13, %14, %15, %16, %17, %18, %19, %20, %21, %22, %23, %24, %25, %26, %27, %28, %29, %30, %31, %32, %33, %34, %35, %36, %37, %38, %39, %40, %41, %42, %43, %44, %45, %46, %47, %48, %49, %50, %51, %52, %53, %54, %55, %56, %57, %58, %59, %60, %61, %62, %63}, {%64, %65, %66, %67}, %68, p, 1, 1, %70;\n}\n"
    : "+f"(d[0]), "+f"(d[1]), "+f"(d[2]), "+f"(d[3]), "+f"(d[4]), "+f"(d[5]), "+f"(d[6]), "+f"(d[7]), "+f"(d[8]), "+f"(d[9]), "+f"(d[10]), "+f"(d[11]), "+f"(d[12]), "+f"(d[13]), "+f"(d[14]), "+f"(d[15]), "+f"(d[16]), "+f"(d[17]), "+f"(d[18]), "+f"(d[19]), "+f"(d[20]), "+f"(d[21]), "+f"(d[22]), "+f"(d[23]), "+f"(d[24]), "+f"(d[25]), "+f"(d[26]), "+f"(d[27]), "+f"(d[28]), "+f"(d[29]), "+f"(d[30]), "+f"(d[31]), "+f"(d[32]), "+f"(d[33]), "+f"(d[34]), "+f"(d[35]), "+f"(d[36]), "+f"(d[37]), "+f"(d[38]), "+f"(d[39]), "+f"(d[40]), "+f"(d[41]), "+f"(d[42]), "+f"(d[43]), "+f"(d[44]), "+f"(d[45]), "+f"(d[46]), "+f"(d[47]), "+f"(d[48]), "+f"(d[49]), "+f"(d[50]), "+f"(d[51]), "+f"(d[52]), "+f"(d[53]), "+f"(d[54]), "+f"(d[55]), "+f"(d[56]), "+f"(d[57]), "+f"(d[58]), "+f"(d[59]), "+f"(d[60]), "+f"(d[61]), "+f"(d[62]), "+f"(d[63])
    : "r"(a0), "r"(a1), "r"(a2), "r"(a3), "l"(db), "r"(sd), "n"(TB));
}


template <int N>
__device__ __forceinline__ void feature_shifted(const float (&p)[16], const float (&p2)[16], float sc0, float sc1, uint32_t (&o)[N]) {
  __align__(16) float t[N];
  __align__(16) uint32_t w[N];
#pragma unroll
  for (int i = 0; i < N; i++) t[i] = i < 16 ? p[i] : p2[i & 15];
#pragma unroll 1
  for (int it = 0; it < N / 4; it++) {
    const float* x = t + (it >> 2) * 16 + (it & 1) * 2;
    const int h = (it >> 1) & 1;
    const float sg = h ? -1.f : 1.f, sc = (it & 1) ? sc1 : sc0;
    float mx = sg * x[0], s = 0.f;
#pragma unroll 1
    for (int j = 0; j < 16; j += 4) mx = fmaxf(mx, fmaxf(sg * x[j], sg * x[j + 1]));
    mx = fmaxf(mx, __shfl_xor_sync(0xffffffffu, mx, 1));
    mx = fmaxf(mx, __shfl_xor_sync(0xffffffffu, mx, 2));
#pragma unroll 1
    for (int j = 0; j < 32; j += 4) {
      const float a = ex2((sg * x[(j & 15) + h] - mx) * sc), c = ex2((sg * x[(j & 15) + 1 - h] - mx) * sc);
      if (j < 16) s += a + c;
      else w[(it >> 1) * 8 + (j >> 1) - 8 + (it & 1)] = pack_bf16(a * s, c * s);
      if (j == 12) {
        s += __shfl_xor_sync(0xffffffffu, s, 1);
        s += __shfl_xor_sync(0xffffffffu, s, 2);
        s = rcp(s);
      }
    }
  }
#pragma unroll
  for (int i = 0; i < N; i++) o[i] = w[i];
}
constexpr float FAST_LIMIT = RCPG == 2 ? 0x1p60f : RCPG == 4 ? 0x1p30f : 0x1p15f;
__device__ __forceinline__ void feature_exp(const float* p, float sc0, float sc1, uint32_t* o, float (&d)[4], uint64_t sel) {
  float e[16], r[8];
#pragma unroll
  for (int i = 0; i < 16; i++) e[i] = ex2(p[i] * ((i & 2) ? sc1 : sc0));
#pragma unroll
  for (int i = 0; i < 8; i++) r[i] = e[2 * i] * e[2 * i + 1];
#pragma unroll
  for (int i = 0; i < 8; i++) o[i] = pack_bf16(e[2 * i], e[2 * i + 1]);
  uint32_t a[4];
#pragma unroll
  for (int i = 0; i < 2; i++) {
    if (RCPG == 2) {
      o[8 + i] = pack_bf16(rcp(r[i]), rcp(r[2 + i]));
      o[10 + i] = pack_bf16(rcp(r[4 + i]), rcp(r[6 + i]));
    } else {
      float u = r[i] * r[2 + i], w = r[4 + i] * r[6 + i];
      if (RCPG == 4) { u = rcp(u); w = rcp(w); }
      else { const float z = rcp(u * w), y = z * u; u = z * w; w = y; }
      o[8 + i] = pack_bf16(u * r[2 + i], u * r[i]);
      o[10 + i] = pack_bf16(w * r[6 + i], w * r[4 + i]);
    }
    a[i] = hadd2(hadd2(o[i], o[2 + i]), hadd2(o[4 + i], o[6 + i]));
    a[2 + i] = hfma2<1>(o[6 + i], o[10 + i], hfma2<0>(o[4 + i], o[10 + i], hfma2<1>(o[2 + i], o[8 + i], hmul2<0>(o[i], o[8 + i]))));
  }
  wg_fence();
  wg_n8_rs<0>(d, a[0], a[1], a[2], a[3], sel, 0);
  wg_commit();
}
template <bool FULL>
__device__ __forceinline__ float feature_norm(uint32_t* o, const float (&d)[4]) {
  uint32_t c[4];
  if (FULL) {
#pragma unroll
    for (int i = 0; i < 2; i++) {
      const float z = rcp(d[2 * i] * d[2 * i + 1]);
      const uint32_t n = pack_bf16(z * d[2 * i + 1], z * d[2 * i]);
      c[i] = hmul2<1>(o[8 + i], n); c[2 + i] = hmul2<1>(o[10 + i], n);
#pragma unroll
      for (int j = i; j < 8; j += 2) {
        o[8 + j] = (j & 2) ? hmul2<1>(o[j], c[(j >> 2) * 2 + i]) : hmul2<0>(o[j], c[(j >> 2) * 2 + i]);
        o[j] = hmul2<0>(o[j], n);
      }
    }
  } else {
    const uint32_t n = pack_bf16(d[0] * rcp(d[1]), d[2] * rcp(d[3]));
    c[0] = hmul2<0>(o[8], n); c[1] = hmul2<1>(o[9], n); c[2] = hmul2<0>(o[10], n); c[3] = hmul2<1>(o[11], n);
#pragma unroll
    for (int j = 0; j < 8; j++) o[8 + j] = (j & 2) ? hmul2<1>(o[j], c[(j >> 2) * 2 + (j & 1)]) : hmul2<0>(o[j], c[(j >> 2) * 2 + (j & 1)]);
  }
  return (d[0] + d[1]) + (d[2] + d[3]);
}
__device__ __forceinline__ float feature_norm32(const float (&e)[16], const float (&r)[8], const float (&d)[4], uint32_t* o) {
#pragma unroll
  for (int i = 0; i < 2; i++) {
    const float z = rcp(d[2 * i] * d[2 * i + 1]), np = z * d[2 * i + 1], nm = z * d[2 * i];
    if (KH2) {
      const float q = nm * d[2 * i];
      const uint32_t c0 = pack_bf16(r[i] * q, r[2 + i] * q), c1 = pack_bf16(r[4 + i] * q, r[6 + i] * q);
#pragma unroll
      for (int j = i; j < 8; j += 2) {
        o[j] = pack_bf16(e[2 * j] * np, e[2 * j + 1] * np);
        o[8 + j] = (j & 2) ? hmul2<1>(o[j], (j & 4) ? c1 : c0) : hmul2<0>(o[j], (j & 4) ? c1 : c0);
      }
    } else {
#pragma unroll
      for (int j = i; j < 8; j += 2) {
        const float c = r[j] * nm;
        o[j] = pack_bf16(e[2 * j] * np, e[2 * j + 1] * np);
        o[8 + j] = pack_bf16(e[2 * j] * c, e[2 * j + 1] * c);
      }
    }
  }
  return (d[0] + d[1]) + (d[2] + d[3]);
}
template <class H>
__device__ __forceinline__ float feature_fast(const float* p, float sc0, float sc1, uint32_t* o, H hook) {
  float e[16], r[8], sp[2] = {0.f, 0.f}, sm[2] = {0.f, 0.f};
#pragma unroll
  for (int i = 0; i < 16; i++) e[i] = ex2(p[i] * ((i & 2) ? sc1 : sc0));
#pragma unroll
  for (int i = 0; i < 8; i++) r[i] = e[2 * i] * e[2 * i + 1];
#pragma unroll
  for (int i = 0; i < 2; i++) {
    float u = r[i] * r[2 + i], w = r[4 + i] * r[6 + i];
    if (RCPG == 4) { u = rcp(u); w = rcp(w); }
    else { const float z = rcp(u * w), y = z * u; u = z * w; w = y; }
    const float c = u * r[i], d = w * r[4 + i];
    r[i] = u * r[2 + i]; r[2 + i] = c; r[4 + i] = w * r[6 + i]; r[6 + i] = d;
  }
#pragma unroll
  for (int i = 0; i < 8; i++) {
    const float t = e[2 * i] + e[2 * i + 1];
    sp[i & 1] += t; sm[i & 1] = fmaf(t, r[i], sm[i & 1]);
  }
  const float tot = (sp[0] + sp[1]) + (sm[0] + sm[1]);
  if (KSH == 1) {
#pragma unroll
    for (int i = 0; i < 2; i++) {
      uint32_t v = pack_bf16(sp[i], sm[i]);
      v = hadd2(v, __shfl_xor_sync(0xffffffffu, v, 1));
      const uint32_t w = __shfl_xor_sync(0xffffffffu, v, 2);
      sp[i] = bf_lo(v) + bf_lo(w); sm[i] = bf_hi(v) + bf_hi(w);
    }
  } else {
#pragma unroll
    for (int m = 1; m <= 2; m <<= 1)
#pragma unroll
      for (int i = 0; i < 2; i++) { sp[i] += __shfl_xor_sync(0xffffffffu, sp[i], m); sm[i] += __shfl_xor_sync(0xffffffffu, sm[i], m); }
  }
  hook();
  const float d[4] = {sp[0], sm[0], sp[1], sm[1]};
  feature_norm32(e, r, d, o);
  return tot;
}
__device__ __forceinline__ bool warp_fails(bool ok) { return __builtin_expect(!__all_sync(0xffffffffu, ok), 0); }
constexpr uint32_t OTAG = 0x00010001u;
__device__ __forceinline__ void attn_out(const float (&u)[20], uint32_t tg, uint32_t* r, uint4* dst, bool pub) {
  const float d0 = rcp(fmaf(u[17], 0.5e-6f, u[16])), d1 = rcp(fmaf(u[19], 0.5e-6f, u[18]));
#pragma unroll
  for (int j = 0; j < 8; j++) r[j] = pack_bf16(u[2 * j] * ((j & 1) ? d1 : d0), u[2 * j + 1] * ((j & 1) ? d1 : d0));
  r[0] = (r[0] & ~OTAG) | tg; r[4] = (r[4] & ~OTAG) | tg;
  if (pub) {
    st_rec16(dst, r[0], r[1], r[2], r[3]);
    st_rec16(dst + 32, r[4], r[5], r[6], r[7]);
  }
}

__device__ __forceinline__ uint32_t with_tag(uint32_t w, uint32_t tg) {
  const uint32_t m = (w ^ tg) & OTAG;
  return w + m - (w & (m + m));
}

constexpr float L2E = 1.4426950408889634f;

__device__ __forceinline__ int pc_chunk(int j, int cb) {
  const int c = j > 8, e = j - 2 - 7 * c;
  return j < 2 ? 2 * cb + j : 2 * (e == cb ? 7 : e) + c;
}
constexpr unsigned long long Q_ASLOTS = 0x1896308963089630ull, Q_BSLOTS = 0x754217542175421ull;
constexpr unsigned long long Q_CHUNKS = 0xAB9876543210FEDCull;
constexpr unsigned long long PC_ASLOTS = 0x2BA02BA02BA02BAull, PC_BSLOTS = 0x3765437654376543ull;
constexpr unsigned long long FFN_SLOTS = 0xBA8954C11897ull;
constexpr unsigned long long FFN_ORDER = 0xB74A69583210ull;
constexpr unsigned long long FFN_WAIT0 = 0x6B4A65497E7E3D3Eull, FFN_WAIT1 = 0x6C6C4B6Bull;
constexpr unsigned long long FFN_PACE0 = 0x6A67647F51ull, FFN_PACE1 = 0x0ull;
constexpr unsigned long long WO_WAIT0 = 0x626160483C3D3C3Bull, WO_WAIT1 = 0x6A69686766656463ull;
constexpr unsigned long long WO_PACE0 = 0x527F502Full, WO_PACE1 = 0x0ull;
constexpr unsigned long long PF_PACE0 = 0x0ull, PF_PACE1 = 0x1D1D1C1C00000000ull, PF_PACE2 = 0x313130301F1F1E1Eull, PF_PACE3 = 0x3232ull;
constexpr unsigned long long PF_EARLY = 0x111111111111ull;
constexpr int PF_FIRST = 12;
__device__ __forceinline__ uint32_t tab4(unsigned long long t, int i) { return (uint32_t)(t >> (4 * i)) & 15u; }
__device__ __forceinline__ uint32_t tab8(unsigned long long lo, unsigned long long hi, int i) { return (uint32_t)((i < 8 ? lo : hi) >> (8 * (i & 7))) & 255u; }

__device__ __forceinline__ float sum8(uint4 v) {
  return ((bf_lo(v.x) + bf_hi(v.x)) + (bf_lo(v.y) + bf_hi(v.y))) + ((bf_lo(v.z) + bf_hi(v.z)) + (bf_lo(v.w) + bf_hi(v.w)));
}
__device__ __forceinline__ float warp_sum(float s) {
#pragma unroll
  for (int m = 16; m >= 1; m >>= 1) s += __shfl_xor_sync(0xffffffffu, s, m);
  return s;
}
template <class T> __device__ __forceinline__ T* settle(T* p, int lane) {
  return reinterpret_cast<T*>(__shfl_sync(0xffffffffu, reinterpret_cast<unsigned long long>(p), lane));
}
__device__ __forceinline__ float pick4(int c, float a, float b, float d, float e) {
  float r;
  asm("{\n.reg .pred p, q;\n.reg .f32 u, v;\n.reg .b32 t;\nand.b32 t, %1, 1;\nsetp.ne.u32 p, t, 0;\nsetp.gt.u32 q, %1, 1;\n"
      "selp.f32 u, %3, %2, p;\nselp.f32 v, %5, %4, p;\nselp.f32 %0, v, u, q;\n}\n" : "=f"(r) : "r"(c), "f"(a), "f"(b), "f"(d), "f"(e));
  return r;
}
__device__ __forceinline__ uint32_t differ(uint32_t a, uint32_t b, uint32_t t) { uint32_t r; asm("lop3.b32 %0, %1, %2, %3, 0x7E;" : "=r"(r) : "r"(a), "r"(b), "r"(t)); return r; }
__device__ __forceinline__ uint32_t ln_res(uint32_t h, float a, float c, uint32_t& n) {
  const float l = bf_lo(h), u = bf_hi(h);
  n = pack_bf16(fmaf(l, a, c), fmaf(u, a, c));
  return hadd2(h, n);
}

__device__ __forceinline__ uint64_t ext_a(uint32_t sb, uint32_t row) { return mk_desc(sb + 12 * SLOT + 4096 + row * 16, 4096 - row * 16, 128, 0); }
__device__ __forceinline__ uint64_t ext_b(uint32_t sb, uint32_t part) { return mk_desc(sb + 12 * SLOT + part * 2048, 1024, 0, 1); }
__device__ __forceinline__ uint64_t sum_b(uint32_t sb) { return mk_desc(sb + OFF_SEL, 16, 128, 0); }
__device__ __forceinline__ uint32_t split_bf16(float v) { return pack_bf16(v, v - bf_round(v)); }

template <int N> __device__ __forceinline__ void padn() { if constexpr (N > 1) { padn<N / 2>(); padn<N - N / 2>(); } else if constexpr (N == 1) asm volatile("nanosleep.u32 1;"); }
__global__ void __launch_bounds__(NTHREADS, 1) fused_kernel(const __grid_constant__ Params P) {
  extern __shared__ __align__(1024) uint8_t smem_raw[];
  const uint32_t sb = smem_u32(smem_raw);
  const uint32_t bars = sb + OFF_BAR;
  const int tid = threadIdx.x;
  const int wg = __shfl_sync(0xffffffffu, tid >> 7, 0);
  const int warp = __shfl_sync(0xffffffffu, (tid >> 5) & 3, 0);
  const int lane = tid & 31;
  const int b = MAP == 0 ? (blockIdx.x & 1) * 64 + (blockIdx.x >> 1)
              : MAP == 1 ? (blockIdx.x >> 5) * 32 + (blockIdx.x & 3) * 8 + ((blockIdx.x >> 2) & 7)
              : MAP == 2 ? (blockIdx.x >> 5) * 32 + ((blockIdx.x >> 2) & 3) * 8 + ((blockIdx.x >> 4) & 1) * 4 + (blockIdx.x & 3)
              : MAP == 3 ? (blockIdx.x & 3) * 32 + (blockIdx.x >> 5) * 8 + ((blockIdx.x >> 2) & 7)
              : (blockIdx.x & 1) * 64 + ((blockIdx.x >> 1) & 1) * 8 + (blockIdx.x >> 5) * 16 + ((blockIdx.x >> 2) & 7);
  const bool ffn = (blockIdx.x & 7) != 7;
  const int fi = blockIdx.x - (blockIdx.x >> 3);
  const int rbk = b >> 4, hp = b & 15;
  const int rb = b >> 3, cb = b & 7;
#define BAR(i) (bars + 8u * (uint32_t)(i))
#define MMA_IDS \
    const int tid = fresh_tid(), lane = tid & 31; \
    const bool leader = (tid & 127) == 0; \
    const uint32_t srow = (uint32_t)(warp * 16 + (lane & 7) + ((lane >> 3) & 1) * 8); \
    const uint32_t sx = (uint32_t)(lane >> 4) ^ (srow & 7); \
    const int c2 = (lane & 3) * 2, lr = warp * 16 + (lane >> 2); \
    (void)leader; (void)sx; (void)c2; (void)lr;

  auto load_kv = [&](int it) {
    const uint32_t s = sb + (uint32_t)(it & 3) * 3 * SLOT, fb = BAR(B_FKV + it);
    mbar_expect_tx(fb, ((SKIP & 8) ? 0 : 2 * SLOT) + ((SKIP & 16) ? 0 : SLOT));
    if (!(SKIP & 8)) {
    tma_load_2d(s, &P.mX, fb, it * 64, rb * 128);
    tma_load_2d(s + SLOT, &P.mX, fb, it * 64, (rb ^ 1) * 128);
    }
    if (!(SKIP & 16)) {
    tma_load_w<WEF & 1>(s + 2 * SLOT, &P.mW, fb, 1024 + hp * 64, it * 64);
    tma_load_w<WEF & 1>(s + 2 * SLOT + 8192, &P.mW, fb, 2048 + hp * 64, it * 64);
    }
  };
  auto prefetch = [&](int c) {
    if (c < 2) { l2_prefetch(P.wo + b * 8192 + c * 4096, 8192); return; }
    if (!ffn) return;
    const int e = c - 2;
    if (e == 0) mbar_expect_tx(BAR(B_TCH), 24 * 1024);
    const CUtensorMap* mp = e >= 16 ? &P.mWdT : (e & 1) ? &P.mWuT : &P.mWgT;
    const int r = e >= 16 ? fi * 512 + (e - 16) * 64 : (e >> 1) * 128 + (fi & 1) * 64;
#pragma unroll 1
    for (int q = 0; q < 64; q += TROWS) tma_load_2d(sb + OFF_TCH, mp, BAR(B_TCH), e >= 16 ? 0 : (fi >> 1) * 64, r + q);
  };

  {
    const int w16 = wg * 4 + warp;
    const uint32_t cnt = w16 == 14 ? 128u : ((0x300Cu >> w16) & 1u) + 1u;
    if (elect()) {
      if (w16 == 11) {
#pragma unroll
        for (int i = 0; i < 4; i++) mbar_init(BAR(B_FKV + i), 1u);
        if (FINE) { mbar_init(BAR(B_F0), 1u); mbar_init(BAR(B_F0 + 1), 1u); }
        asm volatile("fence.mbarrier_init.release.cluster;" ::: "memory");
        if (FINE) {
          mbar_expect_tx(BAR(B_FKV), 24576);
          tma_load_2d(sb, &P.mX2, BAR(B_FKV), 0, rb * 128);
          tma_load_2d(sb + 2 * SLOT, &P.mW2, BAR(B_FKV), 1024 + hp * 64, 0);
          tma_load_2d(sb + 2 * SLOT + 8192, &P.mW2, BAR(B_FKV), 2048 + hp * 64, 0);
          tma_load_2d(sb + SLOT, &P.mX2, BAR(B_FKV), 0, (rb ^ 1) * 128);
          mbar_expect_tx(BAR(B_F0), 8192);
          tma_load_2d(sb + 2 * SLOT + 4096, &P.mW2, BAR(B_F0), 1024 + hp * 64, 32);
          tma_load_2d(sb + 2 * SLOT + 12288, &P.mW2, BAR(B_F0), 2048 + hp * 64, 32);
          mbar_expect_tx(BAR(B_F0 + 1), 16384);
          tma_load_2d(sb + 8192, &P.mX2, BAR(B_F0 + 1), 0, rb * 128 + 64);
          tma_load_2d(sb + SLOT + 8192, &P.mX2, BAR(B_F0 + 1), 0, (rb ^ 1) * 128 + 64);
        } else load_kv(0);
#pragma unroll
        for (int i = 1; i < K1E; i++) load_kv(i);
      }
#pragma unroll
      for (int i = 0; i < 8; i++)
      {
        if (w16 || i >= 4) mbar_init(BAR(w16 * 8 + i), w16 == 15 ? (uint32_t)(MISC_COUNTS >> (8 * i)) & 255u : cnt);
        if (K1M && i == K1M - 1 && w16 == 11) load_kv(1);
      }
      mbar_init(BAR(B_FS + w16), w16 >= 14 ? 2u : 1u);
      mbar_init(BAR(B_FW + w16), 1u);
      asm volatile("fence.mbarrier_init.release.cluster;" ::: "memory");
    }
    __syncwarp();
    if (w16 == 11 && elect()) {
#pragma unroll 1
      for (int i = K1M ? 2 : K1E; i < K2W; i++) { load_kv(i); }
    }
    __syncwarp();
  }

  if (wg >= 2) {
    if (wg == 3) {
      asm volatile("setmaxnreg.dec.sync.aligned.u32 64;");
      asm volatile("barrier.sync 0;" ::: "memory");
        if (warp) {
          const int q = 3 * b + warp - 1, cg = q % 96, kq = q / 96;
          const uint32_t buf = sb + (warp == 3 ? OFF_PHIQ : 12 * SLOT + (warp - 1) * 8192);
          const uint32_t fb = BAR(B_FS + (warp - 1) * 4);
          mbar_wait(BAR(B_FKV + ((CSW >> (4 * (kq + (cg < 32 ? 0 : 4)))) & 15)));
          if (elect()) {
#pragma unroll
            for (int p = 0; p < 2; p++) { mbar_expect_tx(fb + p * 8, 4096); tma_load_w<WEF & 4>(buf + p * 4096, &P.mWs, fb + p * 8, cg * 32, kq * 256 + p * 64); }
          }
          float cs[8];
#pragma unroll
          for (int i = 0; i < 8; i++) cs[i] = 0.f;
          const unsigned ep = ld_relaxed(&g_epoch);
#pragma unroll 1
          for (int p = 0; p < 4; p++) {
            mbar_wait(fb + p * 8);
            uint4 v[8];
#pragma unroll
            for (int i = 0; i < 8; i++) v[i] = lds_u4(buf + (p & 1) * 4096 + i * 512 + lane * 16);
            if (p < 2) {
              uint32_t dep = 0;
#pragma unroll
              for (int i = 0; i < 8; i++) dep ^= v[i].x;
              const int n = p + 2 + (int)__shfl_sync(0xffffffffu, zero_after(dep), 0);
              if (elect()) {
                mbar_expect_tx(fb + n * 8, 4096);
                tma_load_w<WEF & 4>(buf + (n & 1) * 4096, &P.mWs, fb + n * 8, cg * 32, kq * 256 + n * 64);
              }
            }
#pragma unroll
            for (int i = 0; i < 8; i += 2) {
              cs[0] += bf_lo(v[i].x) + bf_lo(v[i + 1].x); cs[1] += bf_hi(v[i].x) + bf_hi(v[i + 1].x);
              cs[2] += bf_lo(v[i].y) + bf_lo(v[i + 1].y); cs[3] += bf_hi(v[i].y) + bf_hi(v[i + 1].y);
              cs[4] += bf_lo(v[i].z) + bf_lo(v[i + 1].z); cs[5] += bf_hi(v[i].z) + bf_hi(v[i + 1].z);
              cs[6] += bf_lo(v[i].w) + bf_lo(v[i + 1].w); cs[7] += bf_hi(v[i].w) + bf_hi(v[i + 1].w);
            }
          }
          {
            const bool u4 = lane & 16, u2 = lane & 8, u1 = lane & 4;
#pragma unroll
            for (int i = 0; i < 4; i++) cs[i] = (u4 ? cs[4 + i] : cs[i]) + __shfl_xor_sync(0xffffffffu, u4 ? cs[i] : cs[4 + i], 16);
#pragma unroll
            for (int i = 0; i < 2; i++) cs[i] = (u2 ? cs[2 + i] : cs[i]) + __shfl_xor_sync(0xffffffffu, u2 ? cs[i] : cs[2 + i], 8);
            cs[0] = (u1 ? cs[1] : cs[0]) + __shfl_xor_sync(0xffffffffu, u1 ? cs[0] : cs[1], 4);
          }
          if (warp == 3 && elect()) {
            mbar_expect_tx(BAR(B_PHI), 12288);
            tma_load_2d(sb + OFF_PHIK, &P.mPhi, BAR(B_PHI), 0, hp * 64);
            tma_load_2d(sb + OFF_PHIQ, &P.mPhi, BAR(B_PHI), (int)zero_after(__float_as_uint(cs[0])), cb * 128);
            tma_load_2d(sb + OFF_PHIQ + 4096, &P.mPhi, BAR(B_PHI), (int)zero_after(__float_as_uint(cs[0])), cb * 128 + 64);
          }
          st_rec8(&g_colsum[kq][cg * 32 + (lane & 3) * 8 + (lane >> 2)], __float_as_uint(cs[0]), ep + 1);
          if (lane == 0) mbar_arrive(BAR(B_CSD));
        }
      asm volatile("setmaxnreg.dec.sync.aligned.u32 32;");
      if (warp == 0) {
        int pc = 0;
#pragma unroll 1
        for (int it = K2W; it < 16; it++) {
          mbar_wait(BAR(it >= 4 ? B_DKV + it - 4 : it == 3 ? K3B : B_FKV));
          if (elect()) {
            load_kv(it);
#pragma unroll 1
            for (int n = tab4(PF_EARLY << 16, it); n > 0; n--) prefetch(pc++);
          }
        }
#pragma unroll 1
        for (int it = 0; it < 16; it++) {
          const uint32_t fb = BAR(B_FQ + it), s = sb + tab4(Q_BSLOTS, it) * SLOT;
          int kc = (int)tab4(Q_CHUNKS, it);
          const bool own = (kc >> 1) == cb;
          kc = (own ? 10 + (kc & 1) : it >= 14 ? 2 * cb + (kc & 1) : kc) * 64;
          if (it == 5) mbar_wait(BAR(B_DKV + 15));
          mbar_wait(it >= QD ? BAR(B_DQ + it - QD) : BAR(B_DKV + 12 + (own && it < 4 ? it : it >> 1)));
          if (elect()) {
            mbar_expect_tx(fb, it < 4 && !own ? SLOT : 2 * SLOT);
            if (it >= 4 || own) tma_load_2d(sb + tab4(Q_ASLOTS, it) * SLOT, &P.mX, fb, kc, rb * 128);
            tma_load_2d(s, &P.mW, fb, cb * 128, kc);
            tma_load_2d(s + 8192, &P.mW, fb, cb * 128 + 64, kc);
          }
        }
        mbar_wait(BAR(B_KVRDY));
        const unsigned tag = lds_u(sb + OFF_RED + 4);
        const unsigned* fp = &g_oflag[rb][cb][lane & 15].x;
        uint32_t seen = 0, all = 0, perm = 0, pv = ld_relaxed(fp), left = cb < 3 ? (0x4015u ^ (1u << (2 * cb))) : 0x15u;
#pragma unroll 1
        for (int j = 2; j < 16; j++) {
          if (!DYN || j >= 5) left = 1u << pc_chunk(j, cb);
          if (j == GATE) all = 0xFFFFu;
#pragma unroll 1
          for (int it = 0; it < SPIN && j <= 8 && !((seen & (seen >> 1) & left) && (seen & all) == all); it++) {
            seen |= __ballot_sync(0xffffffffu, pv == tag);
            pv = ld_relaxed(fp);
          }
          const int kc = (__ffs(j <= 8 ? seen & (seen >> 1) & left : left) - 1) & 15;
          left ^= 1u << kc;
          const int dj = j < 5 ? (kc == 14 ? cb : kc >> 1) + 2 - j : 0;
          const int ds = j < 5 ? dj : (int)(perm << 12) >> 28;
          perm = (perm << 4) | (ds & 15);
          mbar_wait(BAR(j < 4 ? B_KVRDY : j < 6 ? B_QREAD : B_DC + j - 5));
          if (elect()) {
            if (DYN) sts_u2(sb + OFF_RED + 64 + j * 8, dj * 8, ds * 1024);
            mbar_expect_tx(BAR(B_FKV + j), (SKIP & 2) ? 0 : SLOT);
            if (!(SKIP & 2)) asm volatile("cp.async.bulk.shared::cluster.global.mbarrier::complete_tx::bytes [%0], [%1], %2, [%3];"
              :: "r"(sb + tab4(PC_ASLOTS, j) * SLOT), "l"(&g_o[rb][kc][0][0][0]), "n"(SLOT), "r"(BAR(B_FKV + j)) : "memory");
          }
        }
      } else {
        if (warp == 1) {
#pragma unroll 1
          for (int j = 0; j < 16; j++) {
            uint32_t s = sb + tab4(PC_BSLOTS, j) * SLOT;
            const uint32_t fb = BAR(B_FB + j);
            const int kc = pc_chunk(j, cb);
            mbar_wait(BAR(tab8(WO_WAIT0, WO_WAIT1, j)));
            mbar_wait(BAR(tab8(WO_PACE0, WO_PACE1, j)));
            if (DYN && j >= 7) s += lds_u(sb + OFF_RED + 28 + j * 8) * 16;
            if (elect()) {
              mbar_expect_tx(fb, (SKIP & 1) ? 0 : SLOT);
              if (!(SKIP & 1)) {
              tma_load_2d(s, &P.mWo, fb, cb * 128, kc * 64);
              tma_load_2d(s + 8192, &P.mWo, fb, cb * 128 + 64, kc * 64);
              }
            }
          }
        } else if (warp == 3) {
#pragma unroll 1
          for (int c = PF_FIRST; c < 26; c++) {
            mbar_wait(BAR(c < 16 ? tab8(PF_PACE0, PF_PACE1, c) : tab8(PF_PACE2, PF_PACE3, c - 16)));
            if (elect()) prefetch(c);
          }
          __syncwarp();
          if (lane == 0) mbar_arrive(BAR(B_KVRDY));
          if (ffn) mbar_wait(BAR(B_TCH));
          mbar_wait(BAR(B_DC + 10));
#pragma unroll 1
          for (int i = 0; i < 4; i++) st_rec16(&g_o[rb][16][2 * i + (lane >> 4)][cb & 3][(lane & 14) * 2 + (lane & 1) + (cb >> 2) * 2], 0u, 0u, 0u, 0u);
          st_rec16(&g_o[rb][17][0][cb][lane], 0u, 0u, 0u, 0u);
          if (lane < 2) st_rec16(reinterpret_cast<uint4*>(&g_key[cb][rb >> 2][(rb & 3) * 4]) + lane, 0u, 0u, 0u, 0u);
          __syncwarp();
          if (lane == 0) mbar_arrive(BAR(B_RESET2));
        } else {
          mbar_wait(BAR(B_DQ + RSTQ));
#pragma unroll 1
          for (int i = 0; i < 9; i++) {
            st_rec16(&g_kvp[2 * hp][rbk][0][i * 32 + lane], 0u, 0u, 0u, 0u);
            st_rec16(&g_kvp[2 * hp + 1][rbk][0][i * 32 + lane], 0u, 0u, 0u, 0u);
          }
#pragma unroll 1
          for (int i = 0; i < 3; i++) st_rec16(&g_kvr[2 * hp + (lane >> 4)][i][i < 2 ? rbk * 16 + (lane & 15) : rbk * 4 + (lane & 3)], 0u, 0u, 0u, 0u);
          if (lane < 16) st_rec16(&g_oflag[rb][lane >> 1][cb * 2 + (lane & 1)], 0u, 0u, 0u, 0u);
          __syncwarp();
          if (lane == 0) mbar_arrive(BAR(B_RESET));
          if (ffn) {
#pragma unroll 1
            for (int n = 0; n < 12; n++) {
              const int i = (int)tab4(FFN_ORDER, n);
              uint32_t s = sb + tab4(FFN_SLOTS, i) * SLOT;
              const uint32_t fb = BAR(B_FW + i);
              mbar_wait(BAR(tab8(FFN_WAIT0, FFN_WAIT1, n)));
              mbar_wait(BAR(tab8(FFN_PACE0, FFN_PACE1, n)));
              if (DYN && i == 7) s += lds_u(sb + OFF_RED + 84) * 16;
              if (elect()) {
                mbar_expect_tx(fb, (SKIP & 4) ? 0 : SLOT);
                if (!(SKIP & 4)) tma_load_3d_ef(s, i >= 8 ? &P.mWd : (i & 1) ? &P.mWu : &P.mWg, fb, i < 8 ? fi * 32 : 0, i < 8 ? (i >> 1) * 256 : fi * 32, i < 8 ? 0 : (i - 8) * 4);
              }
            }
          }
        }
      }
    } else {
      asm volatile("barrier.sync 0;" ::: "memory");
      const int t = tid - 256;
      const unsigned tag = ld_relaxed(&g_epoch) + 1;
      if (warp == 0) {
        float s = 0.f;
#pragma unroll
        for (int i = 0; i < 4; i++) s += sum8(ldg_nc16(P.wr + i * 256 + lane * 8));
        const uint2 w = *reinterpret_cast<const uint2*>(P.wr + cb * 128 + lane * 4);
        s = warp_sum(s);
        if (lane == 0) { sts_f(sb + OFF_RED, s); sts_u(sb + OFF_RED + 4, tag); sts_u(sb + OFF_RED + 16, 0u); }
        if (lane == 1) { const uint32_t t3 = tag % 3u + 1u; sts_u2(sb + OFF_RED + 8, (t3 & 1u) | ((t3 & 2u) << 15), t3); }
        const uint32_t a = sb + OFF_WR + (lane & 1) * 128 + (lane >> 1) * 4;
        sts_u(a, w.x); sts_u(a + 64, w.y);
      }
      __syncwarp();
      {
        const __nv_bfloat16* xp = P.x + (size_t)(b * 16 + warp * 4 + (lane >> 3)) * DM + (lane & 7) * 8;
        float sh = 0.f, s0 = 0.f, q0 = 0.f, s1 = 0.f, q1 = 0.f;
        uint32_t ns = 0;
#pragma unroll 1
        for (int g = 0; g < 16 / SXN; g++) {
          uint4 xv[SXN];
          mbar_wait(BAR(B_FKV + SX0 + g * SXD));
#pragma unroll
          for (int i = 0; i < SXN; i++) xv[i] = ldg_nc16(xp + (g * SXN + i) * 64);
          if (g == 0) {
            sh = __shfl_sync(0xffffffffu, bf_lo(xv[0].x), lane & 24);
            ns = pack_bf16(-sh, -sh);
          }
#pragma unroll
          for (int i = 0; i < SXN; i++) {
              const uint32_t a = hadd2(xv[i].x, ns), c = hadd2(xv[i].y, ns), d = hadd2(xv[i].z, ns), e = hadd2(xv[i].w, ns);
              const uint32_t u = hadd2(hadd2(a, c), hadd2(d, e)), w = hsq2(a, hsq2(c, hsq2(d, hsq2(e, 0u))));
              s0 += bf_lo_p(u); s1 += bf_hi(u); q0 += bf_lo_p(w); q1 += bf_hi(w);
          }
        }
        s0 += s1; q0 += q1;
#pragma unroll
        for (int m = 4; m >= 1; m >>= 1) { s0 += __shfl_xor_sync(0xffffffffu, s0, m); q0 += __shfl_xor_sync(0xffffffffu, q0, m); }
        s0 *= (1.f / DM);
        const float var = fmaxf(q0 * (1.f / DM) - s0 * s0, 0.f);
        if ((lane & 7) == 0) st_rec16(&g_rowstat[b * 16 + warp * 4 + (lane >> 3)], __float_as_uint(rsq(var + 1e-5f)), __float_as_uint(-(s0 + sh)), 0u, tag);
      }
      {
        const uint4* rp = &g_rowstat[rb * 128 + t];
        const uint4* rq = &g_rowstat[(rb ^ 1) * 128 + t];
        const uint2* c0 = &g_colsum[0][1024 + (t >> 6) * 1024 + hp * 64 + (t & 63)];
        const uint2* c1 = &g_colsum[0][cb * 128 + t];
        uint4 v0, v1; uint2 u[8];
#pragma unroll 1
        for (int it = 0; it < SPIN; it++) {
          v0 = ld_rec16(rp); v1 = ld_rec16(rq);
          bool ok = true;
#pragma unroll
          for (int i = 0; i < 4; i++) { u[i] = ld_rec8(c0 + i * 3072); u[4 + i] = ld_rec8(c1 + i * 3072); }
#pragma unroll
          for (int i = 0; i < 8; i++) ok = ok && u[i].y == tag;
          if (__all_sync(0xffffffffu, ok && v0.w == tag && v1.w == tag)) break;
          __nanosleep(100);
        }
        sts_u(sb + OFF_RSTAT + t * 4, v0.x); sts_u(sb + OFF_RSTAT + (t + 128) * 4, v1.x);
        mbar_wait(BAR(B_CSD));
        {
          const uint32_t m0 = split_bf16(__uint_as_float(v0.y)), m1 = split_bf16(__uint_as_float(v1.y));
          sts_u4(sb + 12 * SLOT + 4096 + t * 16, m0, m0 & 0xFFFFu, 0u, 0u);
          sts_u4(sb + 12 * SLOT + 6144 + t * 16, m1, m1 & 0xFFFFu, 0u, 0u);
          sts_u2(sb + 12 * SLOT + 8192 + t * 8, 0u, 0u);
        }
#pragma unroll
        for (int e = 0; e < 2; e++) {
          const uint32_t hl = split_bf16((__uint_as_float(u[4 * e].x) + __uint_as_float(u[4 * e + 1].x)) + (__uint_as_float(u[4 * e + 2].x) + __uint_as_float(u[4 * e + 3].x)));
          const uint32_t a = sb + 12 * SLOT + e * 2048 + (t >> 6) * 1024 + (t & 7) * 2, ch = (uint32_t)(t >> 3) & 7u;
#pragma unroll
          for (uint32_t r = 0; r < 8; r++) sts_h(a + r * 128 + ((ch ^ r) << 4), r < 2 ? hl : r == 2 ? hl >> 16 : 0u);
        }
        sts_u(sb + OFF_ONES + t * 4, 0x3F803F80u);
        sts_u(sb + OFF_ONES + 512 + t * 4, 0x3F803F80u);
        if (t < 36) sts_u(sb + OFF_SEL + t * 4, (t & 4) ? 0u : 0x3F803F80u);
        {
          const uint32_t one = (t & 56) == 24 ? 0x3F80u << ((t & 1) * 16) : 0u, w = (t >> 1) & 3;
          sts_u4(sb + OFF_EYE + t * 16, w == 0 ? one : 0u, w == 1 ? one : 0u, w == 2 ? one : 0u, w == 3 ? one : 0u);
        }
        fence_async_smem();
        bar_sync(3, 128);
      }
      asm volatile("setmaxnreg.inc.sync.aligned.u32 160;");
      {
        float a0[64], a1[64];
        {
          wg_fence();
          wg_n128<0, 1>(a0, ext_a(sb, 0), ext_b(sb, 1), 0);
          wg_n128<0, 1>(a1, ext_a(sb, 64), ext_b(sb, 1), 0);
          wg_commit();
          wg_wait<0>();
          mbar_arrive(BAR(B_STAT));
        }
        {
#pragma unroll 1
          for (int it = 12; it < 16; it++) mbar_wait(BAR(B_FKV + it));
          mbar_wait(BAR(B_QGO));
#pragma unroll 1
          for (int it = 0; it < 16 - QWIN; it++) {
            if (QGATE < 16 - QWIN && it == QGATE) mbar_wait(BAR(B_KVFREE));
            mbar_wait(BAR(B_FQ + it));
            const uint64_t da = mk_desc(sb + tab4(Q_ASLOTS, it) * SLOT, 16, 1024, 1);
            const uint64_t db = mk_desc(sb + tab4(Q_BSLOTS, it) * SLOT, 8192, 1024, 1);
#pragma unroll
            for (int hf = 0; hf < 2; hf++) {
              int yt = THR > hf ? fresh_tid() : tid;
              if (hf && THR > 1) asm volatile("mov.u32 %0, %%tid.y;" : "=r"(yt));
              wg_fence();
#pragma unroll
              for (int kk = hf ? QSPL : 0; kk < (hf ? 4 : QSPL); kk++) {
                wg_n128<0, 1>(a0, da + kk * 2, db + kk * 128, 1);
                if (THR > 2 && kk == 2 * hf && yt == 8192) pin_order();
                wg_n128<0, 1>(a1, da + kk * 2 + 512, db + kk * 128, 1);
              }
              wg_commit();
              if (hf == 0 || QW2) wg_wait<1>();
              if (hf == 0 && it > 0 && (yt & 127) == 0) mbar_arrive(BAR(B_DQ + it - 1));
            }
          }
        }
        MMA_IDS
        const uint32_t qa = __shfl_sync(0xffffffffu, sb + 10 * SLOT + srow * 128 + (sx << 4), lane);
        const uint32_t tg = lds_u(sb + OFF_RED + 8);
        const uint32_t ka = sb + 12 * SLOT + srow * 64 + (((uint32_t)(lane >> 4) ^ ((srow >> 1) & 3)) << 4);
        const uint4* const src = &g_kvr[4 * cb][0][tid & 127];
        const uint2* const srz = reinterpret_cast<const uint2*>(&g_kvr[4 * cb][2][(tid & 127) >> 2]);
        uint4 a[8];
        uint2 z[4];
#pragma unroll
        for (int i = 0; i < 8; i++) a[i] = make_uint4(0u, 0u, 0u, 0u);
        auto fetch = [&]() {
#pragma unroll
          for (int i = 0; i < 8; i++) {
            ld_rec16_stale(a[i], src + (i >> 1) * 384 + (i & 1) * 128, tg);
            if (i & 1) z[i >> 1] = ld_rec8(srz + (i >> 1) * 768);
          }
        };
        {
          auto step = [&](float (&a)[64], int it, int mb) {
            const uint64_t da = mk_desc(sb + tab4(Q_ASLOTS, it) * SLOT + mb * 8192, 16, 1024, 1);
            const uint64_t db = mk_desc(sb + tab4(Q_BSLOTS, it) * SLOT, 8192, 1024, 1);
            wg_fence();
#pragma unroll
            for (int kk = 0; kk < 4; kk++) wg_n128<0, 1>(a, da + kk * 2, db + kk * 128, 1);
            wg_commit();
          };
          auto dump = [&](const float (&q)[64], int mb, int c) {
#pragma unroll
            for (int jj = 0; jj < 4; jj++) {
              const float* a = &q[32 * c + 8 * jj];
              stsm_x4((qa ^ (32 * jj)) + c * SLOT + mb * 8192, pack_bf16(a[0], a[1]), pack_bf16(a[2], a[3]), pack_bf16(a[4], a[5]), pack_bf16(a[6], a[7]));
            }
            fence_async_smem();
            mbar_arrive(BAR(B_QD + c + 3 * mb));
            pin_order();
          };
#pragma unroll
          for (int it = 16 - QWIN; it < 16; it++) {
            if (it == QGATE) mbar_wait(BAR(B_KVFREE));
            mbar_wait(BAR(B_FQ + it));
            step(a1, it, 1);
            if (it == 16 - QWIN) {
              wg_wait<1>();
              if (leader) mbar_arrive(BAR(B_DQ + it - 1));
            }
          }
          mbar_wait(BAR(B_KVFREE));
#pragma unroll
          for (int it = 16 - QWIN; it < 16; it++) step(a0, it, 0);
          wg_wait<QWIN>();
          dump(a1, 1, 0);
          dump(a1, 1, 1);
          wg_wait<0>();
          dump(a0, 0, 0);
          if (leader) {
#pragma unroll
            for (int it = 16 - QWIN; it < 16; it++) mbar_arrive(BAR(B_DQ + it));
          }
          dump(a0, 0, 1);
        }
        auto put = [&]() {
#pragma unroll
          for (int h = 0; h < 4; h++) {
            stsm_x4(ka + h * 4096, a[2 * h].x, a[2 * h].y, a[2 * h].z, a[2 * h].w);
            stsm_x4((ka ^ 32) + h * 4096, a[2 * h + 1].x, a[2 * h + 1].y, a[2 * h + 1].z, a[2 * h + 1].w);
            if (h & 1)
              stsm_x4((ka ^ ((h - 1) * 16)) + SLOT, __byte_perm(z[h - 1].y, 0x3F80u, 0x5410), __byte_perm(z[h - 1].y, 0x3F80u, 0x5432),
                      __byte_perm(z[h].y, 0x3F80u, 0x5410), __byte_perm(z[h].y, 0x3F80u, 0x5432));
          }
        };
#pragma unroll 1
        for (int it = 0; it < SPIN; it++) {
          fetch();
          const uint32_t bad = ((differ(a[0].x, a[1].x, tg) | differ(a[2].x, a[3].x, tg)) | (differ(a[4].x, a[5].x, tg) | differ(a[6].x, a[7].x, tg))) |
                               (differ(z[0].x, z[1].x, tg) | differ(z[2].x, z[3].x, tg));
          if (GSPEC) put();
          if (__all_sync(0xffffffffu, (bad & OTAG) == 0)) break;
        }
        if (!GSPEC) put();
        fence_async_smem();
        __syncwarp();
        if (lane == 0) mbar_arrive(BAR(B_KVRDY));
      }
    }
    if (wg == 3) mbar_wait(BAR(B_DC + 15));
    asm volatile("setmaxnreg.inc.sync.aligned.u32 160;");
    const int w8 = (wg - 2) * 4 + warp;
    uint32_t wf[32][4], wd[16][4];
    {
      const int lane = fresh_tid() & 31;
      const uint32_t mrow = (uint32_t)((lane & 7) + (lane >> 4) * 8), mch = (uint32_t)(lane >> 3) & 1u;
      if (ffn) mbar_wait(BAR(B_FW + w8));
      uint32_t wsm = sb + tab4(FFN_SLOTS, w8) * SLOT + mrow * 64;
      if (DYN && w8 == 7) wsm += lds_u(sb + OFF_RED + 84) * 16;
      const uint32_t sw = (mrow >> 1) & 3;
#pragma unroll
      for (int i = 0; i < 16; i++) {
        ldsm_x4_t(wf[2 * i], wsm + i * 1024 + ((mch ^ sw) << 4));
        ldsm_x4_t(wf[2 * i + 1], wsm + i * 1024 + (((2 + mch) ^ sw) << 4));
      }
      uint32_t dep = 0;
#pragma unroll
      for (int i = 0; i < 32; i++) dep ^= wf[i][0];
      if (w8 < 4 && lane == 0) mbar_arrive(BAR(B_REL + w8) + zero_after(dep));
    }
    if (ffn) {
      const int lane = fresh_tid() & 31;
      if (wg == 2) mbar_wait(BAR(B_DC + 12));
      st_rec16(&g_ypart[w8 * 16 + (lane >> 1)][fi][lane & 1], 0u, 0u, 0u, 0u);
      __syncwarp();
    }
    mbar_wait(BAR(B_DC + 15));
    asm volatile("setmaxnreg.inc.sync.aligned.u32 %0;" :: "n"(256 - TREG));
    {
      const int lane = fresh_tid() & 31;
      const uint32_t mrow = (uint32_t)((lane & 7) + (lane >> 4) * 8), mch = (uint32_t)(lane >> 3) & 1u;
      if (ffn) mbar_wait(BAR(B_FW + 8 + (w8 >> 1)));
      const uint32_t dsm = sb + tab4(FFN_SLOTS, 8 + (w8 >> 1)) * SLOT + (w8 & 1) * 8192 + mrow * 128;
#pragma unroll
      for (int i = 0; i < 8; i++) {
        const uint32_t a = dsm + (i >> 2) * 4096 + ((((uint32_t)(i & 3) * 2 + mch) ^ (mrow & 7)) << 4);
        ldsm_x4_t(wd[2 * i], a);
        ldsm_x4_t(wd[2 * i + 1], a + 2048);
      }
    }
    {
      const int t = fresh_tid() - 256, lane = t & 31, c = lane & 3;
      const unsigned tag = lds_u(sb + OFF_RED + 4);
      uint32_t xw = sb + OFF_PHIQ + w8 * 512 + (lane >> 4) * 64 + c * 16 + (lane & 12);
      uint32_t xr = sb + OFF_PHIQ + w8 * 512 + c * 16;
      uint32_t pw = sb + OFF_CS + (uint32_t)(w8 * 32 + c * 8 + (lane >> 2)) * 4;
      const uint32_t t3 = lds_u(sb + OFF_RED + 12);
      const uint2* kp = &g_key[cb][0][(lane & 15) * 4];
      const char* src = reinterpret_cast<const char*>(&g_o[0][17][0][w8 & 6][lane]);
      uint32_t* yd = &g_ypart[w8 * 16 + c][fi][0].x + (lane >> 2);
      xw = __shfl_sync(0xffffffffu, xw, lane); xr = __shfl_sync(0xffffffffu, xr, lane); pw = __shfl_sync(0xffffffffu, pw, lane);
      kp = settle(kp, lane); src = settle(src, lane); yd = settle(yd, lane);
      uint32_t wkey;
      {
        uint2 v;
        mbar_wait(BAR(B_KEY));
#pragma unroll 1
        for (int it = 0; it < SPIN; it++) {
          v = ld_rec8(kp);
          if (__all_sync(0xffffffffu, v.y == tag)) break;
        }
        wkey = __reduce_max_sync(0xffffffffu, v.x);
      }
      {
        asm volatile("mad.wide.u32 %0, %1, 2304, %0;" : "+l"(src) : "r"(wkey & 0x780u));
        uint4 v0, v1;
#pragma unroll 1
        for (int it = 0; it < SPIN; it++) {
          v0 = ld_rec16(reinterpret_cast<const uint4*>(src)); v1 = ld_rec16(reinterpret_cast<const uint4*>(src) + 32);
          if (__all_sync(0xffffffffu, v0.w == tag && v1.w == tag)) break;
        }
        sts_u(xw, v0.x); sts_u(xw + 128, v0.y); sts_u(xw + 256, v1.x); sts_u(xw + 384, v1.y);
        __syncwarp();
      }
      if (t == 0) mbar_arrive(BAR(B_ROW));
      if (ffn) {
        {
          uint4 xb[8];
#pragma unroll
          for (int i = 0; i < 8; i++) xb[i] = lds_u4(xr + i * 64);
          float d[16];
#pragma unroll
          for (int i = 0; i < 16; i++) d[i] = 0.f;
#pragma unroll
          for (int i = 0; i < 8; i++) {
            mma_bf16(&d[0], wf[4 * i], xb[i].x, xb[i].y); mma_bf16(&d[4], wf[4 * i + 1], xb[i].x, xb[i].y);
            mma_bf16(&d[8], wf[4 * i + 2], xb[i].z, xb[i].w); mma_bf16(&d[12], wf[4 * i + 3], xb[i].z, xb[i].w);
          }
          const float v = pick4(c, d[0], d[2], d[4], d[6]) + pick4(c, d[8], d[10], d[12], d[14]);
          sts_f(pw, v);
        }
        bar_sync(2, 256);
        uint32_t ab[4];
        {
          const uint32_t pr = sb + OFF_CS + lane * 4;
          float p[8];
#pragma unroll
          for (int i = 0; i < 8; i++) p[i] = lds_f(pr + (i & 3) * 256 + (i >> 2) * 128);
          const float g = (p[0] + p[1]) + (p[2] + p[3]);
          const float u = (p[4] + p[5]) + (p[6] + p[7]);
          const float act = (g * u) * rcp(1.f + ex2(-g * L2E));
          const uint32_t pair = pack_bf16(act, __shfl_down_sync(0xffffffffu, act, 1));
#pragma unroll
          for (int i = 0; i < 4; i++) ab[i] = __shfl_sync(0xffffffffu, pair, i * 8 + c * 2);
        }
        float d[32];
#pragma unroll
        for (int i = 0; i < 32; i++) d[i] = 0.f;
#pragma unroll
        for (int h = 0; h < 8; h += DORD) {
#pragma unroll
          for (int i = h; i < h + DORD; i++) mma_bf16(&d[4 * i], wd[2 * i], ab[0], ab[1]);
#pragma unroll
          for (int i = h; i < h + DORD; i++) mma_bf16(&d[4 * i], wd[2 * i + 1], ab[2], ab[3]);
        }
#pragma unroll
        for (int i = 0; i < 4; i++)
          asm volatile("st.relaxed.gpu.global.u32 [%0], %1;" :: "l"(yd + i * 4 * NFFN * 8),
                       "r"((__float_as_uint(pick4(c, d[8 * i], d[8 * i + 2], d[8 * i + 4], d[8 * i + 6])) & ~3u) | t3) : "memory");
      }
      if (b == 0 && t == 32) g_epoch = tag;
      if (w8 == 0) {
        const int wrow = wkey & (SEQ - 1);
        const uint4* fp = &g_o[wrow >> 7][17][2][0][b * 4 + (lane & 1) * 2 + ((lane >> 1) & 1)];
        const uint4* yp = &g_ypart[b][0][0] + lane;
        uint32_t* const op = settle(reinterpret_cast<uint32_t*>(P.out + (size_t)wrow * DM + b * 8 + (lane & 1) * 4 + (lane & 2)), lane);
        const float sig = __shfl_sync(0xffffffffu, rcp(1.f + ex2(-__uint_as_float(wkey ^ (~(uint32_t)((int)wkey >> 31) | 0x80000000u)) * L2E)), lane);
        uint4 fin;
#pragma unroll 1
        for (int it = 0; it < SPIN; it++) {
          fin = ld_rec16(fp);
          if (__all_sync(0xffffffffu, fin.w == tag)) break;
        }
        if (YDLY) {
          const uint32_t c0 = clock();
#pragma unroll 1
          for (int it = 0; it < 1000 && (uint32_t)clock() - c0 < YDLY; it++) { }
        }
        const bool up = lane & 2;
        float y0, y1;
#pragma unroll 1
        for (int it = 0; it < SPIN; it++) {
          uint4 v[7];
#pragma unroll
          for (int i = 0; i < 7; i++) v[i] = ld_rec16(yp + i * 32);
          uint32_t bad[4];
          float y[4];
#pragma unroll
          for (int i = 0; i < 4; i++) {
            const uint32_t* q = reinterpret_cast<const uint32_t*>(v) + i;
            const float* f = reinterpret_cast<const float*>(v) + i;
            bad[i] = (differ(q[0], q[4], t3) | differ(q[8], q[12], t3)) | (differ(q[16], q[20], t3) | (q[24] ^ t3));
            y[i] = ((f[0] + f[4]) + (f[8] + f[12])) + ((f[16] + f[20]) + f[24]);
          }
          y0 = (up ? y[2] : y[0]) + __shfl_xor_sync(0xffffffffu, up ? y[0] : y[2], 2);
          y1 = (up ? y[3] : y[1]) + __shfl_xor_sync(0xffffffffu, up ? y[1] : y[3], 2);
          if (__all_sync(0xffffffffu, (((bad[0] | bad[1]) | (bad[2] | bad[3])) & 3u) == 0)) break;
        }
#pragma unroll
        for (int m = 4; m <= 16; m <<= 1) { y0 += __shfl_xor_sync(0xffffffffu, y0, m); y1 += __shfl_xor_sync(0xffffffffu, y1, m); }
        asm volatile("{\n.reg .pred p;\nsetp.lt.u32 p, %2, 4;\n@p st.global.u32 [%0], %1;\n}\n" :: "l"(op),
                     "r"(pack_bf16(fmaf(y0, sig, bf_lo(fin.y) + bf_lo(fin.x)), fmaf(y1, sig, bf_hi(fin.y) + bf_hi(fin.x)))), "r"(lane) : "memory");
      }
    }
  } else {
    if (PAD && blockIdx.x == 5000) padn<PAD>();
    asm volatile("setmaxnreg.inc.sync.aligned.u32 160;");
    asm volatile("barrier.sync 0;" ::: "memory");
    {
      const bool leader = (tid & 127) == 0;
      {
        float a0[64], a1[64];
        if (FINE) {
          const uint64_t da = mk_desc(sb + wg * SLOT, 16, 1024, 1), db = mk_desc(sb + 2 * SLOT, 8192, 1024, 1);
          mbar_wait(BAR(B_FKV));
          wg_fence();
          wg_n128<0, 1>(a0, da, db, 0);
          wg_n128<0, 1>(a0, da + 2, db + 128, 1);
          mbar_wait(BAR(B_F0));
          wg_fence();
          wg_n128<0, 1>(a0, da + 4, db + 256, 1);
          wg_n128<0, 1>(a0, da + 6, db + 384, 1);
          mbar_wait(BAR(B_F0 + 1));
          wg_fence();
#pragma unroll
          for (int kk = 0; kk < 4; kk++) wg_n128<0, 1>(a1, da + kk * 2 + 512, db + kk * 128, kk != 0);
          wg_commit();
        }
#pragma unroll 1
        for (int it = FINE; it < 16; it++) {
          mbar_wait(BAR(B_FKV + it));
          const uint32_t s = sb + (uint32_t)(it & 3) * 3 * SLOT;
          const uint64_t da = mk_desc(s + wg * SLOT, 16, 1024, 1), db = mk_desc(s + 2 * SLOT, 8192, 1024, 1);
          wg_fence();
#pragma unroll
          for (int kk = 0; kk < 4; kk++) {
            wg_n128<0, 1>(a0, da + kk * 2, db + kk * 128, (it | kk) != 0);
            wg_n128<0, 1>(a1, da + kk * 2 + 512, db + kk * 128, (it | kk) != 0);
            if (kk == KSPL) {
              wg_commit();
              wg_wait<1>();
              if (it > 0 && leader) mbar_arrive(BAR(B_DKV + it - 1));
              if (kk < 3) wg_fence();
            }
          }
          if (KSPL < 3) wg_commit();
        }
        mbar_wait(BAR(B_STAT));
        wg_fence();
        wg_n128<0, 1>(a0, ext_a(sb, wg * 128), ext_b(sb, 0), 1);
        wg_n128<0, 1>(a1, ext_a(sb, wg * 128 + 64), ext_b(sb, 0), 1);
        wg_commit();
        if (leader) mbar_arrive(BAR(B_QGO));
        mbar_wait(BAR(B_PHI));
        wg_wait<0>();
        if (leader) mbar_arrive(BAR(B_DKV + 15));
        if (PIN & 2) pin_order();
        MMA_IDS
        const uint32_t rs = sb + OFF_RSTAT + (uint32_t)(wg * 128 + lr) * 4;
        const uint32_t vt = sb + 12 * SLOT + wg * 4096 + srow * 64 + (((uint32_t)(lane >> 4) ^ ((srow >> 1) & 3)) << 4);
        float pa[16], pb[16];
        uint32_t vp[16];
        const uint64_t dw = mk_desc(sb + OFF_PHIK, 16, 512, 2);
        auto pack_v = [&](const float* a, int mb) {
          const float r0 = lds_f(rs + mb * 256), r1 = lds_f(rs + mb * 256 + 32);
#pragma unroll
          for (int i = 0; i < 16; i++) vp[i] = pack_bf16(a[32 + 2 * i] * ((i & 1) ? r1 : r0), a[33 + 2 * i] * ((i & 1) ? r1 : r0));
        };
        auto put_v = [&]() {
#pragma unroll
          for (int jj = 0; jj < 4; jj++) stsm_x4((vt + (jj >> 1) * 8192) ^ (32 * (jj & 1)), vp[4 * jj], vp[4 * jj + 1], vp[4 * jj + 2], vp[4 * jj + 3]);
        };
        bar_sync(1, 256);
        pack_v(a0, 0);
        put_v();
        auto logits = [&](const uint32_t (&k)[16]) {
          wg_fence();
          wg_n32_rs<1>(pa, k[0], k[1], k[2], k[3], dw, 0);
          wg_n32_rs<1>(pb, k[8], k[9], k[10], k[11], dw + 128, 0);
          wg_n32_rs<1>(pa, k[4], k[5], k[6], k[7], dw + 64, 1);
          wg_n32_rs<1>(pb, k[12], k[13], k[14], k[15], dw + 192, 1);
          wg_commit();
        };
        uint32_t k0[16], k1[16];
        pin_order();
#pragma unroll
        for (int i = 0; i < 16; i++) k0[i] = pack_pin(a0[2 * i], a0[2 * i + 1]);
        logits(k0);
#pragma unroll
        for (int i = 0; i < 16; i++) k1[i] = pack_pin(a1[2 * i], a1[2 * i + 1]);
        pack_v(a1, 1);
        if (PIN & 1) pin_order();
        wg_wait<0>();
        float kv[20];
        auto half = [&](float (&p0)[16], float (&p1)[16], int mb) {
          const float sc0 = lds_f(rs + mb * 256) * L2E, sc1 = lds_f(rs + mb * 256 + 32) * L2E;
          const uint32_t ft = sb + 10 * SLOT + wg * 8192 + srow * 128 + (sx << 4);
          uint32_t fo[32];
          auto put = [&](int h) {
#pragma unroll
            for (int g = 4 * h; g < 4 * h + 4; g++) stsm_x4((ft + h * SLOT) ^ (32 * (g & 3)), fo[4 * g], fo[4 * g + 1], fo[4 * g + 2], fo[4 * g + 3]);
          };
          float tot;
          {
            tot = feature_fast(p0, sc0, sc1, &fo[0], [&]() {
              if (mb) {
                if (PIN & 128) pin_order();
                wg_wait<0>();
                bar_arrive(6 + wg, 256);
              }
            });
            if (mb) {
              bar_sync(7 - wg, 256);
              put_v();
            }
            put(0);
            tot += feature_fast(p1, sc0, sc1, &fo[16], []() {});
          }
          put(1);
          if (warp_fails(tot < FAST_LIMIT)) {
            feature_shifted(p0, p1, sc0, sc1, fo);
            put(0);
            put(1);
          }
          if (mb == 0) logits(k1);
          fence_async_smem();
          bar_sync(1, 256);
          if (PIN & 4) pin_order();
          const uint64_t d = mk_desc(sb + (10 + wg) * SLOT, 16, 1024, 1);
          const uint64_t e = mk_desc(sb + 12 * SLOT + wg * 8192, OFF_ONES - 12 * SLOT - wg * 8192, 512, 2);
          wg_fence();
#pragma unroll
          for (int kk = 0; kk < 8; kk++) wg_n40<1, 1>(kv, d + kk * 128, e + kk * (64 - (64 << 16)), (mb | kk) != 0);
          wg_commit();
        };
        half(pa, pb, 0);
        wg_wait<1>();
        half(pa, pb, 1);
        mbar_wait(BAR(B_RESET));
        const uint32_t tg = lds_u(sb + OFF_RED + 8);
        uint4* const dst = settle(&g_kvp[2 * hp + wg][rbk][0][tid & 127], lane);
        uint4* const dsz = settle(&g_kvp[2 * hp + wg][rbk][2][(tid & 127) >> 2], lane);
        const int si = warp < 2 ? rbk * 16 + (lane & 15) : rbk * 4 + (lane & 3);
        const uint4* const src = &g_kvp[2 * hp + (lane >> 4)][0][warp][si];
        uint4 a[8];
        if (wg == 0 && warp < 3) {
#pragma unroll
          for (int p = 0; p < 8; p++) a[p] = ld_rec16(src + p * 384);
        }
        pin_order();
        wg_wait<0>();
        if (PIN & 8) pin_order();
        {
          uint32_t w[8];
#pragma unroll
          for (int i = 0; i < 8; i++) w[i] = pack_bf16(kv[2 * i], kv[2 * i + 1]);
          w[0] = with_tag(w[0], tg); w[4] = with_tag(w[4], tg);
          st_rec16(dst, w[0], w[1], w[2], w[3]);
          st_rec16(dst + 128, w[4], w[5], w[6], w[7]);
          st_rec16_if((lane & 3) == 0, dsz, tg, pack_bf16(kv[16], kv[18]), 0u, 0u);
          if (leader) mbar_arrive(BAR(B_KVFREE));
        }
        if (wg == 0 && warp < 3) {
          uint32_t v[4];
          uint4* const red = settle(&g_kvr[2 * hp + (lane >> 4)][warp][si], lane);
#pragma unroll 1
          for (int it = 0; it < SPIN; it++) {
#pragma unroll
            for (int p = 0; p < 8; p++) ld_rec16_stale(a[p], src + p * 384, tg);
            const uint32_t bad = (differ(a[0].x, a[1].x, tg) | differ(a[2].x, a[3].x, tg)) | (differ(a[4].x, a[5].x, tg) | differ(a[6].x, a[7].x, tg));
#pragma unroll
            for (int i = 0; i < 4; i++) {
              const uint32_t* q = reinterpret_cast<const uint32_t*>(a) + i;
              if (KSUM) v[i] = hadd2(hadd2(hadd2(q[0], q[4]), hadd2(q[8], q[12])), hadd2(hadd2(q[16], q[20]), hadd2(q[24], q[28])));
            }
            if (__all_sync(0xffffffffu, (bad & OTAG) == 0)) break;
          }
          if (!KSUM) {
#pragma unroll
            for (int i = 0; i < 4; i++) {
              const uint32_t* q = reinterpret_cast<const uint32_t*>(a) + i;
              const uint32_t c0 = hadd2(q[0], q[4]), c1 = hadd2(q[8], q[12]), c2 = hadd2(q[16], q[20]), c3 = hadd2(q[24], q[28]);
              v[i] = pack_bf16((bf_lo(c0) + bf_lo(c1)) + (bf_lo(c2) + bf_lo(c3)), (bf_hi(c0) + bf_hi(c1)) + (bf_hi(c2) + bf_hi(c3)));
            }
          }
          st_rec16(red, with_tag(v[0], tg), v[1], v[2], v[3]);
        }
      }
    }
    const uint32_t stg = sb + wg * 8192;
    uint4* hsrc;
    int trow;
    {
      MMA_IDS
      const unsigned tag = lds_u(sb + OFF_RED + 4);
      const uint32_t tg = lds_u(sb + OFF_RED + 8);
      const uint32_t ln = __shfl_sync(0xffffffffu, (uint32_t)lane, lane);
      uint4* const og = &g_o[rb][0][wg * 4 + warp][0][ln];
      const uint32_t af = sb + (uint32_t)(wg * 4 + warp) * 2048 + ln * 16;
      float acc[64];
      auto tile_addr = [&]() {
        uint32_t l = ln;
        asm volatile("" : "+r"(l));
        return stg + (uint32_t)warp * 2048 + (l & 15) * 128 + (((l >> 4) ^ (l & 7)) << 4);
      };
      auto add_x = [&]() {
        mbar_wait(BAR(B_FQ + 14));
        mbar_wait(BAR(B_FQ + 15));
        const uint64_t da = mk_desc(sb + OFF_EYE + 384, 512, 128, 0), db = mk_desc(stg + SLOT, 7 * SLOT, 4096, 1);
        wg_fence();
#pragma unroll
        for (int s = 0; s < 4; s++) wg_n128<0, 1>(acc, da - s * 8, db + s * 64, s != 0);
        wg_commit();
      };
      auto announce = [&]() {
        if (warp == FLAGW && ln < 8) asm volatile("st.relaxed.gpu.global.u32 [%0], %1;" :: "l"(&g_oflag[rb][ln][cb * 2 + wg].x), "r"(tag) : "memory");
      };
      auto send = [&](const uint32_t (&a)[16], uint32_t flip, uint32_t slot, int c) {
#pragma unroll
        for (int i = 0; i < 4; i++) sts_u4(af + slot * SLOT + i * 512, a[4 * i] ^ flip, a[4 * i + 1], a[4 * i + 2], a[4 * i + 3]);
        fence_async_smem();
        __syncwarp();
        if (ln == 0) {
          asm volatile("cp.async.bulk.global.shared::cta.bulk_group [%0], [%1], 2048;" :: "l"(og + cb * 2048 + c * 1024), "r"(af + slot * SLOT) : "memory");
          asm volatile("cp.async.bulk.commit_group;" ::: "memory");
        }
        __syncwarp();
      };
      auto take = [&](uint32_t (&a)[16], int j) {
        const uint32_t s = af + tab4(PC_ASLOTS, j) * SLOT;
#pragma unroll
        for (int i = 0; i < 4; i++) {
          const uint4 v = lds_u4(s + i * 512);
          a[4 * i] = v.x; a[4 * i + 1] = v.y; a[4 * i + 2] = v.z; a[4 * i + 3] = v.w;
        }
      };
      auto check = [&](uint32_t (&a)[16], int j) {
        if (PIN & 256) pin_order();
#pragma unroll
        for (int i = 0; i < 4; i++) a[4 * i] ^= tg;
        if (!(SKIP & 2) && warp_fails((((a[0] | a[4]) | (a[8] | a[12])) & OTAG) == 0)) {
          const uint4* p = og + pc_chunk(j, cb) * 1024;
#pragma unroll 1
          for (int it = 0; it < SPIN; it++) {
#pragma unroll
            for (int i = 0; i < 4; i++) {
              const uint4 v = ld_rec16(p + i * 32);
              a[4 * i] = v.x ^ tg; a[4 * i + 1] = v.y; a[4 * i + 2] = v.z; a[4 * i + 3] = v.w;
            }
            if (__all_sync(0xffffffffu, (((a[0] | a[4]) | (a[8] | a[12])) & OTAG) == 0)) break;
          }
        }
      };
      auto project = [&](const uint32_t (&a)[16], int k0, uint64_t db) {
        wg_fence();
#pragma unroll
        for (int kk = k0; kk < k0 + 2; kk++) wg_n128_rs<1>(acc, a[4 * kk], a[4 * kk + 1], a[4 * kk + 2], a[4 * kk + 3], db + kk * 128, 1);
        wg_commit();
      };
      const bool early = !((LATE >> cb) & 1);
      uint32_t A[2][16];
      float u3[20];
      const bool lead = warp == 0 && ln == 0;
      {
        const float sc0 = lds_f(sb + OFF_RSTAT + (uint32_t)(wg * 64 + lr) * 4) * L2E, sc1 = lds_f(sb + OFF_RSTAT + (uint32_t)(wg * 64 + lr + 8) * 4) * L2E;
        auto logits = [&](float (&p0)[16], float (&p1)[16], int c) {
          const uint64_t dq = mk_desc(sb + (10 + c) * SLOT + wg * 8192, 16, 1024, 1), dw = mk_desc(sb + OFF_PHIQ + c * 4096, 16, 512, 2);
          mbar_wait(BAR(B_QD + c + 3 * wg));
          wg_fence();
          wg_n32<0, 1>(p0, dq, dw, 0);
          wg_n32<0, 1>(p1, dq + 4, dw + 128, 0);
          wg_n32<0, 1>(p0, dq + 2, dw + 64, 1);
          wg_n32<0, 1>(p1, dq + 6, dw + 192, 1);
          wg_commit();
        };
        auto norm = [&](float (&p)[16], uint32_t (&f)[16], const float (&d)[4]) {
          if (warp_fails(feature_norm<false>(f, d) < FAST_LIMIT)) feature_shifted(p, p, sc0, sc1, f);
        };
        auto apply = [&](float (&u)[20], const uint32_t (&f)[16], int h) {
          const uint64_t d = mk_desc(sb + 12 * SLOT + h * 4096, SLOT - h * 4096 + h * 16, 512, 2);
          wg_fence();
#pragma unroll
          for (int s = 0; s < 4; s++) wg_n40_rs<1>(u, f[4 * s], f[4 * s + 1], f[4 * s + 2], f[4 * s + 3], d + s * 64, s != 0);
          wg_commit();
        };
        float pa[16], pb[16], pc[16], pd[16], u0[20], u1[20], u2[20], da[4], db[4];
        uint32_t f0[16], f1[16], f2[16], f3[16];
        uint4* const od = og + cb * 2048;
        logits(pa, pb, 0);
        wg_wait<0>();
        feature_exp(pa, sc0, sc1, f0, da, sum_b(sb));
        if (PIN & 64) pin_order();
        logits(pc, pd, 1);
        feature_exp(pb, sc0, sc1, f1, db, sum_b(sb));
        wg_wait<1>();
        norm(pa, f0, da);
        feature_exp(pc, sc0, sc1, f2, da, sum_b(sb));
        wg_wait<1>();
        norm(pb, f1, db);
        wg_wait<0>();
        if (lead) mbar_arrive(BAR(B_QREAD));
        norm(pc, f2, da);
        mbar_wait(BAR(B_KVRDY));
        apply(u0, f0, 0);
        apply(u1, f1, 1);
        wg_wait<1>();
        attn_out(u0, tg, &A[0][0], od, early);
        if (early) announce();
        wg_wait<0>();
        apply(u2, f2, 2);
        attn_out(u1, tg, &A[0][8], od + 64, early);
        if (PIN & 16) pin_order();
        feature_exp(pd, sc0, sc1, f3, db, sum_b(sb));
        wg_wait<1>();
        attn_out(u2, tg, &A[1][0], od + 1024, false);
        wg_wait<0>();
        norm(pd, f3, db);
        apply(u3, f3, 3);
        add_x();
        wg_wait<1>();
        if (lead) mbar_arrive(BAR(B_XDONE));
      }
      {
#pragma unroll
        for (int i = 0; i < 4; i++) A[0][4 * i] ^= tg;
        uint32_t bt = (uint32_t)mk_desc(sb + 3 * SLOT, 8192, 1024, 1);
        const uint32_t bl = bt + 4096;
        uint2 dl = make_uint2(0u, 0u), dn = dl;
#pragma unroll 1
        for (int m = 0; m < 16; m += 4) {
#pragma unroll
          for (int e = 0; e < 4; e++) {
            const int j = m + e;
            mbar_wait(BAR(B_FB + j) + dl.x);
            const uint64_t db = (mk_desc(0, 0, 1024, 1)) | (bt + dl.y);
            project(A[e & 1], 0, db);
            if (e == 0 && m == 0) {
              if (!early) {
#pragma unroll
                for (int i = 0; i < 4; i++) st_rec16(og + cb * 2048 + i * 32, A[0][4 * i] ^ tg, A[0][4 * i + 1], A[0][4 * i + 2], A[0][4 * i + 3]);
                announce();
              }
              attn_out(u3, tg, &A[1][8], og, false);
            }
            wg_wait<1>();
            if (lead) mbar_arrive(BAR(j ? B_DC + j - 1 : B_XREAD));
            if (e || m) {
              if (e < 3 || m < 12) mbar_wait<1>(BAR(B_FKV + j + 1));
              take(A[(e & 1) ^ 1], (e + 1) & 3);
              if (DYN) dn = lds_u2(sb + OFF_RED + 72 + j * 8);
            }
            if (e == 1 && m == 0) {
              mbar_wait(BAR(B_XDONE));
              send(A[1], tg, 12, 1);
            }
            if (e == 3) asm volatile("cp.async.bulk.wait_group.read 0;" ::: "memory");
            project(A[e & 1], 2, db);
            asm volatile("{\n.reg .pred p;\nsetp.eq.u32 p, %0, %1;\nadd.u32 %0, %0, 1024;\n@p sub.u32 %0, %0, 5120;\n}\n" : "+r"(bt) : "r"(bl));
            dl = dn;
            if (e < 3 || m < 12) check(A[(e & 1) ^ 1], j + 1 + ((int)dl.x >> 3));
          }
        }
      }
      uint4 wb[4];
#pragma unroll
      for (int i = 0; i < 4; i++) wb[i] = lds_u4(sb + ((ln & 4) ? OFF_ONES : OFF_WR + (ln & 3) * 64) + i * 16);
      mbar_wait(BAR(B_RESET2));
      wg_wait<0>();
      if (lead) mbar_arrive(BAR(B_DC + 15));
      uint32_t hp2[8][4];
      float ds[8], q[4];
#pragma unroll 1
      for (int rep = 0; rep < 1; rep++) {
#pragma unroll
      for (int i = 0; i < 8; i++) ds[i] = q[i & 3] = 0.f;
#pragma unroll
      for (int k = 0; k < 8; k++) {
#pragma unroll
        for (int i = 0; i < 4; i++) hp2[k][i] = pack_pin(acc[8 * k + 2 * i], acc[8 * k + 2 * i + 1]);
        mma_bf16(&ds[(k & 1) * 4], hp2[k], (k & 1) ? wb[k >> 1].z : wb[k >> 1].x, (k & 1) ? wb[k >> 1].w : wb[k >> 1].y);
#pragma unroll
        for (int i = SQN * k; i < SQN * (k + 1) && i < 64; i++) asm volatile("fma.rn.f32 %0, %1, %1, %0;" : "+f"(q[i & 3]) : "f"(acc[i]));
      }
#pragma unroll
      for (int i = SQN * 8; i < 64; i++) asm volatile("fma.rn.f32 %0, %1, %1, %0;" : "+f"(q[i & 3]) : "f"(acc[i]));
      const bool hi = ln & 1;
      q[0] += q[1]; q[2] += q[3];
      q[0] = (hi ? q[2] : q[0]) + __shfl_xor_sync(0xffffffffu, hi ? q[0] : q[2], 1);
      q[0] += __shfl_xor_sync(0xffffffffu, q[0], 2);
      st_rec16_if(((ln >> 1) & 1) == (cb >> 2), og + 16384 + (cb & 3) * 32, __float_as_uint((hi ? ds[3] : ds[1]) + (hi ? ds[7] : ds[5])), __float_as_uint(q[0]),
                  __float_as_uint((hi ? ds[2] : ds[0]) + (hi ? ds[6] : ds[4])), tag);
      }
      pin_order();
      hsrc = og + 16384;
      trow = rb * 128 + wg * 64 + warp * 16 + (ln >> 2) + (ln & 1) * 8;
      const uint32_t ha = tile_addr();
#pragma unroll
      for (int jj = 0; jj < 8; jj++) stsm_x4((ha ^ (32 * (jj & 3))) + (jj >> 2) * 2 * SLOT, hp2[jj][0], hp2[jj][1], hp2[jj][2], hp2[jj][3]);
    }
    asm volatile("setmaxnreg.dec.sync.aligned.u32 %0;" :: "n"(TREG));
    {
    const int tid = fresh_tid(), lane = tid & 31;
    const unsigned tag = lds_u(sb + OFF_RED + 4);
    const float sumw = lds_f(sb + OFF_RED);
    uint2* const kp = settle(&g_key[cb][0][rb * 4], lane);
    uint32_t key;
    {
      uint4 r[4];
#pragma unroll 1
      for (int it = 0; it < SPIN; it++) {
#pragma unroll
        for (int i = 0; i < 4; i++) r[i] = ld_rec16(hsrc + i * 32);
        if (__all_sync(0xffffffffu, r[0].w == tag && r[1].w == tag && r[2].w == tag && r[3].w == tag)) break;
      }
      float s = (__uint_as_float(r[0].x) + __uint_as_float(r[1].x)) + (__uint_as_float(r[2].x) + __uint_as_float(r[3].x));
      float q = (__uint_as_float(r[0].y) + __uint_as_float(r[1].y)) + (__uint_as_float(r[2].y) + __uint_as_float(r[3].y));
      float d = (__uint_as_float(r[0].z) + __uint_as_float(r[1].z)) + (__uint_as_float(r[2].z) + __uint_as_float(r[3].z));
      s += __shfl_xor_sync(0xffffffffu, s, 2); q += __shfl_xor_sync(0xffffffffu, q, 2); d += __shfl_xor_sync(0xffffffffu, d, 2);
      const float mean = s * (1.f / DM);
      const float rstd = rsq(fmaxf(fmaf(-mean, mean, q * (1.f / DM)), 0.f) + 1e-5f);
      const uint32_t u = __float_as_uint(rstd * fmaf(-mean, sumw, d));
      key = ((u ^ ((uint32_t)((int)u >> 31) | 0x80000000u)) & ~(uint32_t)(SEQ - 1)) | (uint32_t)trow;
      asm volatile("red.shared.max.u32 [%0], %1;" :: "r"(sb + OFF_RED + 16), "r"(key) : "memory");
      if ((lane & 2) == 0) sts_f2(sb + OFF_RSTAT + (trow & 127) * 8, rstd, -mean * rstd);
      bar_sync(1, 256);
      key = lds_u(sb + OFF_RED + 16 + (trow >> 20));
    }
    if (tid == 0) { st_rec8(kp, key, tag); mbar_arrive(BAR(B_KEY)); }
    const int crow = key & 127;
    const bool own = (crow >> 4) == wg * 4 + warp;
    uint32_t co0 = 0, co1 = 0;
    if (own) {
      const uint32_t r = (uint32_t)(crow & 63);
      const float2 st = lds_f2(sb + OFF_RSTAT + crow * 8);
      const uint32_t a = stg + r * 128 + ((((uint32_t)lane >> 2) ^ (r & 7)) << 4) + (lane & 3) * 4;
      const uint32_t h0 = lds_u(a), h1 = lds_u(a + 2 * SLOT);
      uint32_t n0, n1;
      co0 = ln_res(h0, st.x, st.y, n0); co1 = ln_res(h1, st.x, st.y, n1);
      uint4* const cx = hsrc + (cb * 32 + 1024 - (crow >> 4) * 128);
      st_rec16(cx, n0, n1, key, tag);
      st_rec16(cx + 256 + cb * 32, n0, h0, key, tag);
      st_rec16(cx + 288 + cb * 32, n1, h1, key, tag);
    }
    __nv_bfloat16* ob = P.out + (size_t)(rb * 128 + wg * 64) * DM + cb * 128;
#pragma unroll 4
    for (int i = 0; i < 8; i++) {
      const uint32_t r = (uint32_t)(warp * 16 + (i & 3) * 4 + (lane >> 3));
      const uint32_t a = stg + (i >> 2) * 2 * SLOT + r * 128 + ((((uint32_t)lane & 7) ^ (r & 7)) << 4);
      const uint4 h = lds_u4(a);
      const float2 st = lds_f2(sb + OFF_RSTAT + ((tid >> 7) * 64 + r) * 8);
      uint32_t n;
      uint4 o;
      o.x = ln_res(h.x, st.x, st.y, n); o.y = ln_res(h.y, st.x, st.y, n); o.z = ln_res(h.z, st.x, st.y, n); o.w = ln_res(h.w, st.x, st.y, n);
      if (!own) sts_u4(a, o.x, o.y, o.z, o.w);
      else if ((int)r != (crow & 63)) stg16(ob + (size_t)r * DM + (i >> 2) * 64 + (lane & 7) * 8, o);
      if ((i & 3) == 3) {
        fence_async_smem();
        __syncwarp();
        if (OUTG == 1 ? i == 7 : OUTG == 2 ? i == 3 : OUTG == 3 ? i == 7 || wg : OUTG == 4 ? i == 7 && wg : false) mbar_wait(BAR(B_ROW));
        if (elect()) {
          if (!own) tma_store_2d(&P.mOut, stg + (i >> 2) * 2 * SLOT + warp * 2048, cb * 128 + (i >> 2) * 64, rb * 128 + wg * 64 + warp * 16);
          asm volatile("cp.async.bulk.commit_group;" ::: "memory");
        }
        __syncwarp();
      }
    }
    if (elect()) {
      asm volatile("cp.async.bulk.wait_group.read 0;" ::: "memory");
    }
    __syncwarp();
    if (own) {
      uint2 v;
#pragma unroll 1
      for (int it = 0; it < SPIN; it++) {
        v = ld_rec8(&g_key[cb][0][(lane & 15) * 4]);
        if (__all_sync(0xffffffffu, v.y == tag)) break;
      }
      if (__reduce_max_sync(0xffffffffu, v.x) != key) {
        uint32_t* op = reinterpret_cast<uint32_t*>(ob + (size_t)(crow & 63) * DM);
        op[lane] = co0; op[32 + lane] = co1;
      }
    }
    }
  }
#undef BAR
}

typedef CUresult (*EncodeFn)(CUtensorMap*, CUtensorMapDataType, cuuint32_t, void*, const cuuint64_t*, const cuuint64_t*,
                             const cuuint32_t*, const cuuint32_t*, CUtensorMapInterleave, CUtensorMapSwizzle,
                             CUtensorMapL2promotion, CUtensorMapFloatOOBfill);

void make_map(EncodeFn fn, CUtensorMap* m, const void* ptr, uint64_t cols, uint64_t rows, uint32_t bc, uint32_t br, CUtensorMapSwizzle swz,
              uint32_t parts = 0, uint32_t bp = 1) {
  cuuint64_t dims[3] = {parts ? cols / parts : cols, rows, parts};
  cuuint64_t strides[2] = {cols * 2, dims[0] * 2};
  cuuint32_t box[3] = {bc, br, bp};
  cuuint32_t es[3] = {1, 1, 1};
  fn(m, CU_TENSOR_MAP_DATA_TYPE_BFLOAT16, parts ? 3 : 2, const_cast<void*>(ptr), dims, strides, box, es, CU_TENSOR_MAP_INTERLEAVE_NONE, swz,
     CU_TENSOR_MAP_L2_PROMOTION_L2_128B, CU_TENSOR_MAP_FLOAT_OOB_FILL_NONE);
}

}

extern "C" void kernel_launch(void* const* d_in, const int* in_sizes, int n_in, void* d_out, int out_size) {
  static EncodeFn fn = nullptr;
  if (!fn) {
    cudaDriverEntryPointQueryResult q;
    cudaGetDriverEntryPoint("cuTensorMapEncodeTiled", (void**)&fn, cudaEnableDefault, &q);
    cudaFuncSetAttribute(fused_kernel, cudaFuncAttributeMaxDynamicSharedMemorySize, SMEM_BYTES);
  }
  Params P;
  P.x = (const __nv_bfloat16*)d_in[0];
  P.wqkv = (const __nv_bfloat16*)d_in[1];
  const __nv_bfloat16* wphi = (const __nv_bfloat16*)d_in[2];
  P.wo = (const __nv_bfloat16*)d_in[3];
  P.wr = (const __nv_bfloat16*)d_in[5];
  P.wg = (const __nv_bfloat16*)d_in[6];
  P.wu = (const __nv_bfloat16*)d_in[7];
  P.wd = (const __nv_bfloat16*)d_in[8];
  P.out = (__nv_bfloat16*)d_out;
  make_map(fn, &P.mX, P.x, DM, SEQ, 64, 128, CU_TENSOR_MAP_SWIZZLE_128B);
  make_map(fn, &P.mW, P.wqkv, 3 * DM, DM, 64, 64, CU_TENSOR_MAP_SWIZZLE_128B);
  make_map(fn, &P.mX2, P.x, DM, SEQ, 64, 64, CU_TENSOR_MAP_SWIZZLE_128B);
  make_map(fn, &P.mW2, P.wqkv, 3 * DM, DM, 64, 32, CU_TENSOR_MAP_SWIZZLE_128B);
  make_map(fn, &P.mWo, P.wo, DM, DM, 64, 64, CU_TENSOR_MAP_SWIZZLE_128B);
  make_map(fn, &P.mPhi, wphi, 32, 1024, 32, 64, CU_TENSOR_MAP_SWIZZLE_64B);
  make_map(fn, &P.mWg, P.wg, FF, DM, 32, 256, CU_TENSOR_MAP_SWIZZLE_64B, 1);
  make_map(fn, &P.mWu, P.wu, FF, DM, 32, 256, CU_TENSOR_MAP_SWIZZLE_64B, 1);
  make_map(fn, &P.mWs, P.wqkv, 3 * DM, DM, 32, 64, CU_TENSOR_MAP_SWIZZLE_NONE);
  make_map(fn, &P.mWd, P.wd, DM, FF, 64, 32, CU_TENSOR_MAP_SWIZZLE_128B, 16, 4);
  make_map(fn, &P.mOut, P.out, DM, SEQ, 64, 16, CU_TENSOR_MAP_SWIZZLE_128B);
  make_map(fn, &P.mWgT, P.wg, FF, DM, 8, TROWS, CU_TENSOR_MAP_SWIZZLE_NONE);
  make_map(fn, &P.mWuT, P.wu, FF, DM, 8, TROWS, CU_TENSOR_MAP_SWIZZLE_NONE);
  make_map(fn, &P.mWdT, P.wd, 64, FF * 16, 8, TROWS, CU_TENSOR_MAP_SWIZZLE_NONE);
  fused_kernel<<<NCTA, NTHREADS, SMEM_BYTES, cudaStreamPerThread>>>(P);
}
```
